```python
import torch

def _softmax(x, axis=-1):
    return torch.softmax(x, dim=axis)

def _gelu(x):
    return torch.nn.functional.gelu(x, approximate='tanh')

def _silu(x):
    return torch.nn.functional.silu(x)

def _sigmoid(x):
    return torch.sigmoid(x)

def _layernorm(x, axis=-1, eps=1e-05):
    m = x.mean(dim=axis, keepdim=True)
    v = x.var(dim=axis, keepdim=True, unbiased=False)
    return (x - m) / torch.sqrt(v + eps)

def _scatter_add(tgt, idx, src, axis=0):
    return tgt.clone().index_add_(axis, idx, src)

def _segment_sum(src, seg, n):
    out = torch.zeros((n,) + src.shape[1:], dtype=src.dtype)
    return out.index_add_(0, seg, src)

def _pad(x, pw):
    flat = tuple((v for pair in reversed(pw) for v in pair))
    return torch.nn.functional.pad(x, flat)
kernel_name = 'adaLN_cond__spectral_fnet__moe_arch_mod__prompt'

def setup_inputs():

    _w = lambda a: (lambda t: t.to(torch.bfloat16) if t.is_floating_point() else t)(torch.as_tensor(a))

    def _A_setup():
        B, S, D = (1, 2048, 1024)
        ns = torch.arange(S)[:, None] * torch.arange(S)[None, :]
        nd = torch.arange(D)[:, None] * torch.arange(D)[None, :]
        Ws_re = torch.cos(-2.0 * torch.pi * ns / S).to(float)
        Ws_im = torch.sin(-2.0 * torch.pi * ns / S).to(float)
        Wd_re = torch.cos(-2.0 * torch.pi * nd / D).to(float)
        Wd_im = torch.sin(-2.0 * torch.pi * nd / D).to(float)
        return {'x': _w((lambda *s: torch.randn(*s, dtype=torch.bfloat16) * 0.1)(B, S, D)), 'dft_seq_re': _w(Ws_re), 'dft_seq_im': _w(Ws_im), 'dft_hid_re': _w(Wd_re), 'dft_hid_im': _w(Wd_im)}
    _A_in = _A_setup()

    def _B_setup():
        B, S, D, F, C = (1, 2048, 1024, 3584, 2)
        return {'x': _w((lambda *s: torch.randn(*s, dtype=torch.bfloat16) * 0.1)(B, S, D)), 'w_r': _w((lambda *s: torch.randn(*s, dtype=torch.bfloat16) * 1.6)(D)), 'w_gate': _w((lambda *s: torch.randn(*s, dtype=torch.bfloat16) * 0.8)(D, F)), 'w_up': _w((lambda *s: torch.randn(*s, dtype=torch.bfloat16) * 0.8)(D, F)), 'w_down': _w((lambda *s: torch.randn(*s, dtype=torch.bfloat16) * 0.8)(F, D))}
    _B_in = _B_setup()
    return {'A_x': _A_in['x'], 'A_dft_seq_re': _A_in['dft_seq_re'], 'A_dft_seq_im': _A_in['dft_seq_im'], 'A_dft_hid_re': _A_in['dft_hid_re'], 'A_dft_hid_im': _A_in['dft_hid_im'], 'B_x': _B_in['x'], 'B_w_r': _B_in['w_r'], 'B_w_gate': _B_in['w_gate'], 'B_w_up': _B_in['w_up'], 'B_w_down': _B_in['w_down'], 'c': _w((lambda *s: torch.randn(*s, dtype=torch.bfloat16) * 0.1)(1, 1024) * 8.0), 'w_mod': _w((lambda *s: torch.randn(*s, dtype=torch.bfloat16) * 0.1)(1024, 6 * 1024) * 1024 ** (-0.5) * 8.0)}

def reference(A_x, A_dft_seq_re, A_dft_seq_im, A_dft_hid_re, A_dft_hid_im, B_x, B_w_r, B_w_gate, B_w_up, B_w_down, c, w_mod):

    def _A_ref(x, dft_seq_re, dft_seq_im, dft_hid_re, dft_hid_im):
        a = torch.einsum('bsd,ed->bse', x, dft_hid_re)
        b = torch.einsum('bsd,ed->bse', x, dft_hid_im)
        y = torch.einsum('ts,bse->bte', dft_seq_re, a) - torch.einsum('ts,bse->bte', dft_seq_im, b)
        return y

    def _B_ref(x, w_r, w_gate, w_up, w_down):
        B, S, D = x.shape
        C = 2
        r = x @ w_r
        idx = torch.argsort(-r, axis=-1)[:, :C]
        idx_e = (lambda x, n, axis: torch.repeat_interleave(x, n, dim=axis))(idx.reshape(B, C, 1), D, axis=2)
        x_sel = (lambda x, i, axis: torch.take_along_dim(x, i, dim=axis))(x, idx_e, axis=1)
        g = _silu(x_sel @ w_gate)
        u = x_sel @ w_up
        y = g * u @ w_down
        r_sel = _sigmoid((lambda x, i, axis: torch.take_along_dim(x, i, dim=axis))(r, idx, axis=1))
        y = y * r_sel.reshape(B, C, 1)
        b_off = (torch.arange(B) * S).reshape(B, 1)
        flat_idx = (idx + b_off).reshape(B * C)
        zero = (x * 0.0).reshape(B * S, D)
        upd = _scatter_add(zero, flat_idx, y.reshape(B * C, D), axis=0)
        return x + upd.reshape(B, S, D)
    x = A_x
    mod = (_silu(c) @ w_mod).reshape(c.shape[0], 6, 1, -1)
    sa, ca, ga, sb, cb, gb = (mod[:, 0].clone(), mod[:, 1].clone(), mod[:, 2].clone(), mod[:, 3].clone(), mod[:, 4].clone(), mod[:, 5].clone())
    h = _layernorm(x, axis=-1) * (1 + ca) + sa
    x = x + ga * _A_ref(h, A_dft_seq_re, A_dft_seq_im, A_dft_hid_re, A_dft_hid_im)
    h = _layernorm(x, axis=-1) * (1 + cb) + sb
    x = x + gb * _B_ref(h, B_w_r, B_w_gate, B_w_up, B_w_down)
    return x
```

```cpp
#include <cuda_runtime.h>
#include <cuda_bf16.h>
#include <cuda.h>
#include <stdint.h>

#define DEVINL __device__ __forceinline__

namespace fk {

constexpr int S_ = 2048, D_ = 1024, F_ = 3584;
constexpr int NCTA = 128;
constexpr int NMOE = 112;
constexpr int SLOT = 16384;
constexpr int STAGE = 3 * SLOT;
constexpr int SP_OFF = 4 * STAGE;
constexpr int MISC_OFF = SP_OFF + 32768;
constexpr int SMEM_BYTES = MISC_OFF + 3072;
constexpr int BAR_OFF = MISC_OFF;
constexpr int SEL_OFF = MISC_OFF + 256;
constexpr int CST_OFF = MISC_OFF + 272;
constexpr int TOP_OFF = MISC_OFF + 288;
constexpr int TAB_OFF = MISC_OFF + 512;
constexpr int LNS_OFF = SP_OFF;
constexpr int SILU_OFF = SP_OFF + 4096;
constexpr int WM_OFF = SP_OFF + 8192;
constexpr int RKA_OFF = SP_OFF + 24576;
constexpr int RKB_OFF = RKA_OFF + 2048;
constexpr int RED_OFF = RKB_OFF + 2048;
constexpr int UP0_OFF = 3 * STAGE + 2 * SLOT + 8192;

enum { B_FULL = 0, B_EMPTY = 4, B_PREADY = 8, B_MF = 12, B_RSDONE = 16, B_RESET = 17, B_WFULL = 18, B_UP = 20, B_DN = 21,
       B_TAB = 22, B_HIALL = 23, B_PEER = 24, B_RECV = 25  , B_SEL = 27, B_WFREE = 28   };
constexpr unsigned long long CNT_LO = 0x1111888833331111ull, CNT_HI = 0x1188111221131111ull;

#define FK_G0 20
#define FK_GW 9
#define FK_PDELAY 500
constexpr int SPIN_LIMIT = 1 << 20;
constexpr uint32_t SENT = 0xFFFFFFFFu;

struct Scratch {
  uint4 part[128 * 128 * 4];
  uint4 stats[128 * 128];
  uint4 rowsH[32 * 128];
  uint4 rowsB[32 * 128];
  uint4 cand[16 * 8];
  uint2 rs[2 * S_];
  float mod[6 * D_];
  float u[2 * D_];
  unsigned flagP[128 * 4 * 8];
  unsigned cntN[32 * 32];
  unsigned cntW[8 * 32];
  unsigned cntMod[32];
  unsigned epoch[32];
  alignas(1024) __nv_bfloat16 n[S_ * D_];
  __nv_bfloat16 W2[2 * D_ * D_];
  __nv_bfloat16 P[2 * S_ * D_];
};
__device__ __align__(1024) Scratch g_scr;

struct Params {
  CUtensorMap ws[2];
  CUtensorMap n;
  CUtensorMap wm;
  CUtensorMap p;
  CUtensorMap w2;
  CUtensorMap wg, wu;
  CUtensorMap wdn;
  const __nv_bfloat16* w_r;
};

DEVINL uint32_t smem_u32(const void* p) { return (uint32_t)__cvta_generic_to_shared(p); }
DEVINL void mbar_init(uint32_t bar, uint32_t cnt) { asm volatile("mbarrier.init.shared::cta.b64 [%0], %1;" ::"r"(bar), "r"(cnt) : "memory"); }
DEVINL void mbar_expect_tx(uint32_t bar, uint32_t bytes) { asm volatile("mbarrier.arrive.expect_tx.shared::cta.b64 _, [%0], %1;" ::"r"(bar), "r"(bytes) : "memory"); }
DEVINL void mbar_arrive(uint32_t bar) { asm volatile("mbarrier.arrive.shared::cta.b64 _, [%0];" ::"r"(bar) : "memory"); }
DEVINL void mbar_wait(uint32_t bar, uint32_t parity) {
  asm volatile("{\n.reg .pred p;\n.reg .u32 c;\nmov.u32 c, 0;\n"
               "LW:\nmbarrier.try_wait.parity.shared::cta.b64 p, [%0], %1;\n@p bra LD;\n"
               "add.u32 c, c, 1;\nsetp.lt.u32 p, c, 1048576;\n@p bra LW;\ntrap;\nLD:\n}" ::"r"(bar), "r"(parity) : "memory");
}
DEVINL void mbar_wait_cluster(uint32_t bar, uint32_t parity) {
  asm volatile("{\n.reg .pred p;\n.reg .u32 c;\nmov.u32 c, 0;\n"
               "LW:\nmbarrier.try_wait.parity.acquire.cluster.shared::cta.b64 p, [%0], %1;\n@p bra LD;\n"
               "add.u32 c, c, 1;\nsetp.lt.u32 p, c, 1048576;\n@p bra LW;\ntrap;\nLD:\n}" ::"r"(bar), "r"(parity) : "memory");
}
#define SPIN_CHECK(it) if (++(it) > SPIN_LIMIT) __trap()
DEVINL void fence_async_smem() { asm volatile("fence.proxy.async.shared::cta;" ::: "memory"); }
DEVINL void fence_async_global() { asm volatile("fence.proxy.async.global;" ::: "memory"); }
DEVINL void fence_gpu() { asm volatile("fence.acq_rel.gpu;" ::: "memory"); }
template <int ID, int N> DEVINL void named_bar() { asm volatile("bar.sync %0, %1;" ::"n"(ID), "n"(N) : "memory"); }
DEVINL bool elect_one() { uint32_t p; asm volatile("{\n.reg .pred e;\nelect.sync _|e, 0xffffffff;\nselp.u32 %0, 1, 0, e;\n}" : "=r"(p)); return p; }
DEVINL unsigned clk32() { unsigned c; asm volatile("mov.u32 %0, %%clock;" : "=r"(c)); return c; }
DEVINL void spin(unsigned n) { const unsigned c = clk32(); while (clk32() - c < n) {} }

DEVINL void tma_2d(uint32_t dst, const CUtensorMap* m, int x, int y, uint32_t bar) {
  asm volatile("cp.async.bulk.tensor.2d.shared::cluster.global.mbarrier::complete_tx::bytes [%0], [%1, {%3, %4}], [%2];"
               ::"r"(dst), "l"(m), "r"(bar), "r"(x), "r"(y) : "memory");
}
DEVINL void tma_2d_hint(uint32_t dst, const CUtensorMap* m, int x, int y, uint32_t bar, uint64_t pol) {
  asm volatile("cp.async.bulk.tensor.2d.shared::cluster.global.mbarrier::complete_tx::bytes.L2::cache_hint [%0], [%1, {%3, %4}], [%2], %5;"
               ::"r"(dst), "l"(m), "r"(bar), "r"(x), "r"(y), "l"(pol) : "memory");
}
DEVINL void tma_3d(uint32_t dst, const CUtensorMap* m, int y, int z, uint32_t bar) {
  asm volatile("cp.async.bulk.tensor.3d.shared::cluster.global.mbarrier::complete_tx::bytes [%0], [%1, {0, %3, %4}], [%2];"
               ::"r"(dst), "l"(m), "r"(bar), "r"(y), "r"(z) : "memory");
}
DEVINL void tma_5d(uint32_t dst, const CUtensorMap* m, int x, int a, uint32_t bar) {
  asm volatile("cp.async.bulk.tensor.5d.shared::cluster.global.mbarrier::complete_tx::bytes [%0], [%1, {%3, 0, 0, 0, %4}], [%2];"
               ::"r"(dst), "l"(m), "r"(bar), "r"(x), "r"(a) : "memory");
}
DEVINL void tma_store_2d(const CUtensorMap* m, uint32_t src, int x, int y) {
  asm volatile("cp.async.bulk.tensor.2d.global.shared::cta.bulk_group [%0, {%2, %3}], [%1];" ::"l"(m), "r"(src), "r"(x), "r"(y) : "memory");
}
DEVINL void pf_3d(const CUtensorMap* m, int y, int z) {
  asm volatile("cp.async.bulk.prefetch.tensor.3d.L2.global [%0, {0, %1, %2}];" ::"l"(m), "r"(y), "r"(z) : "memory");
}
DEVINL void pf_5d(const CUtensorMap* m, int x, int a) {
  asm volatile("cp.async.bulk.prefetch.tensor.5d.L2.global [%0, {%1, 0, 0, 0, %2}];" ::"l"(m), "r"(x), "r"(a) : "memory");
}
DEVINL void bulk_store(void* dst, uint32_t src, uint32_t bytes) {
  asm volatile("cp.async.bulk.global.shared::cta.bulk_group [%0], [%1], %2;" ::"l"(dst), "r"(src), "r"(bytes) : "memory");
}
DEVINL void pf_bulk(const void* p, uint32_t bytes) { asm volatile("cp.async.bulk.prefetch.L2.global [%0], %1;" ::"l"(p), "r"(bytes) : "memory"); }
DEVINL void bulk_commit() { asm volatile("cp.async.bulk.commit_group;" ::: "memory"); }
template <int N> DEVINL void bulk_wait() { asm volatile("cp.async.bulk.wait_group %0;" ::"n"(N) : "memory"); }
DEVINL void prefetch_tmap(const CUtensorMap* m) { asm volatile("prefetch.tensormap [%0];" ::"l"(m) : "memory"); }

DEVINL void wg_fence() { asm volatile("wgmma.fence.sync.aligned;" ::: "memory"); }
DEVINL void wg_commit() { asm volatile("wgmma.commit_group.sync.aligned;" ::: "memory"); }
template <int N> DEVINL void wg_wait() { asm volatile("wgmma.wait_group.sync.aligned %0;" ::"n"(N) : "memory"); }
DEVINL uint64_t make_desc(uint32_t addr, uint32_t lbo, uint32_t sbo, uint64_t sw = 1) {
  return (uint64_t)((addr & 0x3FFFF) >> 4) | ((uint64_t)(lbo >> 4) << 16) | ((uint64_t)(sbo >> 4) << 32) | (sw << 62);
}

#define R8(a, o) "+f"(a[o]), "+f"(a[o + 1]), "+f"(a[o + 2]), "+f"(a[o + 3]), "+f"(a[o + 4]), "+f"(a[o + 5]), "+f"(a[o + 6]), "+f"(a[o + 7])
#define R64(a, o) R8(a, o), R8(a, o + 8), R8(a, o + 16), R8(a, o + 24), R8(a, o + 32), R8(a, o + 40), R8(a, o + 48), R8(a, o + 56)
#define ACC64 "{%0, %1, %2, %3, %4, %5, %6, %7, %8, %9, %10, %11, %12, %13, %14, %15, "              \
              "%16, %17, %18, %19, %20, %21, %22, %23, %24, %25, %26, %27, %28, %29, %30, %31, "    \
              "%32, %33, %34, %35, %36, %37, %38, %39, %40, %41, %42, %43, %44, %45, %46, %47, "    \
              "%48, %49, %50, %51, %52, %53, %54, %55, %56, %57, %58, %59, %60, %61, %62, %63"
#define ACC128 ACC64 ", %64, %65, %66, %67, %68, %69, %70, %71, %72, %73, %74, %75, %76, %77, %78, %79, "      \
              "%80, %81, %82, %83, %84, %85, %86, %87, %88, %89, %90, %91, %92, %93, %94, %95, "               \
              "%96, %97, %98, %99, %100, %101, %102, %103, %104, %105, %106, %107, %108, %109, %110, %111, "   \
              "%112, %113, %114, %115, %116, %117, %118, %119, %120, %121, %122, %123, %124, %125, %126, %127"
template <int TB> DEVINL void wgmma_n256(float (&d)[128], uint64_t da, uint64_t db, int scale_d) {
  asm volatile("{\n.reg .pred p;\nsetp.ne.b32 p, %130, 0;\n"
               "wgmma.mma_async.sync.aligned.m64n256k16.f32.bf16.bf16 " ACC128 "}, %128, %129, p, 1, 1, 0, %131;\n}\n"
               : R64(d, 0), R64(d, 64) : "l"(da), "l"(db), "r"(scale_d), "n"(TB));
}
template <int SC> DEVINL void wgmma_n256_rs(float (&d)[128], const uint32_t* a, uint64_t db) {
  asm volatile("{\n.reg .pred p;\nsetp.ne.b32 p, %133, 0;\n"
               "wgmma.mma_async.sync.aligned.m64n256k16.f32.bf16.bf16 " ACC128 "}, {%128, %129, %130, %131}, %132, p, 1, 1, 0;\n}\n"
               : R64(d, 0), R64(d, 64) : "r"(a[0]), "r"(a[1]), "r"(a[2]), "r"(a[3]), "l"(db), "n"(SC));
}
DEVINL void wgmma_n128(float (&d)[64], uint64_t da, uint64_t db) {
  asm volatile("wgmma.mma_async.sync.aligned.m64n128k16.f32.bf16.bf16 " ACC64 "}, %64, %65, 1, 1, 1, 0, 0;\n" : R64(d, 0) : "l"(da), "l"(db));
}
template <int N> DEVINL void reg_fence(float (&a)[N]) {
#pragma unroll
  for (int i = 0; i < N; i++) asm volatile("" : "+f"(a[i])::"memory");
}

DEVINL uint32_t pack_bf16(float lo, float hi) { uint32_t r; asm("cvt.rn.bf16x2.f32 %0, %1, %2;" : "=r"(r) : "f"(hi), "f"(lo)); return r; }
DEVINL uint32_t add_bf16x2(uint32_t a, uint32_t b) { uint32_t r; asm("add.rn.bf16x2 %0, %1, %2;" : "=r"(r) : "r"(a), "r"(b)); return r; }
DEVINL float bf_lo(uint32_t w) { return __uint_as_float(w << 16); }
DEVINL float bf_hi(uint32_t w) { return __uint_as_float(w & 0xFFFF0000u); }
DEVINL float round_bf16(float v) { return bf_lo(pack_bf16(v, 0.f)); }
DEVINL float sigmoid_f(float v) { float r; asm("rcp.approx.ftz.f32 %0, %1;" : "=f"(r) : "f"(1.f + __expf(-v))); return r; }
DEVINL float silu_f(float v) { return v * sigmoid_f(v); }
DEVINL void stsm_x4(uint32_t addr, const uint32_t* r) {
  asm volatile("stmatrix.sync.aligned.m8n8.x4.shared.b16 [%0], {%1, %2, %3, %4};" ::"r"(addr), "r"(r[0]), "r"(r[1]), "r"(r[2]), "r"(r[3]) : "memory");
}
DEVINL void ldsm_x4_t(uint32_t addr, uint32_t* r) {
  asm volatile("ldmatrix.sync.aligned.m8n8.x4.trans.shared.b16 {%0, %1, %2, %3}, [%4];" : "=r"(r[0]), "=r"(r[1]), "=r"(r[2]), "=r"(r[3]) : "r"(addr) : "memory");
}
DEVINL void mma_16816(float (&c)[4], const uint32_t* a, uint32_t b0, uint32_t b1) {
  asm("mma.sync.aligned.m16n8k16.row.col.f32.bf16.bf16.f32 {%0, %1, %2, %3}, {%4, %5, %6, %7}, {%8, %9}, {%0, %1, %2, %3};"
      : "+f"(c[0]), "+f"(c[1]), "+f"(c[2]), "+f"(c[3]) : "r"(a[0]), "r"(a[1]), "r"(a[2]), "r"(a[3]), "r"(b0), "r"(b1));
}
DEVINL float4 lds128(uint32_t a) { float4 v; asm volatile("ld.shared.v4.f32 {%0, %1, %2, %3}, [%4];" : "=f"(v.x), "=f"(v.y), "=f"(v.z), "=f"(v.w) : "r"(a)); return v; }
DEVINL uint4 lds128u(uint32_t a) { uint4 v; asm volatile("ld.shared.v4.u32 {%0, %1, %2, %3}, [%4];" : "=r"(v.x), "=r"(v.y), "=r"(v.z), "=r"(v.w) : "r"(a)); return v; }
DEVINL float2 lds64(uint32_t a) { float2 v; asm volatile("ld.shared.v2.f32 {%0, %1}, [%2];" : "=f"(v.x), "=f"(v.y) : "r"(a)); return v; }
DEVINL uint32_t lds32u(uint32_t a) { uint32_t v; asm volatile("ld.shared.u32 %0, [%1];" : "=r"(v) : "r"(a)); return v; }
DEVINL void sts128(uint32_t a, float x, float y, float z, float w) { asm volatile("st.shared.v4.f32 [%0], {%1, %2, %3, %4};" ::"r"(a), "f"(x), "f"(y), "f"(z), "f"(w) : "memory"); }
DEVINL void sts128u(uint32_t a, uint32_t x, uint32_t y, uint32_t z, uint32_t w) { asm volatile("st.shared.v4.u32 [%0], {%1, %2, %3, %4};" ::"r"(a), "r"(x), "r"(y), "r"(z), "r"(w) : "memory"); }
DEVINL void sts64u(uint32_t a, uint32_t x, uint32_t y) { asm volatile("st.shared.v2.u32 [%0], {%1, %2};" ::"r"(a), "r"(x), "r"(y) : "memory"); }
DEVINL void sts32(uint32_t a, float v) { asm volatile("st.shared.f32 [%0], %1;" ::"r"(a), "f"(v) : "memory"); }

DEVINL uint4 ld_msg(const void* p) {
  unsigned long long a, b;
  asm volatile("{\n.reg .b128 r;\nld.relaxed.gpu.global.b128 r, [%2];\nmov.b128 {%0, %1}, r;\n}" : "=l"(a), "=l"(b) : "l"(p) : "memory");
  return make_uint4((uint32_t)a, (uint32_t)(a >> 32), (uint32_t)b, (uint32_t)(b >> 32));
}
DEVINL void st_msg(void* p, uint32_t x, uint32_t y, uint32_t z, uint32_t w) {
  unsigned long long a = (unsigned long long)x | ((unsigned long long)y << 32), b = (unsigned long long)z | ((unsigned long long)w << 32);
  asm volatile("{\n.reg .b128 r;\nmov.b128 r, {%1, %2};\nst.relaxed.gpu.global.b128 [%0], r;\n}" ::"l"(p), "l"(a), "l"(b) : "memory");
}
DEVINL uint2 ld_msg8(const void* p) {
  unsigned long long a;
  asm volatile("ld.relaxed.gpu.global.b64 %0, [%1];" : "=l"(a) : "l"(p) : "memory");
  return make_uint2((uint32_t)a, (uint32_t)(a >> 32));
}
DEVINL void st_msg8(void* p, uint32_t x, uint32_t y) {
  asm volatile("st.relaxed.gpu.global.b64 [%0], %1;" ::"l"(p), "l"((unsigned long long)x | ((unsigned long long)y << 32)) : "memory");
}
DEVINL unsigned ld_rlx(const void* p) { unsigned v; asm volatile("ld.relaxed.gpu.global.u32 %0, [%1];" : "=r"(v) : "l"(p) : "memory"); return v; }
DEVINL void st_rlx(unsigned* p, unsigned v) { asm volatile("st.relaxed.gpu.global.u32 [%0], %1;" ::"l"(p), "r"(v) : "memory"); }
DEVINL void red_add(unsigned* p, unsigned v) { asm volatile("red.relaxed.gpu.global.add.u32 [%0], %1;" ::"l"(p), "r"(v) : "memory"); }
DEVINL uint4 ldg_nc(const void* p) {
  uint4 v;
  asm volatile("ld.global.nc.L1::no_allocate.v4.u32 {%0, %1, %2, %3}, [%4];" : "=r"(v.x), "=r"(v.y), "=r"(v.z), "=r"(v.w) : "l"(p));
  return v;
}
DEVINL float4 ldg_cg(const float* p) { float4 v; asm volatile("ld.global.cg.v4.f32 {%0, %1, %2, %3}, [%4];" : "=f"(v.x), "=f"(v.y), "=f"(v.z), "=f"(v.w) : "l"(p) : "memory"); return v; }
DEVINL void wait_cnt(const unsigned* p, unsigned target) {
  int it = 0;
  while ((int)(ld_rlx(p) - target) < 0) { SPIN_CHECK(it); __nanosleep(100); }
}

#define TRACE(id)
#define TRACE_CLK(id)

DEVINL uint32_t fkey(float v) { const uint32_t u = __float_as_uint(v); return (u & 0x80000000u) ? ~u : (u | 0x80000000u); }
DEVINL float fkey_inv(uint32_t k) { return __uint_as_float((k & 0x80000000u) ? (k & 0x7FFFFFFFu) : ~k); }
DEVINL uint32_t redux_max(uint32_t v) { uint32_t r; asm volatile("redux.sync.max.u32 %0, %1, 0xffffffff;" : "=r"(r) : "r"(v)); return r; }
DEVINL void warp_top2(uint32_t key, uint32_t& k1, uint32_t& k2) { k1 = redux_max(key); k2 = redux_max(key == k1 ? 0u : key); }
DEVINL int key_row(uint32_t k) { return 2047 - (int)(k & 2047u); }
DEVINL int perm32(int e) { return (e & ~30) | ((e >> 2) & 6) | ((e << 2) & 24); }

__global__ void __launch_bounds__(384, 1) __cluster_dims__(2, 1, 1)
fused_kernel(const __nv_bfloat16* __restrict__ x, Scratch* const S, __nv_bfloat16* __restrict__ out, const __nv_bfloat16* __restrict__ cvec,
             const __nv_bfloat16* __restrict__ wd_re, const __nv_bfloat16* __restrict__ wd_im, const __grid_constant__ Params prm) {
  extern __shared__ __align__(1024) uint8_t smem_raw[];
  const uint32_t sb = smem_u32(smem_raw);
  const int tid = threadIdx.x, lane = tid & 31;
  const int warp = __shfl_sync(~0u, tid >> 5, 0);
  const int b = blockIdx.x;
  const int j = b & 1, m4 = (b >> 1) & 3, t = b >> 3;
  const int cgrp = b & 7;
  auto BAR = [&](int i) { return sb + BAR_OFF + i * 8; };

  uint4 xr[4];
  if ((warp & ~1) == 2) {
    const uint4* src = reinterpret_cast<const uint4*>(x + (size_t)((warp - 2) * 128 + b) * D_) + lane;
#pragma unroll
    for (int i = 0; i < 4; i++) xr[i] = ldg_nc(src + 32 * i);
  }
  if (tid == 0) TRACE(0);
  if ((warp & ~1) != 2 && elect_one()) {
    const int w = warp < 2 ? warp : warp - 2;
#pragma unroll
    for (int k = 0; k < 3; k++) {
      const int i = w + 10 * k;
      mbar_init(BAR(i), (uint32_t)((i < 16 ? CNT_LO : CNT_HI) >> ((i & 15) * 4)) & 15u);
    }
    if (w < 4) mbar_expect_tx(BAR(B_FULL + w), STAGE);
    if (w == B_RECV - 20 || w == B_RECV - 19) mbar_expect_tx(BAR(w + 20), SLOT);
    asm volatile("fence.mbarrier_init.release.cluster;" ::: "memory");
    if (w == 0) tma_2d(sb, &prm.ws[j], 0, t * 128, BAR(B_FULL));
    else if (w < 8) prefetch_tmap(&prm.ws[1] + w);
  }
  __syncthreads();
  asm volatile("barrier.cluster.arrive.relaxed.aligned;" ::: "memory");

  if (warp < 4) {
    auto prefetch_piece = [&](int g) {
      const int pi = g - FK_G0;
      if ((unsigned)(pi - 12) < 4u) {
        asm volatile("prefetch.global.L2 [%0];" ::"l"(x + (size_t)(t * 128 + (pi - 12) * 32 + (lane >> 1)) * D_ + cgrp * 128 + (lane & 1) * 64));
        asm volatile("prefetch.global.L2 [%0];" ::"l"(x + (size_t)(t * 128 + (pi - 12) * 32 + 16 + (lane >> 1)) * D_ + cgrp * 128 + (lane & 1) * 64));
      } else if (b < NMOE && (unsigned)pi < 24u && elect_one()) {
        if (pi < 12) pf_5d(pi < 4 ? &prm.wg : &prm.wu, b * 32, (pi < 4 ? pi + 4 : (pi - 3) & 7) * 4);
        else pf_3d(&prm.wdn, b * 32, (pi - 16) * 2);
      }
    };
    if (warp == 0) {
      const unsigned* flagAddr = &S->cntN[lane * 32];
      const unsigned tgt = (ld_rlx(S->epoch) + 1) * 64u;
      unsigned ready = 0, pend = tgt - 1;
#pragma unroll 1
      for (int g = 0; g < 32; g++) {
        const int s = g & 3;
        ready |= __ballot_sync(~0u, pend == tgt);
        int it = 0;
        while (!((ready >> g) & 1)) {
          ready |= __ballot_sync(~0u, (unsigned)(lane - g) < 4u && ld_rlx(flagAddr) == tgt);
          SPIN_CHECK(it);
        }
        fence_async_global();
        if (g >= 4) {
          if (!((ready >> lane) & 1)) pend = ld_rlx(flagAddr);
          mbar_wait(BAR(B_EMPTY + s), ((g >> 2) - 1) & 1);
        }
        if (elect_one()) {
          const uint32_t sa = sb + s * STAGE, fb = BAR(B_FULL + s);
          if (g >= 4) mbar_expect_tx(fb, STAGE);
          tma_3d(sa + SLOT, &prm.n, g * 64, m4 * 4, fb);
          if (g > 0) tma_2d(sa, &prm.ws[j], g * 64, t * 128, fb);
          if ((unsigned)(g - FK_GW) < 4u) pf_bulk((const char*)(b < 64 ? wd_re : wd_im) + (b & 63) * 32768 + (g - FK_GW) * 8192, 8192);
          TRACE(64 + g);
        }
        prefetch_piece(g);
      }
    }
    asm volatile("" ::: "memory");
    if (warp == 1) {
      const uint32_t tag = ld_rlx(S->epoch) + 1;
      const uint32_t rb = sb + (m4 * 32 + lane) * 128 + ((lane & 7) << 4);
      float a0 = 0.f, a1 = 0.f, a2 = 0.f, a3 = 0.f;
#pragma unroll 1
      for (int g = 0; g < 32; g++) {
        const int s = g & 3;
        mbar_wait(BAR(B_FULL + s), (g >> 2) & 1);
        uint4 u[8];
#pragma unroll
        for (int c = 0; c < 8; c++) u[c] = lds128u((rb + s * STAGE) ^ (c << 4));
#pragma unroll
        for (int c = 0; c < 8; c++) {
          a0 += bf_lo(u[c].x) + bf_lo(u[c].y); a1 += bf_hi(u[c].x) + bf_hi(u[c].y);
          a2 += bf_lo(u[c].z) + bf_lo(u[c].w); a3 += bf_hi(u[c].z) + bf_hi(u[c].w);
        }
        asm volatile("" : "+f"(a0), "+f"(a1), "+f"(a2), "+f"(a3) :: "memory");
        if (elect_one()) mbar_arrive(BAR(B_EMPTY + s));
      }
      if (lane == 0) mbar_arrive(BAR(B_RSDONE));
      st_msg8(&S->rs[j * S_ + t * 128 + m4 * 32 + lane], __float_as_uint((a0 + a1) + (a2 + a3)), tag);
    }
    asm volatile("" ::: "memory");
    if (warp >= 2) {
      {
        int g = warp - 2;
        const uint32_t stg = sb + LNS_OFF + g * 2048;
#pragma unroll 1
        while (true) {
          float s0 = 0.f, s1 = 0.f, q0 = 0.f, q1 = 0.f;
          uint32_t w[16];
#pragma unroll
          for (int i = 0; i < 4; i++) { w[4 * i] = xr[i].x; w[4 * i + 1] = xr[i].y; w[4 * i + 2] = xr[i].z; w[4 * i + 3] = xr[i].w; }
#pragma unroll
          for (int i = 0; i < 16; i++) { const float lo = bf_lo(w[i]), hi = bf_hi(w[i]); s0 += lo; s1 += hi; q0 = fmaf(lo, lo, q0); q1 = fmaf(hi, hi, q1); }
          float sum = s0 + s1, sq = q0 + q1;
#pragma unroll
          for (int o = 16; o; o >>= 1) { sum += __shfl_xor_sync(~0u, sum, o); sq += __shfl_xor_sync(~0u, sq, o); }
          const float mean = sum * (1.f / D_);
          const float rstd = rsqrtf(fmaxf(fmaf(-mean, mean, sq * (1.f / D_)), 0.f) + 1e-5f), nmr = -mean * rstd;
#pragma unroll
          for (int i = 0; i < 16; i++) w[i] = pack_bf16(fmaf(bf_lo(w[i]), rstd, nmr), fmaf(bf_hi(w[i]), rstd, nmr));
#pragma unroll
          for (int i = 0; i < 4; i++) sts128u(stg + lane * 16 + i * 512, w[4 * i], w[4 * i + 1], w[4 * i + 2], w[4 * i + 3]);
          fence_async_smem();
          const bool el = elect_one();
          if (el) { bulk_store(S->n + (size_t)(g * 128 + b) * D_, stg, 2048); bulk_commit(); }
          const int gn = warp == 3 ? 16 : g ? g + 1 : 2;
          if (gn < 16) {
            const uint4* src = reinterpret_cast<const uint4*>(x + (size_t)(gn * 128 + b) * D_);
#pragma unroll
            for (int i = 0; i < 4; i++) xr[i] = ldg_nc(src + lane + 32 * i);
            if (gn < 15 && lane < 16) asm volatile("prefetch.global.L2 [%0];" ::"l"(src + 128 * 128 + lane * 8));
          }
          if (el) {
            bulk_wait<0>();
            red_add(&S->cntN[(g * 2 + (b >> 6)) * 32], 1);
            if (g < 3 || g == 15) TRACE(44 + (g & 3));
          }
          __syncwarp();
          if (gn == 16) break;
          g = gn;
        }
      }
      if (warp == 3) {
        uint64_t pol_first;
        asm volatile("createpolicy.fractional.L2::evict_first.b64 %0, 1.0;" : "=l"(pol_first));
#pragma unroll 1
        for (int i = 0; i < 4; i++) {
          const uint4 cw4 = ldg_nc(reinterpret_cast<const uint4*>(cvec) + lane + 32 * i);
          const uint32_t cw[4] = {cw4.x, cw4.y, cw4.z, cw4.w};
          const uint32_t dst = sb + SILU_OFF + (i * 4 + (lane >> 3)) * 256 + (lane & 7) * 8;
#pragma unroll
          for (int r = 0; r < 4; r++) {
            const float v0 = (r & 1) ? bf_hi(cw[r >> 1]) : bf_lo(cw[r >> 1]), v1 = (r & 1) ? bf_hi(cw[2 + (r >> 1)]) : bf_lo(cw[2 + (r >> 1)]);
            const uint32_t sp = pack_bf16(silu_f(v0), silu_f(v1));
            sts64u(dst + r * 64, sp << 16, sp & 0xFFFF0000u);
          }
        }
        mbar_wait(BAR(B_FULL), 0);
        const int rr = (lane * 43) >> 8;
        float acc[8];
#pragma unroll
        for (int i = 0; i < 8; i++) acc[i] = 0.f;
#pragma unroll 1
        for (int ch = -3; ch < 16; ch++) {
          if (elect_one() && ch < 13) {
            const int nx = ch + 3;
            mbar_expect_tx(BAR(B_MF + (nx & 3)), 6144);
            tma_2d_hint(sb + WM_OFF + (nx & 3) * 6144, &prm.wm, b * 48, nx * 64, BAR(B_MF + (nx & 3)), pol_first);
          }
          if (ch < 0) { __nanosleep(300); continue; }
          mbar_wait(BAR(B_MF + (ch & 3)), (ch >> 2) & 1);
#pragma unroll 1
          for (int h = 0; h < 2; h++) {
            const float4 sv0 = lds128(sb + SILU_OFF + ch * 256 + (rr & 3) * 64 + h * 32), sv1 = lds128(sb + SILU_OFF + ch * 256 + (rr & 3) * 64 + h * 32 + 16);
            const float sc[8] = {sv0.x, sv0.y, sv0.z, sv0.w, sv1.x, sv1.y, sv1.z, sv1.w};
            uint4 v[8];
#pragma unroll
            for (int u = 0; u < 8; u++) v[u] = lds128u(sb + WM_OFF + (ch & 3) * 6144 + (h * 8 + u) * 384 + (lane < 24 ? lane : 0) * 16);
#pragma unroll
            for (int u = 0; u < 8; u++) {
              acc[0] = fmaf(sc[u], bf_lo(v[u].x), acc[0]); acc[1] = fmaf(sc[u], bf_hi(v[u].x), acc[1]);
              acc[2] = fmaf(sc[u], bf_lo(v[u].y), acc[2]); acc[3] = fmaf(sc[u], bf_hi(v[u].y), acc[3]);
              acc[4] = fmaf(sc[u], bf_lo(v[u].z), acc[4]); acc[5] = fmaf(sc[u], bf_hi(v[u].z), acc[5]);
              acc[6] = fmaf(sc[u], bf_lo(v[u].w), acc[6]); acc[7] = fmaf(sc[u], bf_hi(v[u].w), acc[7]);
            }
          }
          asm volatile("" : "+f"(acc[0]) :: "memory");
        }
#pragma unroll
        for (int i = 0; i < 8; i++) { acc[i] += __shfl_down_sync(~0u, acc[i], 12); acc[i] += __shfl_down_sync(~0u, acc[i], 6); acc[i] = round_bf16(acc[i]); }
        if (lane < 6) {
          float4* dst = reinterpret_cast<float4*>(S->mod + b * 48 + lane * 8);
          dst[0] = make_float4(acc[0], acc[1], acc[2], acc[3]); dst[1] = make_float4(acc[4], acc[5], acc[6], acc[7]);
        }
        __syncwarp();
        if (lane == 0) { fence_gpu(); red_add(S->cntMod, 1); TRACE(9); }
      }
      named_bar<1, 64>();
      if (warp == 2 && b < NMOE && elect_one()) {
        fence_async_smem();
        mbar_expect_tx(BAR(B_WFULL), 32768);
      }
      {
        const int jw = b >> 6, e0 = (b & 63) * 16 + (warp - 2) * 8;
        const uint4* src = reinterpret_cast<const uint4*>((jw ? wd_im : wd_re) + (size_t)e0 * D_) + lane;
#pragma unroll
        for (int i = 0; i < 4; i++) xr[i] = ldg_nc(src + 32 * i);
        wait_cnt(S->cntMod, (ld_rlx(S->epoch) + 1) * 128u);
        fence_gpu();
        if (tid == 96) TRACE(10);
        const float gal = __uint_as_float(ld_rlx(S->mod + 2 * D_ + e0 + (lane & 7)) ^ (jw ? 0x80000000u : 0u));
        float4 sa[8], A[8];
#pragma unroll
        for (int i = 0; i < 8; i++) { sa[i] = ldg_cg(S->mod + (i >> 1) * 256 + lane * 8 + (i & 1) * 4); A[i] = ldg_cg(S->mod + D_ + (i >> 1) * 256 + lane * 8 + (i & 1) * 4); }
#pragma unroll
        for (int i = 0; i < 8; i++) {
          const uint32_t p0 = pack_bf16(1.f + A[i].x, 1.f + A[i].y), p1 = pack_bf16(1.f + A[i].z, 1.f + A[i].w);
          A[i] = make_float4(bf_lo(p0), bf_hi(p0), bf_lo(p1), bf_hi(p1));
        }
#pragma unroll 1
        for (int r = 0; r < 8; r++) {
          if (warp == 2 && b < NMOE && (r & 1) && elect_one()) tma_5d(sb + SP_OFF + (r >> 1) * 8192, &prm.wg, b * 32, (r >> 1) * 4, BAR(B_WFULL));
          const float ga = __shfl_sync(~0u, gal, r);
          uint4* dst = reinterpret_cast<uint4*>(S->W2 + (size_t)(jw * D_ + (perm32(e0 + r) ^ (jw * 128))) * D_) + lane;
          float u0 = 0.f, u1 = 0.f;
#pragma unroll
          for (int i = 0; i < 4; i++) {
            const uint32_t w[4] = {xr[i].x, xr[i].y, xr[i].z, xr[i].w};
            if (r < 7) xr[i] = ldg_nc(src + (r + 1) * 128 + 32 * i);
            uint32_t o[4];
#pragma unroll
            for (int h = 0; h < 2; h++) {
              const float w0 = bf_lo(w[2 * h]) * ga, w1 = bf_hi(w[2 * h]) * ga, w2 = bf_lo(w[2 * h + 1]) * ga, w3 = bf_hi(w[2 * h + 1]) * ga;
              u0 = fmaf(w0, sa[2 * i + h].x, u0); u1 = fmaf(w1, sa[2 * i + h].y, u1); u0 = fmaf(w2, sa[2 * i + h].z, u0); u1 = fmaf(w3, sa[2 * i + h].w, u1);
              o[2 * h] = pack_bf16(w0 * A[2 * i + h].x, w1 * A[2 * i + h].y); o[2 * h + 1] = pack_bf16(w2 * A[2 * i + h].z, w3 * A[2 * i + h].w);
            }
            dst[32 * i] = make_uint4(o[0], o[1], o[2], o[3]);
          }
          u0 += u1;
#pragma unroll
          for (int o = 16; o; o >>= 1) u0 += __shfl_xor_sync(~0u, u0, o);
          if (lane == 0) S->u[jw * D_ + e0 + r] = u0;
        }
        __syncwarp();
        if (lane == 0) { fence_gpu(); red_add(&S->cntW[(b >> 4) * 32], 1); TRACE(11 + warp - 2); }
      }
      if (warp == 2) {
#pragma unroll 1
        for (int i = 0; i < 20; i++) {
          const int rowSlot = (t * 2 + (lane >> 4)) * 128 + cgrp * 16 + (lane & 15);
          st_msg(i < 14 ? &S->part[b * 512 + i * 32 + lane] : i < 18 ? &S->stats[b * 128 + (i - 14) * 32 + lane] : &S->rowsH[(i - 18) * 4096 + rowSlot], SENT, SENT, SENT, SENT);
        }
        fence_gpu();
        __syncwarp();
        if (lane == 0) mbar_arrive(BAR(B_RESET));
      } else {
        float c1 = 0.f, c2 = 0.f;
#pragma unroll 1
        for (int i = 0; i < 8; i++) {
          const int col = i * 128 + lane * 4;
          const float4 sv = ldg_cg(S->mod + 3 * D_ + col), cb = ldg_cg(S->mod + 4 * D_ + col), gb = ldg_cg(S->mod + 5 * D_ + col);
          const uint2 wr = __ldg(reinterpret_cast<const uint2*>(prm.w_r + col));
          const float A0 = round_bf16(1.f + cb.x), A1 = round_bf16(1.f + cb.y), A2 = round_bf16(1.f + cb.z), A3 = round_bf16(1.f + cb.w);
          const float w0 = A0 * bf_lo(wr.x), w1 = A1 * bf_hi(wr.x), w2 = A2 * bf_lo(wr.y), w3 = A3 * bf_hi(wr.y);
          c1 += (w0 + w1) + (w2 + w3);
          c2 += (sv.x * bf_lo(wr.x) + sv.y * bf_hi(wr.x)) + (sv.z * bf_lo(wr.y) + sv.w * bf_hi(wr.y));
          if (i == cgrp) {
            const uint32_t tb = sb + TAB_OFF + lane * 16;
            sts128(tb, w0, w1, w2, w3);
            sts128(tb + 512, gb.x * A0, gb.y * A1, gb.z * A2, gb.w * A3);
            sts128(tb + 1024, gb.x * sv.x, gb.y * sv.y, gb.z * sv.z, gb.w * sv.w);
            sts128(tb + 1536, A0, A1, A2, A3);
            sts128(tb + 2048, sv.x, sv.y, sv.z, sv.w);
          }
        }
#pragma unroll
        for (int o = 16; o; o >>= 1) { c1 += __shfl_xor_sync(~0u, c1, o); c2 += __shfl_xor_sync(~0u, c2, o); }
        if (lane == 0) { sts64u(sb + CST_OFF, __float_as_uint(c1), __float_as_uint(c2)); TRACE(27); }
      }
    }
    asm volatile("setmaxnreg.dec.sync.aligned.u32 40;" ::: "memory");
    const uint32_t tag = ld_rlx(S->epoch) + 1;
    if (warp == 0) {
      wait_cnt(&S->cntW[(j * 4 + m4) * 32], tag * 32u);
      if (lane == 0) TRACE(30);
      const int f = (lane - 4) & 15, kk = (f * 11) >> 5, np = (m4 + 1 + f - kk * 3) & 3;
      const unsigned* flagAddr = &S->flagP[((t * 8 + np * 2 + j) * 4 + (kk & 3)) * 8];
      const int kcl = lane < 4 ? m4 * 256 + ((lane + 3) & 3) * 64 : np * 256 + kk * 64;
      unsigned ready = 0xFFFF000Fu, pend = tag - 1;
#pragma unroll 1
      for (int q = 0; q < 16; q++) {
        const int s = q & 3, kc = __shfl_sync(~0u, kcl, q);
        ready |= __ballot_sync(~0u, pend == tag);
        int it = 0;
        while (!((ready >> q) & 1)) {
          ready |= __ballot_sync(~0u, (unsigned)(lane - q) < 3u && ld_rlx(flagAddr) == tag);
          SPIN_CHECK(it);
        }
        fence_async_global();
        if (q >= 3 && !((ready >> lane) & 1)) pend = ld_rlx(flagAddr);
        mbar_wait(BAR(B_EMPTY + s), ((q >> 2) + 1) & 1);
        if (elect_one()) {
          const uint32_t sa = sb + s * STAGE, fb = BAR(B_FULL + s);
          mbar_expect_tx(fb, q < 4 ? 2 * SLOT : STAGE);
          if (q >= 4) { tma_2d(sa, &prm.p, kc, j * S_ + t * 128, fb); mbar_arrive(BAR(B_EMPTY + s)); }
          tma_2d(sa + SLOT, &prm.w2, kc, j * D_ + m4 * 256, fb);
          TRACE(96 + q);
        }
        prefetch_piece(32 + q);
      }
      if (b < NMOE && elect_one()) {
        mbar_wait(BAR(B_HIALL), 0);
        mbar_expect_tx(BAR(B_UP), 32768);
        tma_5d(sb + UP0_OFF, &prm.wu, b * 32, 0, BAR(B_UP));
        tma_5d(sb + 2 * STAGE + 2 * SLOT, &prm.wu, b * 32, 16, BAR(B_UP));
        tma_5d(sb + 2 * STAGE + 2 * SLOT + 8192, &prm.wu, b * 32, 20, BAR(B_UP));
        tma_5d(sb + UP0_OFF - 8192, &prm.wu, b * 32, 24, BAR(B_UP));
        mbar_expect_tx(BAR(B_DN), 65536);
#pragma unroll 1
        for (int i = 0; i < 9; i++) {
          if ((i & 3) == 0) mbar_wait(BAR(B_EMPTY + (i >> 2)), 1);
          if (i == 0) { mbar_expect_tx(BAR(B_UP), 8192); tma_5d(sb, &prm.wu, b * 32, 28, BAR(B_UP)); }
          else tma_3d(sb + (i >> 2) * STAGE + (i & 3) * 8192, &prm.wdn, b * 32, i * 2 - 2, BAR(B_DN));
        }
      }
    }
    asm volatile("" ::: "memory");
    if (warp == 1 && elect_one()) {
      mbar_wait(BAR(B_RESET), 0);
#pragma unroll 1
      for (int kk = 0; kk < 4; kk++) {
        mbar_wait(BAR(B_PREADY + kk), 0);
        tma_store_2d(&prm.p, sb + kk * STAGE, m4 * 256 + kk * 64, j * S_ + t * 128);
        bulk_commit();
        bulk_wait<0>();
        st_rlx(&S->flagP[(b * 4 + kk) * 8], tag);
        mbar_arrive(BAR(B_EMPTY + kk));
        TRACE(40 + kk);
      }
    }
    asm volatile("" ::: "memory");
    if (warp == 2 && b < NMOE && elect_one()) {
#pragma unroll 1
      for (int i = 0; i < 7; i++) {
        const uint32_t bar = BAR(i < 4 ? B_WFULL : B_UP);
        if ((i & 3) == 0) { mbar_wait(BAR(B_WFREE + (i >> 2)), 0); mbar_expect_tx(bar, i ? 24576 : 32768); }
        tma_5d(sb + SP_OFF + (i & 3) * 8192, i < 4 ? &prm.wg : &prm.wu, b * 32, i < 4 ? 16 + i * 4 : i * 4 - 12, bar);
        __nanosleep(100);
      }
    }
    asm volatile("" ::: "memory");
    if (warp == 3) {
      wait_cnt(&S->cntW[(m4 + (lane & 4)) * 32], tag * 32u);
      fence_gpu();
      mbar_wait(BAR(b < NMOE ? B_WFREE + 1 : B_PREADY + 3), 0);
#pragma unroll 1
      for (int i = 0; i < 4; i++) {
        const int r = i * 32 + lane;
        const float v0 = 0.5f * __uint_as_float(ld_rlx(S->u + cgrp * 128 + r)), v1 = 0.5f * __uint_as_float(ld_rlx(S->u + D_ + cgrp * 128 + r));
        uint2 m0, m1; int it = 0;
        while (true) {
          m0 = ld_msg8(&S->rs[t * 128 + r]); m1 = ld_msg8(&S->rs[S_ + t * 128 + r]);
          if (m0.y == tag && m1.y == tag) break;
          SPIN_CHECK(it);
        }
        const float r0 = __uint_as_float(m0.x), r1 = __uint_as_float(m1.x);
        const uint32_t rh = pack_bf16(r0, r1), vh = pack_bf16(v0, v1);
        sts128u(sb + RKA_OFF + r * 16, rh, rh, pack_bf16(r0 - bf_lo(rh), r1 - bf_hi(rh)), 0);
        sts128u(sb + RKB_OFF + perm32(r) * 16, vh, pack_bf16(v0 - bf_lo(vh), v1 - bf_hi(vh)), vh, 0);
      }
      fence_async_smem();
      __syncwarp();
      if (lane == 0) { mbar_arrive(BAR(B_TAB)); TRACE(26); }
      mbar_wait(BAR(B_HIALL), 0);
      uint4 m; int it = 0;
      while (true) {
        m = ld_msg(&S->cand[(lane >> 1) * 8]);
        if (__all_sync(~0u, m.z == tag)) break;
        SPIN_CHECK(it);
      }
      uint32_t k1, k2;
      const uint32_t key = (lane & 1) ? m.y : m.x;
      warp_top2(key, k1, k2);
      if (lane == 0) { sts64u(sb + SEL_OFF, k1, k2); mbar_arrive(BAR(B_SEL)); TRACE(14); }
      const uint32_t ck = __shfl_sync(~0u, key, t * 2 + (lane >> 4));
      if (ck != k1 && ck != k2) {
        it = 0;
        do { m = ld_msg(&S->rowsB[(t * 2 + (lane >> 4)) * 128 + cgrp * 16 + (lane & 15)]); SPIN_CHECK(it); } while (m.x == SENT);
        *reinterpret_cast<uint4*>(out + (size_t)key_row(ck) * D_ + cgrp * 128 + (lane & 15) * 8) = m;
      }
    }
  } else {
    const int cw = (warp - 4) >> 2;
    const int cwarp = warp - 4;
    const int gq = lane >> 2, q4 = lane & 3;
    const bool elect = (tid & 127) == 0;
    asm volatile("barrier.cluster.wait.acquire.aligned;" ::: "memory");

    uint32_t wf[64];
    const int kr = (lane & 7) + (lane >> 4) * 8;
    const uint32_t wo = (cwarp & 1) * 4096 + kr * 64 + ((((lane >> 3) & 1) ^ ((kr >> 1) & 3)) << 4);
    float lo[64], hi[64];
    {
      float acc[128];
#pragma unroll 1
      for (int g = 0; g < 32; g++) {
        const int s = g & 3;
        mbar_wait(BAR(B_FULL + s), (g >> 2) & 1);
        const uint32_t sa = sb + s * STAGE;
        const uint64_t da = make_desc(sa + cw * 8192, 16, 1024), db = make_desc(sa + SLOT, 8192, 1024);
        wg_fence();
        wgmma_n256<1>(acc, da, db, g > 0);
#pragma unroll
        for (int k = 1; k < 4; k++) wgmma_n256<1>(acc, da + k * 2, db + k * 128, 1);
        wg_commit();
        wg_wait<1>();
        if (g > 0 && elect) mbar_arrive(BAR(B_EMPTY + ((g - 1) & 3)));
      }
      mbar_wait(BAR(B_RSDONE), 0);
      asm volatile("setmaxnreg.inc.sync.aligned.u32 232;" ::: "memory");
      mbar_wait(BAR(B_FULL), 0);
      wg_wait<0>();
      if (elect) { mbar_arrive(BAR(B_EMPTY + 3)); TRACE(1 + tr); }
      reg_fence(acc);
      uint32_t pk[64];
#pragma unroll
      for (int i = 0; i < 64; i++) pk[i] = pack_bf16(acc[2 * i], acc[2 * i + 1]);
      const uint32_t so = sb + (uint32_t)(cwarp * 16 + (lane & 15)) * 128 + (((lane >> 4) ^ (lane & 7)) << 4);
      auto stage_p = [&](int kk) {
#pragma unroll
        for (int k = 0; k < 4; k++) stsm_x4((so + kk * STAGE) ^ (k << 5), pk + kk * 16 + k * 4);
        fence_async_smem();
        __syncwarp();
        if (lane == 0) mbar_arrive(BAR(B_PREADY + kk));
      };
#pragma unroll
      for (int s = 0; s < 4; s++) {
        const int kk = (s + 3) & 3;
        if (s) mbar_wait(BAR(B_FULL + s), 0);
        const uint64_t db = make_desc(sb + s * STAGE + SLOT, 16, 1024);
        wg_fence();
        if (s == 0) wgmma_n256_rs<0>(acc, pk + kk * 16, db); else wgmma_n256_rs<1>(acc, pk + kk * 16, db);
#pragma unroll
        for (int k = 1; k < 4; k++) wgmma_n256_rs<1>(acc, pk + kk * 16 + k * 4, db + k * 2);
        wg_commit();
        if (s == 0) { stage_p(0); stage_p(1); stage_p(2); if (elect) TRACE(2 + tr); }
        else {
          wg_wait<1>();
          if (elect) mbar_arrive(BAR(B_EMPTY + s - 1));
          if (s == 1) stage_p(3);
        }
      }
#pragma unroll 1
      for (int g = 36; g < 44; g++) {
        const int s = g & 3;
        mbar_wait(BAR(B_FULL + s), (g >> 2) & 1);
        const uint32_t sa = sb + s * STAGE;
        const uint64_t da = make_desc(sa + cw * 8192, 16, 1024), db = make_desc(sa + SLOT, 16, 1024);
        wg_fence();
#pragma unroll
        for (int k = 0; k < 4; k++) wgmma_n256<0>(acc, da + k * 2, db + k * 2, 1);
        wg_commit();
        wg_wait<1>();
        if (elect) mbar_arrive(BAR(B_EMPTY + ((g - 1) & 3)));
        if (b < NMOE && s == 0) {
          mbar_wait(BAR(B_WFULL), g >= 40);
          const uint32_t wb = sb + SP_OFF + (cwarp >> 1) * 8192 + wo;
          if (g == 36) {
#pragma unroll
            for (int i = 0; i < 8; i++) ldsm_x4_t((wb + (i >> 1) * 1024) ^ ((i & 1) << 5), wf + i * 4);
          } else {
#pragma unroll
            for (int i = 0; i < 8; i++) ldsm_x4_t((wb + (i >> 1) * 1024) ^ ((i & 1) << 5), wf + 32 + i * 4);
          }
          fence_async_smem();
          __syncwarp();
          if (lane == 0) mbar_arrive(BAR(B_WFREE + (g >= 40)));
        }
      }
      wg_wait<0>();
      if (elect) mbar_arrive(BAR(B_EMPTY + 3));
#pragma unroll
      for (int i = 0; i < 64; i++) {
        asm volatile("mov.b32 %0, %1;" : "=f"(lo[i]) : "f"(acc[i]));
        asm volatile("mov.b32 %0, %1;" : "=f"(hi[i]) : "f"(acc[64 + i]));
      }
    }
    if (elect) TRACE(3 + tr);
#pragma unroll 1
    for (int s = 0; s < 4; s++) {
      mbar_wait(BAR(B_FULL + s), 1);
      const uint32_t sa = sb + s * STAGE;
      const uint64_t da = make_desc(sa + cw * 8192, 16, 1024), db = make_desc(sa + 2 * SLOT, 16, 1024);
      wg_fence();
#pragma unroll
      for (int k = 0; k < 4; k++) wgmma_n128(hi, da + k * 2, db + k * 2);
      wg_commit();
      if (s == 2) {
        wg_wait<1>();
        if (elect) asm volatile("{\n.reg .b32 ra;\nmapa.shared::cluster.u32 ra, %0, %1;\nmbarrier.arrive.shared::cluster.b64 _, [ra];\n}"
                                ::"r"(BAR(B_PEER)), "r"(j ^ 1) : "memory");
      }
    }
    mbar_wait(BAR(B_TAB), 0);
    wg_fence();
    wgmma_n128(lo, make_desc(sb + RKA_OFF + cw * 1024, 0, 128, 0), make_desc(sb + RKB_OFF, 0, 128, 0));
#pragma unroll 1
    for (int s = 0; s < 2; s++) {
      const uint32_t sa = sb + s * STAGE;
      const uint64_t da = make_desc(sa + cw * 8192, 16, 1024), db = make_desc(sa + SLOT, 16, 1024);
#pragma unroll
      for (int k = 0; k < 4; k++) wgmma_n128(lo, da + k * 2, db + k * 2);
      wg_commit();
    }
    const uint32_t rcv = sb + cw * STAGE + 2 * SLOT + (tid & 127) * 16;
    const int row0 = cwarp * 16 + gq;
    const uint32_t tag = ld_rlx(S->epoch) + 1;
    uint4 xq[8];
    {
      uint32_t rdst, rbar;
      asm volatile("mapa.shared::cluster.u32 %0, %1, %2;" : "=r"(rdst) : "r"(rcv), "r"(j ^ 1));
      asm volatile("mapa.shared::cluster.u32 %0, %1, %2;" : "=r"(rbar) : "r"(BAR(B_RECV + cw)), "r"(j ^ 1));
      mbar_wait_cluster(BAR(B_PEER), 0);
      wg_wait<2>();
      reg_fence(hi);
      if (elect) { mbar_arrive(BAR(B_HIALL)); TRACE(4 + tr); }
#pragma unroll
      for (int i = 0; i < 8; i++) {
        const float* h = hi + (i >> 1) * 16 + (i & 1) * 2;
        asm volatile("st.async.weak.shared::cluster.mbarrier::complete_tx::bytes.v4.b32 [%0], {%1, %2, %3, %4}, [%5];"
                     ::"r"(rdst + i * 2048), "r"(pack_bf16(h[0], h[1])), "r"(pack_bf16(h[4], h[5])), "r"(pack_bf16(h[8], h[9])), "r"(pack_bf16(h[12], h[13])), "r"(rbar) : "memory");
      }
      const __nv_bfloat16* xp = x + (size_t)(t * 128 + row0) * D_ + cgrp * 128 + q4 * 8;
#pragma unroll
      for (int i = 0; i < 8; i++) xq[i] = ldg_nc(xp + (i & 1) * 8 * D_ + (i >> 1) * 32);
    }
#pragma unroll 1
    for (int s = 2; s < 4; s++) {
      wg_wait<1>();
      if (elect) mbar_arrive(BAR(B_EMPTY + s - 2));
      const uint32_t sa = sb + s * STAGE;
      const uint64_t da = make_desc(sa + cw * 8192, 16, 1024), db = make_desc(sa + SLOT, 16, 1024);
#pragma unroll
      for (int k = 0; k < 4; k++) wgmma_n128(lo, da + k * 2, db + k * 2);
      wg_commit();
    }
    wg_wait<1>();
    if (elect) { mbar_arrive(BAR(B_EMPTY + 2)); TRACE(5 + tr); }
    mbar_wait_cluster(BAR(B_RECV + cw), 0);
    if (elect) TRACE(6 + tr);
#pragma unroll
    for (int i = 0; i < 8; i++) {
      const uint4 rv = lds128u(rcv + i * 2048);
      xq[i].x = add_bf16x2(xq[i].x, rv.x); xq[i].y = add_bf16x2(xq[i].y, rv.y); xq[i].z = add_bf16x2(xq[i].z, rv.z); xq[i].w = add_bf16x2(xq[i].w, rv.w);
    }
    float4 tw[8];
#pragma unroll
    for (int i = 0; i < 8; i++) tw[i] = lds128(sb + TAB_OFF + (i >> 1) * 128 + q4 * 32 + (i & 1) * 16);
    wg_wait<0>();
    reg_fence(lo);
    if (elect) { TRACE(7 + tr); if (cw == 0) TRACE_CLK(121); }
    const bool odd = q4 & 1;
    {
      float s[2] = {0.f, 0.f}, q[2] = {0.f, 0.f}, d[2] = {0.f, 0.f};
#pragma unroll
      for (int i = 0; i < 8; i++) {
        const uint32_t z[4] = {xq[i].x, xq[i].y, xq[i].z, xq[i].w};
        const float w[8] = {tw[i & 6].x, tw[i & 6].y, tw[i & 6].z, tw[i & 6].w, tw[i | 1].x, tw[i | 1].y, tw[i | 1].z, tw[i | 1].w};
        float* v = lo + (i >> 1) * 16 + (i & 1) * 2;
#pragma unroll
        for (int k = 0; k < 4; k++) {
          const float v0 = v[4 * k] + bf_lo(z[k]), v1 = v[4 * k + 1] + bf_hi(z[k]);
          v[4 * k] = v0; v[4 * k + 1] = v1;
          s[i & 1] += v0 + v1;
          q[i & 1] = fmaf(v0, v0, fmaf(v1, v1, q[i & 1]));
          d[i & 1] = fmaf(v0, w[2 * k], fmaf(v1, w[2 * k + 1], d[i & 1]));
        }
      }
      float sa = odd ? s[1] : s[0], qa = odd ? q[1] : q[0], da = odd ? d[1] : d[0];
      sa += __shfl_xor_sync(~0u, odd ? s[0] : s[1], 1); qa += __shfl_xor_sync(~0u, odd ? q[0] : q[1], 1); da += __shfl_xor_sync(~0u, odd ? d[0] : d[1], 1);
      sa += __shfl_xor_sync(~0u, sa, 2); qa += __shfl_xor_sync(~0u, qa, 2); da += __shfl_xor_sync(~0u, da, 2);
      if (q4 < 2) st_msg(&S->stats[b * 128 + row0 + 8 * q4], __float_as_uint(sa), __float_as_uint(qa), __float_as_uint(da), 0);
    }
    if (elect) TRACE(8 + tr);
    float rstd[2], nm[2];
    uint32_t bk1, bk2;
    {
      uint4 m[4];
      const uint4* src = &S->stats[(t * 8 + (q4 >> 1) * 4) * 128 + row0 + 8 * (q4 & 1)];
      const float2 cst = lds64(sb + CST_OFF);
      int it = 0;
      while (true) {
#pragma unroll
        for (int i = 0; i < 4; i++) m[i] = ld_msg(src + 128 * i);
        if (__all_sync(~0u, (m[0].w | m[1].w | m[2].w | m[3].w) == 0)) break;
        SPIN_CHECK(it);
      }
      float sa = (__uint_as_float(m[0].x) + __uint_as_float(m[1].x)) + (__uint_as_float(m[2].x) + __uint_as_float(m[3].x));
      float qa = (__uint_as_float(m[0].y) + __uint_as_float(m[1].y)) + (__uint_as_float(m[2].y) + __uint_as_float(m[3].y));
      float da = (__uint_as_float(m[0].z) + __uint_as_float(m[1].z)) + (__uint_as_float(m[2].z) + __uint_as_float(m[3].z));
      sa += __shfl_xor_sync(~0u, sa, 2); qa += __shfl_xor_sync(~0u, qa, 2); da += __shfl_xor_sync(~0u, da, 2);
      const float mean = sa * (1.f / D_);
      const float rs = rsqrtf(fmaxf(fmaf(-mean, mean, qa * (1.f / D_)), 0.f) + 1e-5f);
      const float r = fmaf(rs, fmaf(-mean, cst.x, da), cst.y);
      uint32_t k1, k2;
      warp_top2((fkey(r) & ~2047u) | (uint32_t)(2047 - (t * 128 + row0 + 8 * (q4 & 1))), k1, k2);
      if (lane == 0) sts64u(sb + TOP_OFF + cwarp * 8, k1, k2);
      const float nmr = -mean * rs, rsx = __shfl_xor_sync(~0u, rs, 1), nmx = __shfl_xor_sync(~0u, nmr, 1);
      rstd[0] = odd ? rsx : rs; rstd[1] = odd ? rs : rsx; nm[0] = odd ? nmx : nmr; nm[1] = odd ? nmr : nmx;
      if (tid == 128) TRACE(12 + 16);
      named_bar<2, 256>();
      warp_top2(lds32u(sb + TOP_OFF + (lane & 15) * 4), bk1, bk2);
      if (tid == 128) { st_msg(&S->cand[t * 8], bk1, bk2, tag, 0); TRACE(13); }
    }
    const int lr1 = key_row(bk1) - t * 128, lr2 = key_row(bk2) - t * 128;
#pragma unroll 1
    for (int ci = 0; ci < 2; ci++) {
      const int lr = ci ? lr2 : lr1;
      if ((lr >> 4) == cwarp) {
        const bool up = lr & 8;
        const float rs = up ? rstd[1] : rstd[0], nmr = up ? nm[1] : nm[0];
#pragma unroll
        for (int a = 0; a < 4; a++) {
          uint32_t o[4];
#pragma unroll
          for (int h = 0; h < 2; h++) {
            const float4 A = lds128(sb + TAB_OFF + 1536 + a * 128 + q4 * 32 + h * 16), B = lds128(sb + TAB_OFF + 2048 + a * 128 + q4 * 32 + h * 16);
            const float* v = lo + a * 16 + h * 8;
            o[2 * h] = pack_bf16(fmaf(fmaf(up ? v[2] : v[0], rs, nmr), A.x, B.x), fmaf(fmaf(up ? v[3] : v[1], rs, nmr), A.y, B.y));
            o[2 * h + 1] = pack_bf16(fmaf(fmaf(up ? v[6] : v[4], rs, nmr), A.z, B.z), fmaf(fmaf(up ? v[7] : v[5], rs, nmr), A.w, B.w));
          }
          if (gq == (lr & 7)) st_msg(&S->rowsH[(t * 2 + ci) * 128 + cgrp * 16 + a * 4 + q4], o[0], o[1], o[2], o[3]);
        }
      }
    }
    {
      uint4* op[2];
#pragma unroll
      for (int h = 0; h < 2; h++) {
        const int lr = row0 + 8 * h;
        op[h] = (lr == lr1 || lr == lr2 ? &S->rowsB[(t * 2 + (lr == lr2)) * 128] : reinterpret_cast<uint4*>(out + (size_t)(t * 128 + lr) * D_)) + cgrp * 16 + q4;
      }
#pragma unroll
      for (int a = 0; a < 4; a++) {
        uint32_t o[2][4];
#pragma unroll
        for (int h = 0; h < 2; h++) {
          const float4 A = lds128(sb + TAB_OFF + 512 + a * 128 + q4 * 32 + h * 16), B = lds128(sb + TAB_OFF + 1024 + a * 128 + q4 * 32 + h * 16);
#pragma unroll
          for (int r = 0; r < 2; r++) {
            const float* v = lo + a * 16 + h * 8 + r * 2;
            o[r][2 * h] = pack_bf16(v[0] + fmaf(fmaf(v[0], rstd[r], nm[r]), A.x, B.x), v[1] + fmaf(fmaf(v[1], rstd[r], nm[r]), A.y, B.y));
            o[r][2 * h + 1] = pack_bf16(v[4] + fmaf(fmaf(v[4], rstd[r], nm[r]), A.z, B.z), v[5] + fmaf(fmaf(v[5], rstd[r], nm[r]), A.w, B.w));
          }
        }
        st_msg(op[0] + a * 4, o[0][0], o[0][1], o[0][2], o[0][3]);
        st_msg(op[1] + a * 4, o[1][0], o[1][1], o[1][2], o[1][3]);
      }
    }
    if (tid == 128) TRACE(15);
    uint32_t uf[64], df[64];
    if (b < NMOE) {
      mbar_wait(BAR(B_UP), 0);
      const int i4 = cwarp >> 1;
      const uint32_t u0 = sb + UP0_OFF + i4 * 8192 + wo, u1 = sb + (i4 < 2 ? 2 * STAGE + 2 * SLOT + i4 * 8192 : i4 == 2 ? UP0_OFF - 8192 : 0) + wo;
#pragma unroll
      for (int i = 0; i < 16; i++) ldsm_x4_t(((i < 8 ? u0 : u1) + ((i >> 1) & 3) * 1024) ^ ((i & 1) << 5), uf + i * 4);
    }
    if (tid == 128) TRACE(29);
    mbar_wait(BAR(B_SEL), 0);
    const float2 selv = lds64(sb + SEL_OFF);
    const uint32_t key1 = __float_as_uint(selv.x), key2 = __float_as_uint(selv.y);
    const int tA = key_row(key1) >> 7, tB = key_row(key2) >> 7;
    const int slotA = tA * 2, slotB = tB * 2 + (tA == tB ? 1 : 0);
    const int fn = (lane >> 3) & 1, fcol = (b >> 1) * 16 + (b & 1) * 4 + q4 + ((lane >> 2) & 1) * 8;
    uint32_t fbase = SENT; float fgb = 0.f;
    const uint32_t* fbp = reinterpret_cast<const uint32_t*>(&S->rowsB[(fn ? slotB : slotA) * 128]) + (fcol >> 1);
    if (b < NMOE) {
      uint4 hb[4];
      const uint4* src = &S->rowsH[((gq & 1) ? slotB : slotA) * 128 + cwarp * 8 + q4];
#pragma unroll
      for (int i = 0; i < 4; i++) hb[i] = ld_msg(src + (i >> 1) * 64 + (i & 1) * 4);
      mbar_wait(BAR(B_DN), 0);
      {
        const int fr = ((lane & 7) >> 1) + (lane & 1) * 8 + (lane >> 4) * 4;
        const uint32_t db = sb + ((cwarp + 1) >> 2) * STAGE + ((cwarp + 1) & 3) * 8192 + fr * 128 + ((((lane >> 3) & 1) ^ (fr & 7)) << 4);
#pragma unroll
        for (int i = 0; i < 16; i++) ldsm_x4_t((db + (i >> 3) * 4096 + (i & 1) * 2048) ^ (((i >> 1) & 3) << 5), df + i * 4);
      }
      int it = 0;
      while (!__all_sync(~0u, hb[0].x != SENT && hb[1].x != SENT && hb[2].x != SENT && hb[3].x != SENT)) {
#pragma unroll
        for (int i = 0; i < 4; i++) hb[i] = ld_msg(src + (i >> 1) * 64 + (i & 1) * 4);
        SPIN_CHECK(it);
      }
      if (tid == 128) TRACE(16);
      float c[4][4];
#pragma unroll
      for (int i = 0; i < 4; i++) c[i][0] = c[i][1] = c[i][2] = c[i][3] = 0.f;
#pragma unroll
      for (int ks = 0; ks < 8; ks++) {
        const uint32_t b0 = (ks & 1) ? hb[ks >> 1].z : hb[ks >> 1].x, b1 = (ks & 1) ? hb[ks >> 1].w : hb[ks >> 1].y;
        mma_16816(c[0], wf + ks * 8, b0, b1); mma_16816(c[1], wf + ks * 8 + 4, b0, b1);
        mma_16816(c[2], uf + ks * 8, b0, b1); mma_16816(c[3], uf + ks * 8 + 4, b0, b1);
      }
      {
        float v[4];
#pragma unroll
        for (int i = 0; i < 4; i++) v[i] = (q4 & 2) ? (odd ? c[3][i] : c[2][i]) : (odd ? c[1][i] : c[0][i]);
        sts128(sb + RED_OFF + cwarp * 512 + (q4 * 8 + gq) * 16, v[0], v[2], v[1], v[3]);
      }
    }
    if (cwarp == 0) { fbase = ld_rlx(fbp); fgb = __uint_as_float(ld_rlx(S->mod + 5 * D_ + fcol)); }
    if (b < NMOE) {
      named_bar<2, 256>();
      float g0 = 0.f, g1 = 0.f, u0 = 0.f, u1 = 0.f;
#pragma unroll
      for (int w = 0; w < 8; w++) {
        const float2 gv = lds64(sb + RED_OFF + w * 512 + lane * 8), uv = lds64(sb + RED_OFF + w * 512 + 256 + lane * 8);
        g0 += gv.x; g1 += gv.y; u0 += uv.x; u1 += uv.y;
      }
      const uint32_t gp = pack_bf16(g0, g1), up = pack_bf16(u0, u1), sp = pack_bf16(silu_f(bf_lo(gp)), silu_f(bf_hi(gp)));
      const uint32_t act = pack_bf16(bf_lo(sp) * bf_lo(up), bf_hi(sp) * bf_hi(up));
      uint32_t ab[4];
#pragma unroll
      for (int i = 0; i < 4; i++) ab[i] = __shfl_sync(~0u, act, i * 8 + q4 * 2 + (gq & 1));
      if (tid == 128) TRACE(31);
#pragma unroll
      for (int T = 0; T < 2; T++) {
        float c[4][4];
#pragma unroll
        for (int i = 0; i < 4; i++) {
          c[i][0] = c[i][1] = c[i][2] = c[i][3] = 0.f;
          mma_16816(c[i], df + (T * 4 + i) * 8, ab[0], ab[1]); mma_16816(c[i], df + (T * 4 + i) * 8 + 4, ab[2], ab[3]);
        }
        float v[4];
#pragma unroll
        for (int i = 0; i < 4; i++) v[i] = (q4 & 2) ? (odd ? c[3][i] : c[2][i]) : (odd ? c[1][i] : c[0][i]);
        st_msg(&S->part[((cwarp * 16 + T * 8 + q4 * 2 + (gq >> 2)) * 128 + b) * 4 + (gq & 3)], __float_as_uint(v[0]), __float_as_uint(v[1]), __float_as_uint(v[2]), __float_as_uint(v[3]));
      }
      if (tid == 128) TRACE(32);
    }
    if (cwarp == 0) {
      const uint32_t fk = fn ? key2 : key1;
      const float sg = round_bf16(sigmoid_f(round_bf16(fkey_inv((fk & ~2047u) | 1024u))));
      int it = 0;
      while (fbase == SENT) { fbase = ld_rlx(fbp); SPIN_CHECK(it); }
      spin(b < NMOE ? FK_PDELAY : FK_PDELAY + 1200);
      uint4 m[14];
      while (true) {
        bool ok = true;
#pragma unroll
        for (int i = 0; i < 14; i++) { m[i] = ld_msg(&S->part[b * 512 + i * 32 + lane]); ok &= m[i].x != SENT; }
        if (__all_sync(~0u, ok)) break;
        SPIN_CHECK(it);
      }
      if (lane == 0) TRACE(33);
      float y[4] = {0.f, 0.f, 0.f, 0.f};
#pragma unroll
      for (int i = 0; i < 14; i++) { y[0] += __uint_as_float(m[i].x); y[1] += __uint_as_float(m[i].y); y[2] += __uint_as_float(m[i].z); y[3] += __uint_as_float(m[i].w); }
      const bool b2 = lane & 4;
      float y0 = (b2 ? y[2] : y[0]) + __shfl_xor_sync(~0u, b2 ? y[0] : y[2], 4), y1 = (b2 ? y[3] : y[1]) + __shfl_xor_sync(~0u, b2 ? y[1] : y[3], 4);
      y0 = (fn ? y1 : y0) + __shfl_xor_sync(~0u, fn ? y0 : y1, 8);
      y0 += __shfl_xor_sync(~0u, y0, 16);
      const float upd = round_bf16(round_bf16(y0) * sg);
      if (lane < 16) out[(size_t)key_row(fk) * D_ + fcol] = __float2bfloat16_rn(fmaf(fgb, upd, (fcol & 1) ? bf_hi(fbase) : bf_lo(fbase)));
      if (lane == 0) {
        TRACE(34); TRACE_CLK(122);
        if (b == 0) S->epoch[0] = tag;
      }
    }
  }
}

typedef CUresult (*PFN_encodeTiled)(CUtensorMap*, CUtensorMapDataType, cuuint32_t, void*, const cuuint64_t*, const cuuint64_t*,
                                    const cuuint32_t*, const cuuint32_t*, CUtensorMapInterleave, CUtensorMapSwizzle,
                                    CUtensorMapL2promotion, CUtensorMapFloatOOBfill);

static void mapnd(PFN_encodeTiled enc, CUtensorMap* m, const void* p, int nd, const cuuint64_t* dims, const cuuint64_t* str, const cuuint32_t* box,
                  CUtensorMapSwizzle sw, CUtensorMapL2promotion pr) {
  const cuuint32_t es[5] = {1, 1, 1, 1, 1};
  enc(m, CU_TENSOR_MAP_DATA_TYPE_BFLOAT16, nd, (void*)p, dims, str, box, es, CU_TENSOR_MAP_INTERLEAVE_NONE, sw, pr, CU_TENSOR_MAP_FLOAT_OOB_FILL_NONE);
}
static void map2d(PFN_encodeTiled enc, CUtensorMap* m, const void* p, uint64_t rows, uint64_t cols, uint32_t brows, uint32_t bcols,
                  CUtensorMapSwizzle sw = CU_TENSOR_MAP_SWIZZLE_128B, CUtensorMapL2promotion pr = CU_TENSOR_MAP_L2_PROMOTION_L2_128B) {
  const cuuint64_t dims[2] = {cols, rows}, str[1] = {cols * 2}; const cuuint32_t box[2] = {bcols, brows};
  mapnd(enc, m, p, 2, dims, str, box, sw, pr);
}
static void map3d(PFN_encodeTiled enc, CUtensorMap* m, const void* p, uint64_t rows, uint64_t cols, uint32_t brows, uint32_t bgroups) {
  const cuuint64_t dims[3] = {64, rows, cols / 64}, str[2] = {cols * 2, 128}; const cuuint32_t box[3] = {64, brows, bgroups};
  mapnd(enc, m, p, 3, dims, str, box, CU_TENSOR_MAP_SWIZZLE_128B, CU_TENSOR_MAP_L2_PROMOTION_L2_128B);
}
static void map5d(PFN_encodeTiled enc, CUtensorMap* m, const void* p) {
  const cuuint64_t rb = F_ * 2, dims[5] = {F_, 2, 4, 4, 32}, str[4] = {rb, 8 * rb, 2 * rb, 32 * rb}; const cuuint32_t box[5] = {32, 2, 4, 4, 4};
  mapnd(enc, m, p, 5, dims, str, box, CU_TENSOR_MAP_SWIZZLE_64B, CU_TENSOR_MAP_L2_PROMOTION_L2_64B);
}

}

extern "C" void kernel_launch(void* const* d_in, const int* in_sizes, int n_in, void* d_out, int out_size) {
  using namespace fk;
  (void)in_sizes; (void)n_in; (void)out_size;
  static PFN_encodeTiled enc = nullptr;
  static Scratch* scr = nullptr;
  if (!enc) {
    void* fn = nullptr; cudaDriverEntryPointQueryResult qr;
    cudaGetDriverEntryPoint("cuTensorMapEncodeTiled", &fn, cudaEnableDefault, &qr);
    enc = (PFN_encodeTiled)fn;
    cudaGetSymbolAddress((void**)&scr, g_scr);
    cudaFuncSetAttribute(fused_kernel, cudaFuncAttributeMaxDynamicSharedMemorySize, SMEM_BYTES);
  }
  typedef const __nv_bfloat16* bp;
  Params prm;
  prm.w_r = (bp)d_in[6];
  map2d(enc, &prm.ws[0], d_in[1], S_, S_, 128, 64);
  map2d(enc, &prm.ws[1], d_in[2], S_, S_, 128, 64);
  map3d(enc, &prm.n, scr->n, S_, D_, 64, 4);
  map2d(enc, &prm.wm, d_in[11], D_, 6 * D_, 64, 48, CU_TENSOR_MAP_SWIZZLE_NONE, CU_TENSOR_MAP_L2_PROMOTION_NONE);
  map2d(enc, &prm.p, scr->P, 2 * S_, D_, 128, 64);
  map2d(enc, &prm.w2, scr->W2, 2 * D_, D_, 256, 64);
  map5d(enc, &prm.wg, d_in[7]);
  map5d(enc, &prm.wu, d_in[8]);
  map3d(enc, &prm.wdn, d_in[9], F_, D_, 32, 2);

  fused_kernel<<<NCTA, 384, SMEM_BYTES, cudaStreamPerThread>>>((bp)d_in[0], scr, (__nv_bfloat16*)d_out, (bp)d_in[10], (bp)d_in[3], (bp)d_in[4], prm);
}
```

```cpp
#include <cuda_runtime.h>
#include <cuda_bf16.h>
#include <cuda.h>
#include <stdint.h>

#define DEVINL __device__ __forceinline__

namespace fk {

constexpr int S_ = 2048, D_ = 1024, F_ = 3584;
constexpr int NCTA = 128;
constexpr int NMOE = 112;
constexpr int SLOT = 16384;
constexpr int STAGE = 3 * SLOT;
constexpr int SP_OFF = 4 * STAGE;
constexpr int MISC_OFF = SP_OFF + 32768;
constexpr int SMEM_BYTES = MISC_OFF + 3072;
constexpr int BAR_OFF = MISC_OFF;
constexpr int SEL_OFF = MISC_OFF + 320;
constexpr int CST_OFF = MISC_OFF + 336;
constexpr int TOP_OFF = MISC_OFF + 352;
constexpr int TAB_OFF = MISC_OFF + 512;
constexpr int RKA_OFF = SP_OFF + 24576;
constexpr int RKB_OFF = RKA_OFF + 2048;
constexpr int RED_OFF = RKB_OFF + 2048;
constexpr int UP0_OFF = 3 * STAGE + 2 * SLOT + 8192;

enum { B_FULL = 0, B_EMPTY = 4, B_PREADY = 8, B_MF = 12  , B_UP = 20, B_DN = 21, B_TAB = 22, B_HIALL = 23, B_PEER = 24,
       B_RECV = 25  , B_SEL = 27, B_WFREE = 28  , B_RESET = 30, B_WFULL = 31, B_RSDONE = 32 };
constexpr unsigned long long CNT_LO = 0x1111888833331111ull, CNT_HI = 0x0088111222131111ull;

#define FK_WSPF 6
#define FK_G0 15
#define FK_G1 31
#define FK_GX 40
#define FK_PDELAY 500
constexpr int SPIN_LIMIT = 1 << 20;
constexpr uint32_t SENT = 0xFFFFFFFFu;

struct Scratch {
  uint4 part[128 * 128 * 4];
  uint4 stats[128 * 128];
  uint4 rowsH[32 * 128];
  uint4 rowsB[32 * 128];
  uint4 cand[16 * 8];
  uint2 rs[2 * S_];
  uint4 cst[8];
  float mod[2][6 * D_];
  uint2 u[2 * D_];
  unsigned flagP[128 * 4 * 8];
  unsigned cntN[32 * 32];
  unsigned cntW[8 * 32];
  unsigned cntMod[2 * 32];
  unsigned epoch[32];
  alignas(1024) __nv_bfloat16 n[S_ * D_];
  __nv_bfloat16 W2[2 * D_ * D_];
  __nv_bfloat16 P[2 * S_ * D_];
};
__device__ __align__(1024) Scratch g_scr;

struct Params {
  CUtensorMap ws[2];
  CUtensorMap n;
  CUtensorMap wm;
  CUtensorMap p;
  CUtensorMap w2;
  CUtensorMap wg, wu;
  CUtensorMap wdn;
  const __nv_bfloat16* w_r;
  const char* we[3];
  const char* wsp[2];
};

DEVINL uint32_t smem_u32(const void* p) { return (uint32_t)__cvta_generic_to_shared(p); }
DEVINL void mbar_init(uint32_t bar, uint32_t cnt) { asm volatile("mbarrier.init.shared::cta.b64 [%0], %1;" ::"r"(bar), "r"(cnt) : "memory"); }
DEVINL void mbar_expect_tx(uint32_t bar, uint32_t bytes) { asm volatile("mbarrier.arrive.expect_tx.shared::cta.b64 _, [%0], %1;" ::"r"(bar), "r"(bytes) : "memory"); }
DEVINL void mbar_arrive(uint32_t bar) { asm volatile("mbarrier.arrive.shared::cta.b64 _, [%0];" ::"r"(bar) : "memory"); }
DEVINL void mbar_wait(uint32_t bar, uint32_t parity) {
  asm volatile("{\n.reg .pred p;\n.reg .u32 c;\nmov.u32 c, 0;\n"
               "LW:\nmbarrier.try_wait.parity.shared::cta.b64 p, [%0], %1;\n@p bra LD;\n"
               "add.u32 c, c, 1;\nsetp.lt.u32 p, c, 1048576;\n@p bra LW;\ntrap;\nLD:\n}" ::"r"(bar), "r"(parity) : "memory");
}
DEVINL void mbar_wait_cluster(uint32_t bar, uint32_t parity) {
  asm volatile("{\n.reg .pred p;\n.reg .u32 c;\nmov.u32 c, 0;\n"
               "LW:\nmbarrier.try_wait.parity.acquire.cluster.shared::cta.b64 p, [%0], %1;\n@p bra LD;\n"
               "add.u32 c, c, 1;\nsetp.lt.u32 p, c, 1048576;\n@p bra LW;\ntrap;\nLD:\n}" ::"r"(bar), "r"(parity) : "memory");
}
#define SPIN_CHECK(it) if (++(it) > SPIN_LIMIT) __trap()
DEVINL void fence_async_smem() { asm volatile("fence.proxy.async.shared::cta;" ::: "memory"); }
DEVINL void fence_async_global() { asm volatile("fence.proxy.async.global;" ::: "memory"); }
DEVINL void fence_gpu() { asm volatile("fence.acq_rel.gpu;" ::: "memory"); }
template <int ID, int N> DEVINL void named_bar() { asm volatile("bar.sync %0, %1;" ::"n"(ID), "n"(N) : "memory"); }
DEVINL bool elect_one() { uint32_t p; asm volatile("{\n.reg .pred e;\nelect.sync _|e, 0xffffffff;\nselp.u32 %0, 1, 0, e;\n}" : "=r"(p)); return p; }
DEVINL unsigned clk32() { unsigned c; asm volatile("mov.u32 %0, %%clock;" : "=r"(c)); return c; }
DEVINL void spin(unsigned n) { const unsigned c = clk32(); while (clk32() - c < n) {} }

DEVINL void tma_2d(uint32_t dst, const CUtensorMap* m, int x, int y, uint32_t bar) {
  asm volatile("cp.async.bulk.tensor.2d.shared::cluster.global.mbarrier::complete_tx::bytes [%0], [%1, {%3, %4}], [%2];"
               ::"r"(dst), "l"(m), "r"(bar), "r"(x), "r"(y) : "memory");
}
DEVINL void tma_2d_hint(uint32_t dst, const CUtensorMap* m, int x, int y, uint32_t bar, uint64_t pol) {
  asm volatile("cp.async.bulk.tensor.2d.shared::cluster.global.mbarrier::complete_tx::bytes.L2::cache_hint [%0], [%1, {%3, %4}], [%2], %5;"
               ::"r"(dst), "l"(m), "r"(bar), "r"(x), "r"(y), "l"(pol) : "memory");
}
DEVINL void tma_3d(uint32_t dst, const CUtensorMap* m, int y, int z, uint32_t bar) {
  asm volatile("cp.async.bulk.tensor.3d.shared::cluster.global.mbarrier::complete_tx::bytes [%0], [%1, {0, %3, %4}], [%2];"
               ::"r"(dst), "l"(m), "r"(bar), "r"(y), "r"(z) : "memory");
}
DEVINL void tma_5d(uint32_t dst, const CUtensorMap* m, int x, int a, uint32_t bar) {
  asm volatile("cp.async.bulk.tensor.5d.shared::cluster.global.mbarrier::complete_tx::bytes [%0], [%1, {%3, 0, 0, 0, %4}], [%2];"
               ::"r"(dst), "l"(m), "r"(bar), "r"(x), "r"(a) : "memory");
}
DEVINL void tma_store_2d(const CUtensorMap* m, uint32_t src, int x, int y) {
  asm volatile("cp.async.bulk.tensor.2d.global.shared::cta.bulk_group [%0, {%2, %3}], [%1];" ::"l"(m), "r"(src), "r"(x), "r"(y) : "memory");
}
DEVINL void pf_3d(const CUtensorMap* m, int y, int z) {
  asm volatile("cp.async.bulk.prefetch.tensor.3d.L2.global [%0, {0, %1, %2}];" ::"l"(m), "r"(y), "r"(z) : "memory");
}
DEVINL void pf_5d(const CUtensorMap* m, int x, int a) {
  asm volatile("cp.async.bulk.prefetch.tensor.5d.L2.global [%0, {%1, 0, 0, 0, %2}];" ::"l"(m), "r"(x), "r"(a) : "memory");
}
DEVINL void bulk_store(void* dst, uint32_t src, uint32_t bytes) {
  asm volatile("cp.async.bulk.global.shared::cta.bulk_group [%0], [%1], %2;" ::"l"(dst), "r"(src), "r"(bytes) : "memory");
}
DEVINL void bulk_load(uint32_t dst, const void* src, uint32_t bytes, uint32_t bar) {
  asm volatile("cp.async.bulk.shared::cluster.global.mbarrier::complete_tx::bytes [%0], [%1], %2, [%3];" ::"r"(dst), "l"(src), "r"(bytes), "r"(bar) : "memory");
}
template <int N> DEVINL void bulk_wait_read() { asm volatile("cp.async.bulk.wait_group.read %0;" ::"n"(N) : "memory"); }
DEVINL void pf_bulk(const void* p, uint32_t bytes) { asm volatile("cp.async.bulk.prefetch.L2.global [%0], %1;" ::"l"(p), "r"(bytes) : "memory"); }
DEVINL void bulk_commit() { asm volatile("cp.async.bulk.commit_group;" ::: "memory"); }
template <int N> DEVINL void bulk_wait() { asm volatile("cp.async.bulk.wait_group %0;" ::"n"(N) : "memory"); }
DEVINL void prefetch_tmap(const CUtensorMap* m) { asm volatile("prefetch.tensormap [%0];" ::"l"(m) : "memory"); }

DEVINL void wg_fence() { asm volatile("wgmma.fence.sync.aligned;" ::: "memory"); }
DEVINL void wg_commit() { asm volatile("wgmma.commit_group.sync.aligned;" ::: "memory"); }
template <int N> DEVINL void wg_wait() { asm volatile("wgmma.wait_group.sync.aligned %0;" ::"n"(N) : "memory"); }
DEVINL uint64_t make_desc(uint32_t addr, uint32_t lbo, uint32_t sbo, uint64_t sw = 1) {
  return (uint64_t)((addr & 0x3FFFF) >> 4) | ((uint64_t)(lbo >> 4) << 16) | ((uint64_t)(sbo >> 4) << 32) | (sw << 62);
}

#define R8(a, o) "+f"(a[o]), "+f"(a[o + 1]), "+f"(a[o + 2]), "+f"(a[o + 3]), "+f"(a[o + 4]), "+f"(a[o + 5]), "+f"(a[o + 6]), "+f"(a[o + 7])
#define R64(a, o) R8(a, o), R8(a, o + 8), R8(a, o + 16), R8(a, o + 24), R8(a, o + 32), R8(a, o + 40), R8(a, o + 48), R8(a, o + 56)
#define ACC64 "{%0, %1, %2, %3, %4, %5, %6, %7, %8, %9, %10, %11, %12, %13, %14, %15, "              \
              "%16, %17, %18, %19, %20, %21, %22, %23, %24, %25, %26, %27, %28, %29, %30, %31, "    \
              "%32, %33, %34, %35, %36, %37, %38, %39, %40, %41, %42, %43, %44, %45, %46, %47, "    \
              "%48, %49, %50, %51, %52, %53, %54, %55, %56, %57, %58, %59, %60, %61, %62, %63"
#define ACC128 ACC64 ", %64, %65, %66, %67, %68, %69, %70, %71, %72, %73, %74, %75, %76, %77, %78, %79, "      \
              "%80, %81, %82, %83, %84, %85, %86, %87, %88, %89, %90, %91, %92, %93, %94, %95, "               \
              "%96, %97, %98, %99, %100, %101, %102, %103, %104, %105, %106, %107, %108, %109, %110, %111, "   \
              "%112, %113, %114, %115, %116, %117, %118, %119, %120, %121, %122, %123, %124, %125, %126, %127"
template <int TB> DEVINL void wgmma_n256(float (&d)[128], uint64_t da, uint64_t db, int scale_d) {
  asm volatile("{\n.reg .pred p;\nsetp.ne.b32 p, %130, 0;\n"
               "wgmma.mma_async.sync.aligned.m64n256k16.f32.bf16.bf16 " ACC128 "}, %128, %129, p, 1, 1, 0, %131;\n}\n"
               : R64(d, 0), R64(d, 64) : "l"(da), "l"(db), "r"(scale_d), "n"(TB));
}
template <int SC> DEVINL void wgmma_n256_rs(float (&d)[128], const uint32_t* a, uint64_t db) {
  asm volatile("{\n.reg .pred p;\nsetp.ne.b32 p, %133, 0;\n"
               "wgmma.mma_async.sync.aligned.m64n256k16.f32.bf16.bf16 " ACC128 "}, {%128, %129, %130, %131}, %132, p, 1, 1, 0;\n}\n"
               : R64(d, 0), R64(d, 64) : "r"(a[0]), "r"(a[1]), "r"(a[2]), "r"(a[3]), "l"(db), "n"(SC));
}
DEVINL void wgmma_n128(float (&d)[64], uint64_t da, uint64_t db) {
  asm volatile("wgmma.mma_async.sync.aligned.m64n128k16.f32.bf16.bf16 " ACC64 "}, %64, %65, 1, 1, 1, 0, 0;\n" : R64(d, 0) : "l"(da), "l"(db));
}
template <int N> DEVINL void reg_fence(float (&a)[N]) {
#pragma unroll
  for (int i = 0; i < N; i++) asm volatile("" : "+f"(a[i])::"memory");
}

DEVINL uint32_t pack_bf16(float lo, float hi) { uint32_t r; asm("cvt.rn.bf16x2.f32 %0, %1, %2;" : "=r"(r) : "f"(hi), "f"(lo)); return r; }
DEVINL uint32_t add_bf16x2(uint32_t a, uint32_t b) { uint32_t r; asm("add.rn.bf16x2 %0, %1, %2;" : "=r"(r) : "r"(a), "r"(b)); return r; }
DEVINL uint32_t mul_bf16x2(uint32_t a, uint32_t b) { uint32_t r; asm("mul.rn.bf16x2 %0, %1, %2;" : "=r"(r) : "r"(a), "r"(b)); return r; }
DEVINL uint32_t fma_bf16x2(uint32_t a, uint32_t b, uint32_t c) { uint32_t r; asm("fma.rn.bf16x2 %0, %1, %2, %3;" : "=r"(r) : "r"(a), "r"(b), "r"(c)); return r; }
DEVINL float bf_lo(uint32_t w) { return __uint_as_float(w << 16); }
DEVINL float bf_hi(uint32_t w) { return __uint_as_float(w & 0xFFFF0000u); }
DEVINL float round_bf16(float v) { return bf_lo(pack_bf16(v, 0.f)); }
DEVINL float sigmoid_f(float v) { float r; asm("rcp.approx.ftz.f32 %0, %1;" : "=f"(r) : "f"(1.f + __expf(-v))); return r; }
DEVINL float silu_f(float v) { return v * sigmoid_f(v); }
DEVINL void stsm_x4(uint32_t addr, const uint32_t* r) {
  asm volatile("stmatrix.sync.aligned.m8n8.x4.shared.b16 [%0], {%1, %2, %3, %4};" ::"r"(addr), "r"(r[0]), "r"(r[1]), "r"(r[2]), "r"(r[3]) : "memory");
}
DEVINL void ldsm_x4_t(uint32_t addr, uint32_t* r) {
  asm volatile("ldmatrix.sync.aligned.m8n8.x4.trans.shared.b16 {%0, %1, %2, %3}, [%4];" : "=r"(r[0]), "=r"(r[1]), "=r"(r[2]), "=r"(r[3]) : "r"(addr) : "memory");
}
DEVINL void mma_16816(float (&c)[4], const uint32_t* a, uint32_t b0, uint32_t b1) {
  asm("mma.sync.aligned.m16n8k16.row.col.f32.bf16.bf16.f32 {%0, %1, %2, %3}, {%4, %5, %6, %7}, {%8, %9}, {%0, %1, %2, %3};"
      : "+f"(c[0]), "+f"(c[1]), "+f"(c[2]), "+f"(c[3]) : "r"(a[0]), "r"(a[1]), "r"(a[2]), "r"(a[3]), "r"(b0), "r"(b1));
}
DEVINL float4 lds128(uint32_t a) { float4 v; asm volatile("ld.shared.v4.f32 {%0, %1, %2, %3}, [%4];" : "=f"(v.x), "=f"(v.y), "=f"(v.z), "=f"(v.w) : "r"(a)); return v; }
DEVINL uint4 lds128u(uint32_t a) { uint4 v; asm volatile("ld.shared.v4.u32 {%0, %1, %2, %3}, [%4];" : "=r"(v.x), "=r"(v.y), "=r"(v.z), "=r"(v.w) : "r"(a)); return v; }
DEVINL float2 lds64(uint32_t a) { float2 v; asm volatile("ld.shared.v2.f32 {%0, %1}, [%2];" : "=f"(v.x), "=f"(v.y) : "r"(a)); return v; }
DEVINL uint32_t lds32u(uint32_t a) { uint32_t v; asm volatile("ld.shared.u32 %0, [%1];" : "=r"(v) : "r"(a)); return v; }
DEVINL void sts128(uint32_t a, float x, float y, float z, float w) { asm volatile("st.shared.v4.f32 [%0], {%1, %2, %3, %4};" ::"r"(a), "f"(x), "f"(y), "f"(z), "f"(w) : "memory"); }
DEVINL void sts128u(uint32_t a, uint32_t x, uint32_t y, uint32_t z, uint32_t w) { asm volatile("st.shared.v4.u32 [%0], {%1, %2, %3, %4};" ::"r"(a), "r"(x), "r"(y), "r"(z), "r"(w) : "memory"); }
DEVINL void sts64u(uint32_t a, uint32_t x, uint32_t y) { asm volatile("st.shared.v2.u32 [%0], {%1, %2};" ::"r"(a), "r"(x), "r"(y) : "memory"); }
DEVINL void sts32(uint32_t a, float v) { asm volatile("st.shared.f32 [%0], %1;" ::"r"(a), "f"(v) : "memory"); }

DEVINL uint4 ld_msg(const void* p) {
  unsigned long long a, b;
  asm volatile("{\n.reg .b128 r;\nld.relaxed.gpu.global.b128 r, [%2];\nmov.b128 {%0, %1}, r;\n}" : "=l"(a), "=l"(b) : "l"(p) : "memory");
  return make_uint4((uint32_t)a, (uint32_t)(a >> 32), (uint32_t)b, (uint32_t)(b >> 32));
}
DEVINL void st_msg(void* p, uint32_t x, uint32_t y, uint32_t z, uint32_t w) {
  unsigned long long a = (unsigned long long)x | ((unsigned long long)y << 32), b = (unsigned long long)z | ((unsigned long long)w << 32);
  asm volatile("{\n.reg .b128 r;\nmov.b128 r, {%1, %2};\nst.relaxed.gpu.global.b128 [%0], r;\n}" ::"l"(p), "l"(a), "l"(b) : "memory");
}
DEVINL uint2 ld_msg8(const void* p) {
  unsigned long long a;
  asm volatile("ld.relaxed.gpu.global.b64 %0, [%1];" : "=l"(a) : "l"(p) : "memory");
  return make_uint2((uint32_t)a, (uint32_t)(a >> 32));
}
DEVINL void st_msg8(void* p, uint32_t x, uint32_t y) {
  asm volatile("st.relaxed.gpu.global.b64 [%0], %1;" ::"l"(p), "l"((unsigned long long)x | ((unsigned long long)y << 32)) : "memory");
}
DEVINL unsigned ld_rlx(const void* p) { unsigned v; asm volatile("ld.relaxed.gpu.global.u32 %0, [%1];" : "=r"(v) : "l"(p) : "memory"); return v; }
DEVINL void st_rlx(unsigned* p, unsigned v) { asm volatile("st.relaxed.gpu.global.u32 [%0], %1;" ::"l"(p), "r"(v) : "memory"); }
DEVINL void red_add(unsigned* p, unsigned v) { asm volatile("red.relaxed.gpu.global.add.u32 [%0], %1;" ::"l"(p), "r"(v) : "memory"); }
DEVINL uint4 ldg_nc(const void* p) {
  uint4 v;
  asm volatile("ld.global.nc.L1::no_allocate.v4.u32 {%0, %1, %2, %3}, [%4];" : "=r"(v.x), "=r"(v.y), "=r"(v.z), "=r"(v.w) : "l"(p));
  return v;
}
DEVINL float4 ldg_cg(const float* p) { float4 v; asm volatile("ld.global.cg.v4.f32 {%0, %1, %2, %3}, [%4];" : "=f"(v.x), "=f"(v.y), "=f"(v.z), "=f"(v.w) : "l"(p) : "memory"); return v; }
DEVINL void wait_cnt(const unsigned* p, unsigned target) {
  int it = 0;
  while ((int)(ld_rlx(p) - target) < 0) { SPIN_CHECK(it); __nanosleep(100); }
}

#define TRACE(id)
#define TRACE_CLK(id)

DEVINL uint32_t fkey(float v) { const uint32_t u = __float_as_uint(v); return (u & 0x80000000u) ? ~u : (u | 0x80000000u); }
DEVINL float fkey_inv(uint32_t k) { return __uint_as_float((k & 0x80000000u) ? (k & 0x7FFFFFFFu) : ~k); }
DEVINL uint32_t redux_max(uint32_t v) { uint32_t r; asm volatile("redux.sync.max.u32 %0, %1, 0xffffffff;" : "=r"(r) : "r"(v)); return r; }
DEVINL void warp_top2(uint32_t key, uint32_t& k1, uint32_t& k2) { k1 = redux_max(key); k2 = redux_max(key == k1 ? 0u : key); }
DEVINL int key_row(uint32_t k) { return 2047 - (int)(k & 2047u); }
DEVINL int perm32(int e) { return (e & ~30) | ((e >> 2) & 6) | ((e << 2) & 24); }

__global__ void __launch_bounds__(384, 1) __cluster_dims__(2, 1, 1)
fused_kernel(const __nv_bfloat16* __restrict__ x, Scratch* const S, __nv_bfloat16* __restrict__ out, const __nv_bfloat16* __restrict__ cvec,
             const __nv_bfloat16* __restrict__ wd_re, const __nv_bfloat16* __restrict__ wd_im, const __grid_constant__ Params prm) {
  extern __shared__ __align__(1024) uint8_t smem_raw[];
  const uint32_t sb = smem_u32(smem_raw);
  const int tid = threadIdx.x, lane = tid & 31;
  const int warp = __shfl_sync(~0u, tid >> 5, 0);
  const int b = blockIdx.x;
  const int j = b & 1, m4 = (b >> 1) & 3, t = b >> 3;
  const int cgrp = b & 7;
  auto BAR = [&](int i) { return sb + BAR_OFF + i * 8; };

  uint4 xr[4];
  if ((warp & ~1) == 2) {
    const uint4* src = reinterpret_cast<const uint4*>(x + (size_t)((warp - 2) * 128 + b) * D_) + lane;
#pragma unroll
    for (int i = 0; i < 4; i++) xr[i] = ldg_nc(src + 32 * i);
  }
  if (tid == 0) TRACE(0);
  if ((warp & ~1) != 2 && elect_one()) {
    const int w = warp < 2 ? warp : warp - 2;
#pragma unroll
    for (int k = 0; k < 3; k++) {
      const int i = w + 10 * k;
      mbar_init(BAR(i), (uint32_t)((i < 16 ? CNT_LO : CNT_HI) >> ((i & 15) * 4)) & 15u);
    }
    if (w >= 7) mbar_init(BAR(w + 23), 1);
    if (w < 4) mbar_expect_tx(BAR(B_FULL + w), STAGE);
    if (w == B_RECV - 20 || w == B_RECV - 19) mbar_expect_tx(BAR(w + 20), SLOT);
    asm volatile("fence.mbarrier_init.release.cluster;" ::: "memory");
    if (w == 0) tma_2d(sb, &prm.ws[j], 0, t * 128, BAR(B_FULL));
    else if (w < 8) prefetch_tmap(&prm.ws[1] + w);
  }
  __syncthreads();
  asm volatile("barrier.cluster.arrive.relaxed.aligned;" ::: "memory");

  if (warp < 4) {
    auto prefetch_piece = [&](int g) {
      if ((unsigned)(g - FK_GX) < 4u) {
        const __nv_bfloat16* xp = x + (size_t)(t * 128 + (g - FK_GX) * 32 + (lane >> 1)) * D_ + cgrp * 128 + (lane & 1) * 64;
        asm volatile("prefetch.global.L2 [%0];" ::"l"(xp));
        asm volatile("prefetch.global.L2 [%0];" ::"l"(xp + 16 * D_));
      }
      int p = g < FK_G1 ? (g - FK_G0) >> 1 : (FK_G1 - FK_G0) / 2 + (g - FK_G1) * 2;
      const int pe = g < FK_G1 ? (g - FK_G0 + 1) >> 1 : p + 2;
#pragma unroll 1
      for (; p < pe; p++)
        if ((unsigned)p < 42u) {
          const int m = (p * 37) >> 9;
          if (elect_one()) pf_bulk(prm.we[m] + (p - m * 14) * 524288 + b * 4096, 4096);
        }
    };
    if (warp == 0) {
      const unsigned* flagAddr = &S->cntN[lane * 32];
      const unsigned tgt = (ld_rlx(S->epoch) + 1) * 64u;
      unsigned ready = 0, pend = tgt - 1;
#pragma unroll 1
      for (int g = 0; g < 32; g++) {
        const int s = g & 3;
        ready |= __ballot_sync(~0u, pend == tgt);
        int it = 0;
        while (!((ready >> g) & 1)) {
          ready |= __ballot_sync(~0u, (unsigned)(lane - g) < 4u && ld_rlx(flagAddr) == tgt);
          SPIN_CHECK(it);
        }
        fence_async_global();
        if (g >= 4) {
          if (!((ready >> lane) & 1)) pend = ld_rlx(flagAddr);
          mbar_wait(BAR(B_EMPTY + s), ((g >> 2) - 1) & 1);
        }
        if (elect_one()) {
          const uint32_t sa = sb + s * STAGE, fb = BAR(B_FULL + s);
          if (g >= 4) mbar_expect_tx(fb, STAGE);
          tma_3d(sa + SLOT, &prm.n, g * 64, m4 * 4, fb);
          if (g > 0) tma_2d(sa, &prm.ws[j], g * 64, t * 128, fb);
          TRACE(64 + g);
        }
        if (FK_WSPF && g + FK_WSPF < 32)
          asm volatile("prefetch.global.L2 [%0];" ::"l"(prm.wsp[j] + (size_t)(t * 128 + m4 * 32 + ((g + FK_WSPF) & 3) * 8 + (lane >> 2)) * 4096 + ((g + FK_WSPF) >> 2) * 512 + (lane & 3) * 128));
        prefetch_piece(g);
      }
    }
    asm volatile("" ::: "memory");
    if (warp == 1) {
      const uint32_t tag = ld_rlx(S->epoch) + 1;
      const uint32_t rb = sb + (m4 * 32 + lane) * 128 + ((lane & 7) << 4);
      float a0 = 0.f, a1 = 0.f, a2 = 0.f, a3 = 0.f;
#pragma unroll 1
      for (int g = 0; g < 32; g++) {
        const int s = g & 3;
        mbar_wait(BAR(B_FULL + s), (g >> 2) & 1);
        uint4 u[8];
#pragma unroll
        for (int c = 0; c < 8; c++) u[c] = lds128u((rb + s * STAGE) ^ (c << 4));
        u[7].x = __shfl_sync(~0u, u[7].x, lane);
        if (elect_one()) mbar_arrive(BAR(B_EMPTY + s));
#pragma unroll
        for (int c = 0; c < 8; c++) {
          a0 += bf_lo(u[c].x) + bf_lo(u[c].y); a1 += bf_hi(u[c].x) + bf_hi(u[c].y);
          a2 += bf_lo(u[c].z) + bf_lo(u[c].w); a3 += bf_hi(u[c].z) + bf_hi(u[c].w);
        }
      }
      if (lane == 0) mbar_arrive(BAR(B_RSDONE));
      st_msg8(&S->rs[j * S_ + t * 128 + m4 * 32 + lane], __float_as_uint((a0 + a1) + (a2 + a3)), tag);
    }
    asm volatile("" ::: "memory");
    if (warp >= 2) {
      const uint32_t ring = sb + SP_OFF + (warp - 2) * 16384, mf = BAR(B_MF + (warp - 2) * 4);
      const uint4 cw4 = ldg_nc(cvec + b * 8);
      const uint32_t tag = ld_rlx(S->epoch) + 1;
      int nc = 0;
      {
        const int last = warp == 2 ? 14 : 0;
        int ni = 0;
#pragma unroll 1
        for (int i = 0; i <= last; i++) {
          const uint32_t stg = ring + (i & 7) * 2048;
          if (i) {
            mbar_wait(mf + (nc & 3) * 8, (nc >> 2) & 1); nc++;
#pragma unroll
            for (int k = 0; k < 4; k++) xr[k] = lds128u(stg + lane * 16 + k * 512);
          }
          float s0 = 0.f, s1 = 0.f, q0 = 0.f, q1 = 0.f;
          uint32_t w[16];
#pragma unroll
          for (int k = 0; k < 4; k++) { w[4 * k] = xr[k].x; w[4 * k + 1] = xr[k].y; w[4 * k + 2] = xr[k].z; w[4 * k + 3] = xr[k].w; }
#pragma unroll
          for (int k = 0; k < 16; k++) { const float lo = bf_lo(w[k]), hi = bf_hi(w[k]); s0 += lo; s1 += hi; q0 = fmaf(lo, lo, q0); q1 = fmaf(hi, hi, q1); }
          float sum = s0 + s1, sq = q0 + q1;
#pragma unroll
          for (int o = 16; o; o >>= 1) { sum += __shfl_xor_sync(~0u, sum, o); sq += __shfl_xor_sync(~0u, sq, o); }
          const float mean = sum * (1.f / D_);
          const float rstd = rsqrtf(fmaxf(fmaf(-mean, mean, sq * (1.f / D_)), 0.f) + 1e-5f), nmr = -mean * rstd;
#pragma unroll
          for (int k = 0; k < 16; k++) w[k] = pack_bf16(fmaf(bf_lo(w[k]), rstd, nmr), fmaf(bf_hi(w[k]), rstd, nmr));
#pragma unroll
          for (int k = 0; k < 4; k++) sts128u(stg + lane * 16 + k * 512, w[4 * k], w[4 * k + 1], w[4 * k + 2], w[4 * k + 3]);
          fence_async_smem();
          const int upto = min(last, min(2 * i + 1, i + 3));
          if (elect_one()) {
            const int g = i ? i + 1 : warp - 2;
            unsigned* cnt = &S->cntN[(g * 2 + (b >> 6)) * 32];
            bulk_store(S->n + (size_t)(g * 128 + b) * D_, stg, 2048); bulk_commit();
            if (i <= 1 || i == last) { bulk_wait<0>(); red_add(cnt, 1); } else bulk_wait<1>();
            if (i >= 3) red_add(cnt - 64, 1);
            if (g < 3 || g == 15) TRACE(44 + (g & 3));
#pragma unroll 1
            for (int k = ni; k < upto; k++) {
              mbar_expect_tx(mf + (k & 3) * 8, 2048);
              bulk_load(ring + ((k + 1) & 7) * 2048, x + (size_t)((k + 2) * 128 + b) * D_, 2048, mf + (k & 3) * 8);
            }
          }
          ni = upto;
          __syncwarp();
        }
      }
      if (warp == 3) mbar_wait(BAR(B_FULL), 0);
      float sc[8];
      {
        const uint32_t cw[4] = {cw4.x, cw4.y, cw4.z, cw4.w};
#pragma unroll
        for (int r = 0; r < 4; r++) { const uint32_t sp = pack_bf16(silu_f(bf_lo(cw[r])), silu_f(bf_hi(cw[r]))); sc[2 * r] = bf_lo(sp); sc[2 * r + 1] = bf_hi(sp); }
      }
      uint64_t pol_first;
      asm volatile("createpolicy.fractional.L2::evict_first.b64 %0, 1.0;" : "=l"(pol_first));
      float* const mod = S->mod[tag & 1];
#pragma unroll 1
      for (int pass = warp == 3 ? 0 : 2;; pass++) {
#pragma unroll 1
        for (int bx = -2; bx < 8; bx++) {
          if (bx < 6 && elect_one()) {
            const int k = nc + min(bx, 0) + 2;
            bulk_wait_read<1>();
            mbar_expect_tx(mf + (k & 3) * 8, 4096);
            tma_2d_hint(ring + (k & 3) * 4096, &prm.wm, pass * 2048 + ((bx + 2 + b) & 7) * 256, b * 8, mf + (k & 3) * 8, pol_first);
          }
          if (bx < 0) continue;
          const uint32_t sl = ring + (nc & 3) * 4096;
          mbar_wait(mf + (nc & 3) * 8, (nc >> 2) & 1); nc++;
          uint4 v[8];
#pragma unroll
          for (int u = 0; u < 8; u++) v[u] = lds128u(sl + u * 512 + lane * 16);
          float acc[8];
#pragma unroll
          for (int i = 0; i < 8; i++) acc[i] = 0.f;
#pragma unroll
          for (int u = 0; u < 8; u++) {
            acc[0] = fmaf(sc[u], bf_lo(v[u].x), acc[0]); acc[1] = fmaf(sc[u], bf_hi(v[u].x), acc[1]);
            acc[2] = fmaf(sc[u], bf_lo(v[u].y), acc[2]); acc[3] = fmaf(sc[u], bf_hi(v[u].y), acc[3]);
            acc[4] = fmaf(sc[u], bf_lo(v[u].z), acc[4]); acc[5] = fmaf(sc[u], bf_hi(v[u].z), acc[5]);
            acc[6] = fmaf(sc[u], bf_lo(v[u].w), acc[6]); acc[7] = fmaf(sc[u], bf_hi(v[u].w), acc[7]);
          }
          __syncwarp();
          sts128(sl + lane * 32, acc[0], acc[1], acc[2], acc[3]); sts128(sl + lane * 32 + 16, acc[4], acc[5], acc[6], acc[7]);
          fence_async_smem();
          if (elect_one()) {
            asm volatile("cp.reduce.async.bulk.global.shared::cta.bulk_group.add.f32 [%0], [%1], 1024;" ::"l"(mod + pass * 2048 + ((bx + b) & 7) * 256), "r"(sl) : "memory");
            bulk_commit();
          }
        }
        const int jw = b >> 6, e0 = (b & 63) * 16;
        const __nv_bfloat16* src = (jw ? wd_im : wd_re) + (size_t)e0 * D_;
        if (elect_one()) {
          bulk_wait<0>();
          red_add(&S->cntMod[pass ? 32 : 0], 1);
          TRACE(9 + (pass ? 25 + pass : 0));
          if (pass == 0) {
#pragma unroll 1
            for (int k = 0; k < 4; k++) { mbar_expect_tx(mf + ((nc + k) & 3) * 8, 2048); bulk_load(ring + k * 2048, src + k * D_, 2048, mf + ((nc + k) & 3) * 8); }
          }
        }
        __syncwarp();
        if (pass) break;
        wait_cnt(S->cntMod, tag * 128u);
        if (lane == 0) TRACE(10);
        float4 sa[8]; uint32_t A[16];
#pragma unroll
        for (int i = 0; i < 8; i++) {
          const float4 sv = ldg_cg(mod + (i >> 1) * 256 + lane * 8 + (i & 1) * 4), ca = ldg_cg(mod + D_ + (i >> 1) * 256 + lane * 8 + (i & 1) * 4);
          const uint32_t s0 = pack_bf16(sv.x, sv.y), s1 = pack_bf16(sv.z, sv.w);
          sa[i] = make_float4(bf_lo(s0), bf_hi(s0), bf_lo(s1), bf_hi(s1));
          A[2 * i] = add_bf16x2(pack_bf16(ca.x, ca.y), 0x3F803F80u) ^ (jw ? 0x80008000u : 0u);
          A[2 * i + 1] = add_bf16x2(pack_bf16(ca.z, ca.w), 0x3F803F80u) ^ (jw ? 0x80008000u : 0u);
        }
        float ul = 0.f;
#pragma unroll 1
        for (int r = 0; r < 16; r++) {
          const uint32_t stg = ring + (r & 7) * 2048;
          mbar_wait(mf + (nc & 3) * 8, (nc >> 2) & 1);
          float u0 = 0.f, u1 = 0.f;
#pragma unroll
          for (int i = 0; i < 4; i++) xr[i] = lds128u(stg + lane * 16 + i * 512);
#pragma unroll
          for (int i = 0; i < 4; i++)
            sts128u(stg + lane * 16 + i * 512, mul_bf16x2(xr[i].x, A[4 * i]), mul_bf16x2(xr[i].y, A[4 * i + 1]), mul_bf16x2(xr[i].z, A[4 * i + 2]), mul_bf16x2(xr[i].w, A[4 * i + 3]));
#pragma unroll
          for (int i = 0; i < 4; i++) {
            u0 = fmaf(bf_lo(xr[i].x), sa[2 * i].x, u0); u1 = fmaf(bf_hi(xr[i].x), sa[2 * i].y, u1);
            u0 = fmaf(bf_lo(xr[i].y), sa[2 * i].z, u0); u1 = fmaf(bf_hi(xr[i].y), sa[2 * i].w, u1);
            u0 = fmaf(bf_lo(xr[i].z), sa[2 * i + 1].x, u0); u1 = fmaf(bf_hi(xr[i].z), sa[2 * i + 1].y, u1);
            u0 = fmaf(bf_lo(xr[i].w), sa[2 * i + 1].z, u0); u1 = fmaf(bf_hi(xr[i].w), sa[2 * i + 1].w, u1);
          }
          u0 += u1;
          asm volatile("" : "+f"(u0) :: "memory");
          fence_async_smem();
          if (elect_one()) {
            bulk_store(S->W2 + (size_t)(jw * D_ + (perm32(e0 + r) ^ (jw * 128))) * D_, stg, 2048); bulk_commit();
            if (r < 12) {
              bulk_wait_read<3>();
              mbar_expect_tx(mf + (nc & 3) * 8, 2048);
              bulk_load(ring + ((r + 4) & 7) * 2048, src + (r + 4) * D_, 2048, mf + (nc & 3) * 8);
            }
          }
          nc++;
#pragma unroll
          for (int o = 16; o; o >>= 1) u0 += __shfl_xor_sync(~0u, u0, o);
          if (lane == r) ul = jw ? -u0 : u0;
        }
        if (lane < 16) st_msg8(&S->u[jw * D_ + e0 + lane], __float_as_uint(ul), tag);
        if (elect_one()) { bulk_wait<0>(); red_add(&S->cntW[(b >> 4) * 32], 1); TRACE(11); }
        __syncwarp();
      }
      if (warp == 2) {
#pragma unroll
        for (int i = 0; i < 4; i++) sts128u(ring + lane * 16 + i * 512, SENT, SENT, SENT, SENT);
        fence_async_smem();
        if (elect_one()) {
#pragma unroll 1
          for (int i = 0; i < 9; i++)
            bulk_store(i < 4 ? &S->part[b * 512 + i * 128] : i == 4 ? &S->stats[b * 128] : &S->rowsH[((i - 5) >> 1) * 4096 + (t * 2 + (i & 1)) * 128 + cgrp * 16], ring, i < 5 ? 2048 : 256);
          bulk_commit(); bulk_wait<0>();
          mbar_arrive(BAR(B_RESET));
        }
        if (lane < 12) reinterpret_cast<float4*>(S->mod[~tag & 1] + b * 48)[lane] = make_float4(0.f, 0.f, 0.f, 0.f);
      }
      named_bar<1, 64>();
    }
    asm volatile("setmaxnreg.dec.sync.aligned.u32 40;" ::: "memory");
    const uint32_t tag = ld_rlx(S->epoch) + 1;
    if (warp == 0) {
      wait_cnt(&S->cntW[(j * 4 + m4) * 32], tag * 16u);
      if (lane == 0) TRACE(30);
      const int f = (lane - 4) & 15, kk = (f * 11) >> 5, np = (m4 + 1 + f - kk * 3) & 3;
      const unsigned* flagAddr = &S->flagP[((t * 8 + np * 2 + j) * 4 + (kk & 3)) * 8];
      const int kcl = lane < 4 ? m4 * 256 + ((lane + 3) & 3) * 64 : np * 256 + kk * 64;
      unsigned ready = 0xFFFF000Fu, pend = tag - 1;
#pragma unroll 1
      for (int q = 0; q < 16; q++) {
        const int s = q & 3, kc = __shfl_sync(~0u, kcl, q);
        ready |= __ballot_sync(~0u, pend == tag);
        int it = 0;
        while (!((ready >> q) & 1)) {
          ready |= __ballot_sync(~0u, (unsigned)(lane - q) < 3u && ld_rlx(flagAddr) == tag);
          SPIN_CHECK(it);
        }
        fence_async_global();
        if (q >= 3 && !((ready >> lane) & 1)) pend = ld_rlx(flagAddr);
        mbar_wait(BAR(B_EMPTY + s), ((q >> 2) + 1) & 1);
        if (elect_one()) {
          const uint32_t sa = sb + s * STAGE, fb = BAR(B_FULL + s);
          mbar_expect_tx(fb, q < 4 ? 2 * SLOT : STAGE);
          if (q >= 4) { tma_2d(sa, &prm.p, kc, j * S_ + t * 128, fb); mbar_arrive(BAR(B_EMPTY + s)); }
          tma_2d(sa + SLOT, &prm.w2, kc, j * D_ + m4 * 256, fb);
          TRACE(96 + q);
        }
        prefetch_piece(32 + q);
      }
      if (b < NMOE && elect_one()) {
        mbar_wait(BAR(B_HIALL), 0);
        mbar_expect_tx(BAR(B_UP), 32768);
        tma_5d(sb + UP0_OFF, &prm.wu, b * 32, 0, BAR(B_UP));
        tma_5d(sb + 2 * STAGE + 2 * SLOT, &prm.wu, b * 32, 16, BAR(B_UP));
        tma_5d(sb + 2 * STAGE + 2 * SLOT + 8192, &prm.wu, b * 32, 20, BAR(B_UP));
        tma_5d(sb + UP0_OFF - 8192, &prm.wu, b * 32, 24, BAR(B_UP));
        mbar_expect_tx(BAR(B_DN), 65536);
#pragma unroll 1
        for (int i = 0; i < 9; i++) {
          if ((i & 3) == 0) mbar_wait(BAR(B_EMPTY + (i >> 2)), 1);
          if (i == 0) { mbar_expect_tx(BAR(B_UP), 8192); tma_5d(sb, &prm.wu, b * 32, 28, BAR(B_UP)); }
          else tma_3d(sb + (i >> 2) * STAGE + (i & 3) * 8192, &prm.wdn, b * 32, i * 2 - 2, BAR(B_DN));
        }
      }
    }
    asm volatile("" ::: "memory");
    if (warp == 1) {
      if (elect_one()) {
        mbar_wait(BAR(B_RESET), 0);
#pragma unroll 1
        for (int kk = 0; kk < 4; kk++) {
          mbar_wait(BAR(B_PREADY + kk), 0);
          tma_store_2d(&prm.p, sb + kk * STAGE, m4 * 256 + kk * 64, j * S_ + t * 128);
          bulk_commit();
          bulk_wait<0>();
          st_rlx(&S->flagP[(b * 4 + kk) * 8], tag);
          mbar_arrive(BAR(B_EMPTY + kk));
          TRACE(40 + kk);
        }
      }
      __syncwarp();
      uint32_t rk[16];
#pragma unroll
      for (int h = 0; h < 2; h++) {
        const uint2* src = (h ? &S->u[cgrp * 128] : &S->rs[t * 128]) + lane;
        uint2 m[8]; int it = 0;
        while (true) {
          bool ok = true;
#pragma unroll
          for (int i = 0; i < 8; i++) { m[i] = ld_msg8(src + (i >> 1) * 32 + (i & 1) * (h ? D_ : S_)); ok &= m[i].y == tag; }
          if (ok) break;
          SPIN_CHECK(it);
        }
#pragma unroll
        for (int i = 0; i < 4; i++) {
          const float r0 = __uint_as_float(m[2 * i].x) * (h ? 0.5f : 1.f), r1 = __uint_as_float(m[2 * i + 1].x) * (h ? 0.5f : 1.f);
          const uint32_t hi = pack_bf16(r0, r1);
          rk[h * 8 + 2 * i] = hi; rk[h * 8 + 2 * i + 1] = pack_bf16(r0 - bf_lo(hi), r1 - bf_hi(hi));
        }
      }
      if (b < NMOE) mbar_wait(BAR(B_WFREE + 1), 0);
#pragma unroll
      for (int i = 0; i < 4; i++) {
        sts128u(sb + RKA_OFF + (i * 32 + lane) * 16, rk[2 * i], rk[2 * i], rk[2 * i + 1], 0);
        sts128u(sb + RKB_OFF + (i * 32 + perm32(lane)) * 16, rk[8 + 2 * i], rk[9 + 2 * i], rk[8 + 2 * i], 0);
      }
      fence_async_smem();
      __syncwarp();
      if (lane == 0) { mbar_arrive(BAR(B_TAB)); TRACE(26); }
    }
    asm volatile("" ::: "memory");
    if (warp == 2 && b < NMOE && elect_one()) {
      fence_async_smem();
#pragma unroll 1
      for (int i = 0; i < 11; i++) {
        const uint32_t bar = BAR(i < 8 ? B_WFULL : B_UP);
        if ((i & 3) == 0) { if (i) mbar_wait(BAR(B_WFREE - 1 + (i >> 2)), 0); mbar_expect_tx(bar, i == 8 ? 24576 : 32768); }
        tma_5d(sb + SP_OFF + (i & 3) * 8192, i < 8 ? &prm.wg : &prm.wu, b * 32, i < 8 ? i * 4 : i * 4 - 28, bar);
        __nanosleep(100);
      }
    }
    asm volatile("" ::: "memory");
    if (warp == 3) {
      wait_cnt(&S->cntMod[32], tag * 256u);
      {
        const float* mp = S->mod[tag & 1] + cgrp * 128 + lane * 4;
        const float4 ga = ldg_cg(mp + 2 * D_), sv = ldg_cg(mp + 3 * D_), cb = ldg_cg(mp + 4 * D_), gb = ldg_cg(mp + 5 * D_);
        const uint2 wr = __ldg(reinterpret_cast<const uint2*>(prm.w_r + cgrp * 128 + lane * 4));
        const uint32_t Aa = add_bf16x2(pack_bf16(cb.x, cb.y), 0x3F803F80u), Ab = add_bf16x2(pack_bf16(cb.z, cb.w), 0x3F803F80u);
        const uint32_t Sa = pack_bf16(sv.x, sv.y), Sb = pack_bf16(sv.z, sv.w), Ga = pack_bf16(gb.x, gb.y), Gb = pack_bf16(gb.z, gb.w);
        const float w0 = bf_lo(Aa) * bf_lo(wr.x), w1 = bf_hi(Aa) * bf_hi(wr.x), w2 = bf_lo(Ab) * bf_lo(wr.y), w3 = bf_hi(Ab) * bf_hi(wr.y);
        const uint32_t tb = sb + TAB_OFF + lane * 16;
        sts128(tb, w0, w1, w2, w3);
        sts128(tb + 512, bf_lo(Ga) * bf_lo(Aa), bf_hi(Ga) * bf_hi(Aa), bf_lo(Gb) * bf_lo(Ab), bf_hi(Gb) * bf_hi(Ab));
        sts128(tb + 1024, bf_lo(Ga) * bf_lo(Sa), bf_hi(Ga) * bf_hi(Sa), bf_lo(Gb) * bf_lo(Sb), bf_hi(Gb) * bf_hi(Sb));
        sts128(tb + 1536, round_bf16(ga.x), round_bf16(ga.y), round_bf16(ga.z), round_bf16(ga.w));
        sts128u(tb + 2048, Aa, Ab, Sa, Sb);
        float c1 = (w0 + w1) + (w2 + w3), c2 = (bf_lo(Sa) * bf_lo(wr.x) + bf_hi(Sa) * bf_hi(wr.x)) + (bf_lo(Sb) * bf_lo(wr.y) + bf_hi(Sb) * bf_hi(wr.y));
#pragma unroll 1
        for (int h = 0; h < 2; h++) {
#pragma unroll
          for (int o = 16; o; o >>= 1) { c1 += __shfl_xor_sync(~0u, c1, o); c2 += __shfl_xor_sync(~0u, c2, o); }
          if (h) break;
          if (t == 0 && lane == 0) st_msg(&S->cst[cgrp], __float_as_uint(c1), __float_as_uint(c2), tag, 0);
          uint4 cm; int it = 0;
          while (true) {
            cm = ld_msg(&S->cst[lane & 7]);
            if (__all_sync(~0u, cm.z == tag)) break;
            SPIN_CHECK(it); __nanosleep(200);
          }
          c1 = 0.25f * __uint_as_float(cm.x); c2 = 0.25f * __uint_as_float(cm.y);
        }
        if (lane == 0) { sts128u(sb + CST_OFF, __float_as_uint(c1), __float_as_uint(c2), tag, 0); mbar_arrive(BAR(B_TAB)); TRACE(27); }
      }
      mbar_wait(BAR(B_HIALL), 0);
      uint4 m; int it = 0;
      while (true) {
        m = ld_msg(&S->cand[(lane >> 1) * 8]);
        if (__all_sync(~0u, m.z == tag)) break;
        SPIN_CHECK(it);
      }
      uint32_t k1, k2;
      const uint32_t key = (lane & 1) ? m.y : m.x;
      warp_top2(key, k1, k2);
      if (lane == 0) { sts64u(sb + SEL_OFF, k1, k2); mbar_arrive(BAR(B_SEL)); TRACE(14); }
    }
  } else {
    const int cw = (warp - 4) >> 2;
    const int cwarp = warp - 4;
    const int gq = lane >> 2, q4 = lane & 3;
    const bool elect = (tid & 127) == 0;
    asm volatile("barrier.cluster.wait.acquire.aligned;" ::: "memory");

    uint32_t wf[64];
    const int kr = (lane & 7) + (lane >> 4) * 8;
    const uint32_t wo = (cwarp & 1) * 4096 + kr * 64 + ((((lane >> 3) & 1) ^ ((kr >> 1) & 3)) << 4);
    float lo[64], hi[64];
    {
      float acc[128];
#pragma unroll 1
      for (int g = 0; g < 32; g++) {
        const int s = g & 3;
        mbar_wait(BAR(B_FULL + s), (g >> 2) & 1);
        const uint32_t sa = sb + s * STAGE;
        const uint64_t da = make_desc(sa + cw * 8192, 16, 1024), db = make_desc(sa + SLOT, 8192, 1024);
        wg_fence();
        wgmma_n256<1>(acc, da, db, g > 0);
#pragma unroll
        for (int k = 1; k < 4; k++) wgmma_n256<1>(acc, da + k * 2, db + k * 128, 1);
        wg_commit();
        wg_wait<1>();
        if (g > 0 && elect) mbar_arrive(BAR(B_EMPTY + ((g - 1) & 3)));
      }
      mbar_wait(BAR(B_RSDONE), 0);
      asm volatile("setmaxnreg.inc.sync.aligned.u32 232;" ::: "memory");
      mbar_wait(BAR(B_FULL), 0);
      wg_wait<0>();
      if (elect) { mbar_arrive(BAR(B_EMPTY + 3)); TRACE(1 + tr); }
      reg_fence(acc);
      uint32_t pk[64];
#pragma unroll
      for (int i = 0; i < 64; i++) pk[i] = pack_bf16(acc[2 * i], acc[2 * i + 1]);
      const uint32_t so = sb + (uint32_t)(cwarp * 16 + (lane & 15)) * 128 + (((lane >> 4) ^ (lane & 7)) << 4);
      auto stage_p = [&](int kk) {
#pragma unroll
        for (int k = 0; k < 4; k++) stsm_x4((so + kk * STAGE) ^ (k << 5), pk + kk * 16 + k * 4);
        fence_async_smem();
        __syncwarp();
        if (lane == 0) mbar_arrive(BAR(B_PREADY + kk));
      };
#pragma unroll
      for (int s = 0; s < 4; s++) {
        const int kk = (s + 3) & 3;
        if (s) mbar_wait(BAR(B_FULL + s), 0);
        const uint64_t db = make_desc(sb + s * STAGE + SLOT, 16, 1024);
        wg_fence();
        if (s == 0) wgmma_n256_rs<0>(acc, pk + kk * 16, db); else wgmma_n256_rs<1>(acc, pk + kk * 16, db);
#pragma unroll
        for (int k = 1; k < 4; k++) wgmma_n256_rs<1>(acc, pk + kk * 16 + k * 4, db + k * 2);
        wg_commit();
        if (s == 0) { stage_p(0); stage_p(1); stage_p(2); if (elect) TRACE(2 + tr); }
        else {
          wg_wait<1>();
          if (elect) mbar_arrive(BAR(B_EMPTY + s - 1));
          if (s == 1) stage_p(3);
        }
      }
#pragma unroll 1
      for (int g = 36; g < 44; g++) {
        const int s = g & 3;
        mbar_wait(BAR(B_FULL + s), (g >> 2) & 1);
        const uint32_t sa = sb + s * STAGE;
        const uint64_t da = make_desc(sa + cw * 8192, 16, 1024), db = make_desc(sa + SLOT, 16, 1024);
        wg_fence();
#pragma unroll
        for (int k = 0; k < 4; k++) wgmma_n256<0>(acc, da + k * 2, db + k * 2, 1);
        wg_commit();
        wg_wait<1>();
        if (elect) mbar_arrive(BAR(B_EMPTY + ((g - 1) & 3)));
        if (b < NMOE && s == 0) {
          mbar_wait(BAR(B_WFULL), g >= 40);
          const uint32_t wb = sb + SP_OFF + (cwarp >> 1) * 8192 + wo;
          if (g == 36) {
#pragma unroll
            for (int i = 0; i < 8; i++) ldsm_x4_t((wb + (i >> 1) * 1024) ^ ((i & 1) << 5), wf + i * 4);
          } else {
#pragma unroll
            for (int i = 0; i < 8; i++) ldsm_x4_t((wb + (i >> 1) * 1024) ^ ((i & 1) << 5), wf + 32 + i * 4);
          }
          fence_async_smem();
          __syncwarp();
          if (lane == 0) mbar_arrive(BAR(B_WFREE + (g >= 40)));
        }
      }
      wg_wait<0>();
      if (elect) mbar_arrive(BAR(B_EMPTY + 3));
#pragma unroll
      for (int i = 0; i < 64; i++) {
        asm volatile("mov.b32 %0, %1;" : "=f"(lo[i]) : "f"(acc[i]));
        asm volatile("mov.b32 %0, %1;" : "=f"(hi[i]) : "f"(acc[64 + i]));
      }
    }
    if (elect) TRACE(3 + tr);
#pragma unroll 1
    for (int s = 0; s < 4; s++) {
      mbar_wait(BAR(B_FULL + s), 1);
      const uint32_t sa = sb + s * STAGE;
      const uint64_t da = make_desc(sa + cw * 8192, 16, 1024), db = make_desc(sa + 2 * SLOT, 16, 1024);
      wg_fence();
#pragma unroll
      for (int k = 0; k < 4; k++) wgmma_n128(hi, da + k * 2, db + k * 2);
      wg_commit();
      if (s == 2) {
        wg_wait<1>();
        if (elect) asm volatile("{\n.reg .b32 ra;\nmapa.shared::cluster.u32 ra, %0, %1;\nmbarrier.arrive.shared::cluster.b64 _, [ra];\n}"
                                ::"r"(BAR(B_PEER)), "r"(j ^ 1) : "memory");
      }
    }
    mbar_wait(BAR(B_TAB), 0);
    wg_fence();
    wgmma_n128(lo, make_desc(sb + RKA_OFF + cw * 1024, 0, 128, 0), make_desc(sb + RKB_OFF, 0, 128, 0));
    auto lo_block = [&](int s) {
      const uint64_t da = make_desc(sb + cw * 8192, 16, 1024) + s * (STAGE >> 4), db = make_desc(sb + SLOT, 16, 1024) + s * (STAGE >> 4);
#pragma unroll
      for (int k = 0; k < 4; k++) wgmma_n128(lo, da + k * 2, db + k * 2);
      wg_commit();
    };
    lo_block(0);
    const uint32_t rcv = sb + cw * STAGE + 2 * SLOT + (tid & 127) * 16;
    const int row0 = cwarp * 16 + gq;
    uint4 xq[8];
    {
      uint32_t rdst, rbar;
      asm volatile("mapa.shared::cluster.u32 %0, %1, %2;" : "=r"(rdst) : "r"(rcv), "r"(j ^ 1));
      asm volatile("mapa.shared::cluster.u32 %0, %1, %2;" : "=r"(rbar) : "r"(BAR(B_RECV + cw)), "r"(j ^ 1));
      mbar_wait_cluster(BAR(B_PEER), 0);
      wg_wait<1>();
      reg_fence(hi);
      lo_block(1);
      if (elect) { mbar_arrive(BAR(B_HIALL)); TRACE(4 + tr); }
      uint32_t pw[32];
#pragma unroll
      for (int i = 0; i < 32; i++) { const float* h = hi + (i >> 3) * 16 + ((i >> 2) & 1) * 2 + (i & 3) * 4; pw[i] = pack_bf16(h[0], h[1]); }
      const __nv_bfloat16* xp = x + (size_t)(t * 128 + row0) * D_ + cgrp * 128 + q4 * 8;
#pragma unroll
      for (int i = 0; i < 8; i++) xq[i] = ldg_nc(xp + (i & 1) * 8 * D_ + (i >> 1) * 32);
#pragma unroll
      for (int i = 0; i < 8; i++)
        asm volatile("st.async.weak.shared::cluster.mbarrier::complete_tx::bytes.v4.b32 [%0], {%1, %2, %3, %4}, [%5];"
                     ::"r"(rdst + i * 2048), "r"(pw[4 * i]), "r"(pw[4 * i + 1]), "r"(pw[4 * i + 2]), "r"(pw[4 * i + 3]), "r"(rbar) : "memory");
    }
    lo_block(2);
    lo_block(3);
    if (elect) TRACE(60 + cw);
    wg_wait<3>();
    if (elect) mbar_arrive(BAR(B_EMPTY));
    wg_wait<2>();
    if (elect) mbar_arrive(BAR(B_EMPTY + 1));
    wg_wait<1>();
    if (elect) { mbar_arrive(BAR(B_EMPTY + 2)); TRACE(5 + tr); }
    float4 tg[8];
#pragma unroll
    for (int i = 0; i < 8; i++) tg[i] = lds128(sb + TAB_OFF + 1536 + (i >> 1) * 128 + q4 * 32 + (i & 1) * 16);
    mbar_wait_cluster(BAR(B_RECV + cw), 0);
    if (elect) TRACE(6 + tr);
#pragma unroll
    for (int i = 0; i < 8; i++) {
      const uint4 rv = lds128u(rcv + i * 2048);
      const float4 g0 = tg[i & 6], g1 = tg[i | 1];
      xq[i].x = fma_bf16x2(pack_bf16(g0.x, g0.y), rv.x, xq[i].x); xq[i].y = fma_bf16x2(pack_bf16(g0.z, g0.w), rv.y, xq[i].y);
      xq[i].z = fma_bf16x2(pack_bf16(g1.x, g1.y), rv.z, xq[i].z); xq[i].w = fma_bf16x2(pack_bf16(g1.z, g1.w), rv.w, xq[i].w);
    }
    wg_wait<0>();
    reg_fence(lo);
    if (elect) { TRACE(7 + tr); if (cw == 0) TRACE_CLK(121); }
    const bool odd = q4 & 1;
    {
      float s[2] = {0.f, 0.f}, q[2] = {0.f, 0.f}, d[2] = {0.f, 0.f};
#pragma unroll
      for (int a = 0; a < 4; a++) {
        const float4 w0 = lds128(sb + TAB_OFF + a * 128 + q4 * 32), w1 = lds128(sb + TAB_OFF + a * 128 + q4 * 32 + 16);
        const float w[8] = {w0.x, w0.y, w0.z, w0.w, w1.x, w1.y, w1.z, w1.w};
        const float g[8] = {tg[2 * a].x, tg[2 * a].y, tg[2 * a].z, tg[2 * a].w, tg[2 * a + 1].x, tg[2 * a + 1].y, tg[2 * a + 1].z, tg[2 * a + 1].w};
#pragma unroll
        for (int r = 0; r < 2; r++) {
          const uint32_t z[4] = {xq[2 * a + r].x, xq[2 * a + r].y, xq[2 * a + r].z, xq[2 * a + r].w};
          float* v = lo + a * 16 + r * 2;
#pragma unroll
          for (int k = 0; k < 4; k++) {
            const float v0 = fmaf(v[4 * k], g[2 * k], bf_lo(z[k])), v1 = fmaf(v[4 * k + 1], g[2 * k + 1], bf_hi(z[k]));
            v[4 * k] = v0; v[4 * k + 1] = v1;
            s[r] += v0 + v1;
            q[r] = fmaf(v0, v0, fmaf(v1, v1, q[r]));
            d[r] = fmaf(v0, w[2 * k], fmaf(v1, w[2 * k + 1], d[r]));
          }
        }
      }
      float sa = odd ? s[1] : s[0], qa = odd ? q[1] : q[0], da = odd ? d[1] : d[0];
      sa += __shfl_xor_sync(~0u, odd ? s[0] : s[1], 1); qa += __shfl_xor_sync(~0u, odd ? q[0] : q[1], 1); da += __shfl_xor_sync(~0u, odd ? d[0] : d[1], 1);
      sa += __shfl_xor_sync(~0u, sa, 2); qa += __shfl_xor_sync(~0u, qa, 2); da += __shfl_xor_sync(~0u, da, 2);
      if (q4 < 2) st_msg(&S->stats[b * 128 + row0 + 8 * q4], __float_as_uint(sa), __float_as_uint(qa), __float_as_uint(da), 0);
    }
    if (elect) TRACE(8 + tr);
    uint32_t uf[64], df[64];
    if (b < NMOE) {
      mbar_wait(BAR(B_UP), 0);
      const int i4 = cwarp >> 1;
      const uint32_t u0 = sb + UP0_OFF + i4 * 8192 + wo, u1 = sb + (i4 < 2 ? 2 * STAGE + 2 * SLOT + i4 * 8192 : i4 == 2 ? UP0_OFF - 8192 : 0) + wo;
#pragma unroll
      for (int i = 0; i < 16; i++) ldsm_x4_t(((i < 8 ? u0 : u1) + ((i >> 1) & 3) * 1024) ^ ((i & 1) << 5), uf + i * 4);
    }
    if (tid == 128) TRACE(29);
    float rstd[2], nm[2];
    uint32_t bk1, bk2;
    {
      uint4 m[4];
      const uint4* src = &S->stats[(t * 8 + (q4 >> 1) * 4) * 128 + row0 + 8 * (q4 & 1)];
      const float4 cst = lds128(sb + CST_OFF);
      int it = 0;
      while (true) {
#pragma unroll
        for (int i = 0; i < 4; i++) m[i] = ld_msg(src + 128 * i);
        if (__all_sync(~0u, (m[0].w | m[1].w | m[2].w | m[3].w) == 0)) break;
        SPIN_CHECK(it);
      }
      float sa = (__uint_as_float(m[0].x) + __uint_as_float(m[1].x)) + (__uint_as_float(m[2].x) + __uint_as_float(m[3].x));
      float qa = (__uint_as_float(m[0].y) + __uint_as_float(m[1].y)) + (__uint_as_float(m[2].y) + __uint_as_float(m[3].y));
      float da = (__uint_as_float(m[0].z) + __uint_as_float(m[1].z)) + (__uint_as_float(m[2].z) + __uint_as_float(m[3].z));
      sa += __shfl_xor_sync(~0u, sa, 2); qa += __shfl_xor_sync(~0u, qa, 2); da += __shfl_xor_sync(~0u, da, 2);
      const float mean = sa * (1.f / D_);
      const float rs = rsqrtf(fmaxf(fmaf(-mean, mean, qa * (1.f / D_)), 0.f) + 1e-5f);
      const float r = fmaf(rs, fmaf(-mean, cst.x, da), cst.y);
      uint32_t k1, k2;
      warp_top2((fkey(r) & ~2047u) | (uint32_t)(2047 - (t * 128 + row0 + 8 * (q4 & 1))), k1, k2);
      if (lane == 0) sts64u(sb + TOP_OFF + cwarp * 8, k1, k2);
      const float nmr = -mean * rs, rsx = __shfl_xor_sync(~0u, rs, 1), nmx = __shfl_xor_sync(~0u, nmr, 1);
      rstd[0] = odd ? rsx : rs; rstd[1] = odd ? rs : rsx; nm[0] = odd ? nmx : nmr; nm[1] = odd ? nmr : nmx;
      if (tid == 128) TRACE(12 + 16);
      named_bar<2, 256>();
      warp_top2(lds32u(sb + TOP_OFF + (lane & 15) * 4), bk1, bk2);
      if (tid == 128) { st_msg(&S->cand[t * 8], bk1, bk2, __float_as_uint(cst.z), 0); TRACE(13); }
    }
    const int lr1 = key_row(bk1) - t * 128, lr2 = key_row(bk2) - t * 128;
#pragma unroll 1
    for (int ci = 0; ci < 2; ci++) {
      const int lr = ci ? lr2 : lr1;
      if ((lr >> 4) == cwarp) {
        const bool up = lr & 8;
        const float rs = up ? rstd[1] : rstd[0], nmr = up ? nm[1] : nm[0];
#pragma unroll
        for (int a = 0; a < 4; a++) {
          uint32_t o[4];
#pragma unroll
          for (int h = 0; h < 2; h++) {
            const uint4 T = lds128u(sb + TAB_OFF + 2048 + a * 128 + q4 * 32 + h * 16);
            const float* v = lo + a * 16 + h * 8;
            o[2 * h] = fma_bf16x2(pack_bf16(fmaf(up ? v[2] : v[0], rs, nmr), fmaf(up ? v[3] : v[1], rs, nmr)), T.x, T.z);
            o[2 * h + 1] = fma_bf16x2(pack_bf16(fmaf(up ? v[6] : v[4], rs, nmr), fmaf(up ? v[7] : v[5], rs, nmr)), T.y, T.w);
          }
          if (gq == (lr & 7)) st_msg(&S->rowsH[(t * 2 + ci) * 128 + cgrp * 16 + a * 4 + q4], o[0], o[1], o[2], o[3]);
        }
      }
    }
    uint4 ov[8];
#pragma unroll
    for (int a = 0; a < 4; a++) {
      uint32_t o[2][4];
#pragma unroll
      for (int h = 0; h < 2; h++) {
        const float4 A = lds128(sb + TAB_OFF + 512 + a * 128 + q4 * 32 + h * 16), B = lds128(sb + TAB_OFF + 1024 + a * 128 + q4 * 32 + h * 16);
#pragma unroll
        for (int r = 0; r < 2; r++) {
          const float* v = lo + a * 16 + h * 8 + r * 2;
          o[r][2 * h] = pack_bf16(v[0] + fmaf(fmaf(v[0], rstd[r], nm[r]), A.x, B.x), v[1] + fmaf(fmaf(v[1], rstd[r], nm[r]), A.y, B.y));
          o[r][2 * h + 1] = pack_bf16(v[4] + fmaf(fmaf(v[4], rstd[r], nm[r]), A.z, B.z), v[5] + fmaf(fmaf(v[5], rstd[r], nm[r]), A.w, B.w));
        }
      }
      ov[2 * a] = make_uint4(o[0][0], o[0][1], o[0][2], o[0][3]); ov[2 * a + 1] = make_uint4(o[1][0], o[1][1], o[1][2], o[1][3]);
    }
#pragma unroll
    for (int r = 0; r < 2; r++) {
      const int lr = row0 + 8 * r;
      if (lr == lr1 || lr == lr2) {
#pragma unroll
        for (int a = 0; a < 4; a++) st_msg(&S->rowsB[(t * 2 + (lr == lr2)) * 128 + cgrp * 16 + a * 4 + q4], ov[2 * a + r].x, ov[2 * a + r].y, ov[2 * a + r].z, ov[2 * a + r].w);
      }
    }
    if (tid == 128) TRACE(15);
    mbar_wait(BAR(B_SEL), 0);
    const float2 selv = lds64(sb + SEL_OFF);
    const uint32_t key1 = __float_as_uint(selv.x), key2 = __float_as_uint(selv.y);
    const int tA = key_row(key1) >> 7, tB = key_row(key2) >> 7;
    const int slotA = tA * 2, slotB = tB * 2 + (tA == tB ? 1 : 0);
    const int fn = (lane >> 3) & 1, fcol = (b >> 1) * 16 + (b & 1) * 4 + q4 + ((lane >> 2) & 1) * 8;
    uint32_t fbase = SENT; float fgb = 0.f;
    const uint32_t* fbp = reinterpret_cast<const uint32_t*>(&S->rowsB[(fn ? slotB : slotA) * 128]) + (fcol >> 1);
    uint4 hb[4];
    const uint4* src = &S->rowsH[((gq & 1) ? slotB : slotA) * 128 + cwarp * 8 + q4];
    if (b < NMOE) {
#pragma unroll
      for (int i = 0; i < 4; i++) hb[i] = ld_msg(src + (i >> 1) * 64 + (i & 1) * 4);
    }
#pragma unroll
    for (int r = 0; r < 2; r++) {
      const int row = t * 128 + row0 + 8 * r;
      if (row != key_row(key1) && row != key_row(key2)) {
#pragma unroll
        for (int a = 0; a < 4; a++) reinterpret_cast<uint4*>(out + (size_t)row * D_)[cgrp * 16 + a * 4 + q4] = ov[2 * a + r];
      }
    }
    if (b < NMOE) {
      mbar_wait(BAR(B_DN), 0);
      {
        const int fr = ((lane & 7) >> 1) + (lane & 1) * 8 + (lane >> 4) * 4;
        const uint32_t db = sb + ((cwarp + 1) >> 2) * STAGE + ((cwarp + 1) & 3) * 8192 + fr * 128 + ((((lane >> 3) & 1) ^ (fr & 7)) << 4);
#pragma unroll
        for (int i = 0; i < 16; i++) ldsm_x4_t((db + (i >> 3) * 4096 + (i & 1) * 2048) ^ (((i >> 1) & 3) << 5), df + i * 4);
      }
      int it = 0;
      while (!__all_sync(~0u, hb[0].x != SENT && hb[1].x != SENT && hb[2].x != SENT && hb[3].x != SENT)) {
#pragma unroll
        for (int i = 0; i < 4; i++) hb[i] = ld_msg(src + (i >> 1) * 64 + (i & 1) * 4);
        SPIN_CHECK(it);
      }
      if (tid == 128) TRACE(16);
      float c[4][4];
#pragma unroll
      for (int i = 0; i < 4; i++) c[i][0] = c[i][1] = c[i][2] = c[i][3] = 0.f;
#pragma unroll
      for (int ks = 0; ks < 8; ks++) {
        const uint32_t b0 = (ks & 1) ? hb[ks >> 1].z : hb[ks >> 1].x, b1 = (ks & 1) ? hb[ks >> 1].w : hb[ks >> 1].y;
        mma_16816(c[0], wf + ks * 8, b0, b1); mma_16816(c[1], wf + ks * 8 + 4, b0, b1);
        mma_16816(c[2], uf + ks * 8, b0, b1); mma_16816(c[3], uf + ks * 8 + 4, b0, b1);
      }
      {
        float v[4];
#pragma unroll
        for (int i = 0; i < 4; i++) v[i] = (q4 & 2) ? (odd ? c[3][i] : c[2][i]) : (odd ? c[1][i] : c[0][i]);
        sts128(sb + RED_OFF + cwarp * 512 + (q4 * 8 + gq) * 16, v[0], v[2], v[1], v[3]);
      }
    }
    if (cwarp == 0) { fbase = ld_rlx(fbp); fgb = __uint_as_float(ld_rlx(S->mod[lds32u(sb + CST_OFF + 8) & 1] + 5 * D_ + fcol)); }
    if (b < NMOE) {
      named_bar<2, 256>();
      float g0 = 0.f, g1 = 0.f, u0 = 0.f, u1 = 0.f;
#pragma unroll
      for (int w = 0; w < 8; w++) {
        const float2 gv = lds64(sb + RED_OFF + w * 512 + lane * 8), uv = lds64(sb + RED_OFF + w * 512 + 256 + lane * 8);
        g0 += gv.x; g1 += gv.y; u0 += uv.x; u1 += uv.y;
      }
      const uint32_t gp = pack_bf16(g0, g1), up = pack_bf16(u0, u1), sp = pack_bf16(silu_f(bf_lo(gp)), silu_f(bf_hi(gp)));
      const uint32_t act = pack_bf16(bf_lo(sp) * bf_lo(up), bf_hi(sp) * bf_hi(up));
      uint32_t ab[4];
#pragma unroll
      for (int i = 0; i < 4; i++) ab[i] = __shfl_sync(~0u, act, i * 8 + q4 * 2 + (gq & 1));
      if (tid == 128) TRACE(31);
#pragma unroll
      for (int T = 0; T < 2; T++) {
        float c[4][4];
#pragma unroll
        for (int i = 0; i < 4; i++) {
          c[i][0] = c[i][1] = c[i][2] = c[i][3] = 0.f;
          mma_16816(c[i], df + (T * 4 + i) * 8, ab[0], ab[1]); mma_16816(c[i], df + (T * 4 + i) * 8 + 4, ab[2], ab[3]);
        }
        float v[4];
#pragma unroll
        for (int i = 0; i < 4; i++) v[i] = (q4 & 2) ? (odd ? c[3][i] : c[2][i]) : (odd ? c[1][i] : c[0][i]);
        st_msg(&S->part[((cwarp * 16 + T * 8 + q4 * 2 + (gq >> 2)) * 128 + b) * 4 + (gq & 3)], __float_as_uint(v[0]), __float_as_uint(v[1]), __float_as_uint(v[2]), __float_as_uint(v[3]));
      }
      if (tid == 128) TRACE(32);
    }
    if (cwarp == 0) {
      const uint32_t fk = fn ? key2 : key1;
      const float sg = round_bf16(sigmoid_f(round_bf16(fkey_inv((fk & ~2047u) | 1024u))));
      int it = 0;
      while (fbase == SENT) { fbase = ld_rlx(fbp); SPIN_CHECK(it); }
      spin(b < NMOE ? FK_PDELAY : FK_PDELAY + 1200);
      uint4 m[14];
      while (true) {
        bool ok = true;
#pragma unroll
        for (int i = 0; i < 14; i++) { m[i] = ld_msg(&S->part[b * 512 + i * 32 + lane]); ok &= m[i].x != SENT; }
        if (__all_sync(~0u, ok)) break;
        SPIN_CHECK(it);
      }
      if (lane == 0) TRACE(33);
      float y[4] = {0.f, 0.f, 0.f, 0.f};
#pragma unroll
      for (int i = 0; i < 14; i++) { y[0] += __uint_as_float(m[i].x); y[1] += __uint_as_float(m[i].y); y[2] += __uint_as_float(m[i].z); y[3] += __uint_as_float(m[i].w); }
      const bool b2 = lane & 4;
      float y0 = (b2 ? y[2] : y[0]) + __shfl_xor_sync(~0u, b2 ? y[0] : y[2], 4), y1 = (b2 ? y[3] : y[1]) + __shfl_xor_sync(~0u, b2 ? y[1] : y[3], 4);
      y0 = (fn ? y1 : y0) + __shfl_xor_sync(~0u, fn ? y0 : y1, 8);
      y0 += __shfl_xor_sync(~0u, y0, 16);
      const float upd = round_bf16(round_bf16(y0) * sg);
      if (lane < 16) out[(size_t)key_row(fk) * D_ + fcol] = __float2bfloat16_rn(fmaf(round_bf16(fgb), upd, (fcol & 1) ? bf_hi(fbase) : bf_lo(fbase)));
      if (lane == 0) {
        TRACE(34); TRACE_CLK(122);
        if (b == 0) S->epoch[0] = lds32u(sb + CST_OFF + 8);
      }
    }
  }
}

typedef CUresult (*PFN_encodeTiled)(CUtensorMap*, CUtensorMapDataType, cuuint32_t, void*, const cuuint64_t*, const cuuint64_t*,
                                    const cuuint32_t*, const cuuint32_t*, CUtensorMapInterleave, CUtensorMapSwizzle,
                                    CUtensorMapL2promotion, CUtensorMapFloatOOBfill);

static void mapnd(PFN_encodeTiled enc, CUtensorMap* m, const void* p, int nd, const cuuint64_t* dims, const cuuint64_t* str, const cuuint32_t* box,
                  CUtensorMapSwizzle sw, CUtensorMapL2promotion pr) {
  const cuuint32_t es[5] = {1, 1, 1, 1, 1};
  enc(m, CU_TENSOR_MAP_DATA_TYPE_BFLOAT16, nd, (void*)p, dims, str, box, es, CU_TENSOR_MAP_INTERLEAVE_NONE, sw, pr, CU_TENSOR_MAP_FLOAT_OOB_FILL_NONE);
}
static void map2d(PFN_encodeTiled enc, CUtensorMap* m, const void* p, uint64_t rows, uint64_t cols, uint32_t brows, uint32_t bcols,
                  CUtensorMapSwizzle sw = CU_TENSOR_MAP_SWIZZLE_128B, CUtensorMapL2promotion pr = CU_TENSOR_MAP_L2_PROMOTION_L2_128B) {
  const cuuint64_t dims[2] = {cols, rows}, str[1] = {cols * 2}; const cuuint32_t box[2] = {bcols, brows};
  mapnd(enc, m, p, 2, dims, str, box, sw, pr);
}
static void map3d(PFN_encodeTiled enc, CUtensorMap* m, const void* p, uint64_t rows, uint64_t cols, uint32_t brows, uint32_t bgroups) {
  const cuuint64_t dims[3] = {64, rows, cols / 64}, str[2] = {cols * 2, 128}; const cuuint32_t box[3] = {64, brows, bgroups};
  mapnd(enc, m, p, 3, dims, str, box, CU_TENSOR_MAP_SWIZZLE_128B, CU_TENSOR_MAP_L2_PROMOTION_L2_128B);
}
static void map5d(PFN_encodeTiled enc, CUtensorMap* m, const void* p) {
  const cuuint64_t rb = F_ * 2, dims[5] = {F_, 2, 4, 4, 32}, str[4] = {rb, 8 * rb, 2 * rb, 32 * rb}; const cuuint32_t box[5] = {32, 2, 4, 4, 4};
  mapnd(enc, m, p, 5, dims, str, box, CU_TENSOR_MAP_SWIZZLE_64B, CU_TENSOR_MAP_L2_PROMOTION_L2_128B);
}

}

extern "C" void kernel_launch(void* const* d_in, const int* in_sizes, int n_in, void* d_out, int out_size) {
  using namespace fk;
  (void)in_sizes; (void)n_in; (void)out_size;
  static PFN_encodeTiled enc = nullptr;
  static Scratch* scr = nullptr;
  if (!enc) {
    void* fn = nullptr; cudaDriverEntryPointQueryResult qr;
    cudaGetDriverEntryPoint("cuTensorMapEncodeTiled", &fn, cudaEnableDefault, &qr);
    enc = (PFN_encodeTiled)fn;
    cudaGetSymbolAddress((void**)&scr, g_scr);
    cudaFuncSetAttribute(fused_kernel, cudaFuncAttributeMaxDynamicSharedMemorySize, SMEM_BYTES);
  }
  typedef const __nv_bfloat16* bp;
  Params prm;
  prm.w_r = (bp)d_in[6];
  prm.wsp[0] = (const char*)d_in[1]; prm.wsp[1] = (const char*)d_in[2];
  for (int i = 0; i < 3; i++) prm.we[i] = (const char*)d_in[7 + i];
  map2d(enc, &prm.ws[0], d_in[1], S_, S_, 128, 64);
  map2d(enc, &prm.ws[1], d_in[2], S_, S_, 128, 64);
  map3d(enc, &prm.n, scr->n, S_, D_, 64, 4);
  map2d(enc, &prm.wm, d_in[11], D_, 6 * D_, 8, 256, CU_TENSOR_MAP_SWIZZLE_NONE, CU_TENSOR_MAP_L2_PROMOTION_L2_256B);
  map2d(enc, &prm.p, scr->P, 2 * S_, D_, 128, 64);
  map2d(enc, &prm.w2, scr->W2, 2 * D_, D_, 256, 64);
  map5d(enc, &prm.wg, d_in[7]);
  map5d(enc, &prm.wu, d_in[8]);
  map3d(enc, &prm.wdn, d_in[9], F_, D_, 32, 2);

  fused_kernel<<<NCTA, 384, SMEM_BYTES, cudaStreamPerThread>>>((bp)d_in[0], scr, (__nv_bfloat16*)d_out, (bp)d_in[10], (bp)d_in[3], (bp)d_in[4], prm);
}
```

```cpp
#include <cuda_runtime.h>
#include <cuda_bf16.h>
#include <cuda.h>
#include <stdint.h>

#define DEVINL __device__ __forceinline__

namespace fk {

constexpr int S_ = 2048, D_ = 1024, F_ = 3584;
constexpr int NCTA = 128;
constexpr int SLOT = 16384;
constexpr int STAGE = 3 * SLOT;
constexpr int BUF = 2 * SLOT;
constexpr int E_OFF = 5 * BUF;
constexpr int SP_OFF = 4 * STAGE;
constexpr int MISC_OFF = SP_OFF + 32768;
constexpr int SMEM_BYTES = MISC_OFF + 3072;
constexpr int BAR_OFF = MISC_OFF;
constexpr int SEL_OFF = MISC_OFF + 352;
constexpr int RDY_OFF = MISC_OFF + 360;
constexpr int CST_OFF = MISC_OFF + 368;
constexpr int DUMMY_OFF = MISC_OFF + 384;
constexpr int TOP_OFF = DUMMY_OFF;
constexpr int TAB_OFF = MISC_OFF + 512;
constexpr int POLL_OFF = TAB_OFF + 256;
constexpr int T1_OFF = TAB_OFF + 1536;
constexpr int RKA_OFF = BUF;
constexpr int RKB_OFF = RKA_OFF + 2048;
constexpr int RED_OFF = RKB_OFF + 2048;
constexpr int DN_OFF = RED_OFF + 4096;

enum { B_FULL = 0, B_EMPTY = 4, B_PREADY = 8, B_MF = 12  , B_FULL2 = 20  , B_EMPTY2 = 25  , B_A29 = 30, B_ADONE = 31,
       B_RSDONE = 32, B_TAB = 33, B_B27 = 34, B_SEL = 35, B_DN = 36, B_SPFULL = 37, B_EFULL = 38, B_TAKEN = 39  , B_PS = 42  , B_NUM = 44 };
constexpr unsigned long long CNT0 = 0x1111888855551111ull, CNT1 = 0x4244444111111111ull, CNT2 = 0x1111118881111122ull;

#define FK_REL 0x14
#define FK_WSPF 22
#define FK_G0 32
#define FK_N1 2
#define FK_P0 16
#define FK_PACE 250
#define FK_PHOME 0
#define FK_PTOUCH 96
#define FK_PEND 96
#define FK_Q1 14
#define FK_Q2 20
#define FK_Q3 27
#define FK_QA 5
#define FK_P3DELAY 1000
#define FK_SPACE 450
#define FK_PDELAY 500
constexpr int SPIN_LIMIT = 1 << 20;
constexpr uint32_t SENT = 0xFFFFFFFFu;

struct Scratch {
  uint4 part[128 * 128 * 4];
  uint4 stats[128 * 128];
  uint4 rowsH[32 * 128];
  uint4 rowsB[32 * 128];
  uint4 cand[16 * 8];
  uint2 rs[2 * S_];
  uint4 cst[8];
  float mod[2][6 * D_];
  uint2 u[2 * D_];
  unsigned flagP[128 * 4 * 8];
  unsigned cntN[12 * 32];
  unsigned cntMod[2 * 32];
  unsigned epoch[32];
  alignas(1024) __nv_bfloat16 n[S_ * D_];
  __nv_bfloat16 P[2 * S_ * D_];
};
__device__ __align__(1024) Scratch g_scr;

struct Params {
  CUtensorMap ws[2];
  CUtensorMap n;
  CUtensorMap wm;
  CUtensorMap p;
  CUtensorMap wg, wu;
  CUtensorMap xm;
  CUtensorMap wdn;
  CUtensorMap wd[2];
  CUtensorMap om;
  CUtensorMap tch[3];
  const __nv_bfloat16* w_r;
  const char* wsp[2];
};

DEVINL uint32_t smem_u32(const void* p) { return (uint32_t)__cvta_generic_to_shared(p); }
DEVINL void mbar_init(uint32_t bar, uint32_t cnt) { asm volatile("mbarrier.init.shared::cta.b64 [%0], %1;" ::"r"(bar), "r"(cnt) : "memory"); }
DEVINL void mbar_expect_tx(uint32_t bar, uint32_t bytes) { asm volatile("mbarrier.arrive.expect_tx.shared::cta.b64 _, [%0], %1;" ::"r"(bar), "r"(bytes) : "memory"); }
DEVINL void mbar_arrive(uint32_t bar) { asm volatile("mbarrier.arrive.shared::cta.b64 _, [%0];" ::"r"(bar) : "memory"); }
DEVINL void arrive_peer(uint32_t bar, uint32_t cta) {
  asm volatile("{\n.reg .b32 ra;\nmapa.shared::cluster.u32 ra, %0, %1;\nmbarrier.arrive.shared::cluster.b64 _, [ra];\n}" ::"r"(bar), "r"(cta) : "memory");
}
DEVINL void mbar_wait(uint32_t bar, uint32_t parity) {
  asm volatile("{\n.reg .pred p;\n.reg .u32 c;\nmov.u32 c, 0;\n"
               "LW:\nmbarrier.try_wait.parity.shared::cta.b64 p, [%0], %1;\n@p bra LD;\n"
               "add.u32 c, c, 1;\nsetp.lt.u32 p, c, 1048576;\n@p bra LW;\ntrap;\nLD:\n}" ::"r"(bar), "r"(parity) : "memory");
}
DEVINL void mbar_wait_cluster(uint32_t bar, uint32_t parity) {
  asm volatile("{\n.reg .pred p;\n.reg .u32 c;\nmov.u32 c, 0;\n"
               "LW:\nmbarrier.try_wait.parity.acquire.cluster.shared::cta.b64 p, [%0], %1;\n@p bra LD;\n"
               "add.u32 c, c, 1;\nsetp.lt.u32 p, c, 1048576;\n@p bra LW;\ntrap;\nLD:\n}" ::"r"(bar), "r"(parity) : "memory");
}
#define SPIN_CHECK(it) if (++(it) > SPIN_LIMIT) __trap()
DEVINL void fence_async_smem() { asm volatile("fence.proxy.async.shared::cta;" ::: "memory"); }
DEVINL void fence_async_global() { asm volatile("fence.proxy.async.global;" ::: "memory"); }
template <int BIT> DEVINL void rel_fence() { if ((FK_REL >> BIT) & 1) asm volatile("fence.acq_rel.gpu;" ::: "memory"); }
DEVINL void fence_gpu() { asm volatile("fence.acq_rel.gpu;" ::: "memory"); }
template <int ID, int N> DEVINL void named_bar() { asm volatile("bar.sync %0, %1;" ::"n"(ID), "n"(N) : "memory"); }
DEVINL bool elect_one() { uint32_t p; asm volatile("{\n.reg .pred e;\nelect.sync _|e, 0xffffffff;\nselp.u32 %0, 1, 0, e;\n}" : "=r"(p)); return p; }
DEVINL unsigned clk32() { unsigned c; asm volatile("mov.u32 %0, %%clock;" : "=r"(c)); return c; }
#define FK_GRIDW 32
#define FK_GRID 0
DEVINL void grid_wait() {
  if (FK_GRID) {
    unsigned t0, t1;
    asm volatile("mov.u32 %0, %%globaltimer_lo;" : "=r"(t0));
    do { asm volatile("mov.u32 %0, %%globaltimer_lo;" : "=r"(t1)); } while (((t0 - FK_GRIDW) ^ t1) < FK_GRID + 0u + !FK_GRID);
  }
}
DEVINL void spin(unsigned n) { const unsigned c = clk32(); while (clk32() - c < n) {} }

constexpr uint64_t POL_NORMAL = 0x1000000000000000ull, POL_FIRST = 0x12F0000000000000ull;
#define FK_HINTS 0x11B
template <int BIT> DEVINL constexpr uint64_t pol() { return ((FK_HINTS >> BIT) & 1) ? POL_FIRST : POL_NORMAL; }
DEVINL void tma_2d(uint32_t dst, const CUtensorMap* m, int x, int y, uint32_t bar, uint64_t pol) {
  asm volatile("cp.async.bulk.tensor.2d.shared::cluster.global.mbarrier::complete_tx::bytes.L2::cache_hint [%0], [%1, {%3, %4}], [%2], %5;"
               ::"r"(dst), "l"(m), "r"(bar), "r"(x), "r"(y), "l"(pol) : "memory");
}
DEVINL void tma_3d(uint32_t dst, const CUtensorMap* m, int y, int z, uint32_t bar, uint64_t pol) {
  asm volatile("cp.async.bulk.tensor.3d.shared::cluster.global.mbarrier::complete_tx::bytes.L2::cache_hint [%0], [%1, {0, %3, %4}], [%2], %5;"
               ::"r"(dst), "l"(m), "r"(bar), "r"(y), "r"(z), "l"(pol) : "memory");
}
DEVINL void tma_5d(uint32_t dst, const CUtensorMap* m, int x, int a, uint32_t bar) {
  asm volatile("cp.async.bulk.tensor.5d.shared::cluster.global.mbarrier::complete_tx::bytes.L2::cache_hint [%0], [%1, {%3, 0, 0, 0, %4}], [%2], %5;"
               ::"r"(dst), "l"(m), "r"(bar), "r"(x), "r"(a), "l"(pol<3>()) : "memory");
}
DEVINL void tma_3d_mc(uint32_t dst, const CUtensorMap* m, int y, int z, uint32_t bar, uint64_t pol) {
  asm volatile("cp.async.bulk.tensor.3d.shared::cluster.global.mbarrier::complete_tx::bytes.multicast::cluster.L2::cache_hint [%0], [%1, {0, %3, %4}], [%2], %5, %6;"
               ::"r"(dst), "l"(m), "r"(bar), "r"(y), "r"(z), "h"((unsigned short)3), "l"(pol) : "memory");
}
DEVINL void tma_5d_mc(uint32_t dst, const CUtensorMap* m, int x, int a, uint32_t bar, uint64_t pol) {
  asm volatile("cp.async.bulk.tensor.5d.shared::cluster.global.mbarrier::complete_tx::bytes.multicast::cluster.L2::cache_hint [%0], [%1, {%3, 0, 0, 0, %4}], [%2], %5, %6;"
               ::"r"(dst), "l"(m), "r"(bar), "r"(x), "r"(a), "h"((unsigned short)3), "l"(pol) : "memory");
}
DEVINL void tma_store_2d(const CUtensorMap* m, uint32_t src, int x, int y) {
  asm volatile("cp.async.bulk.tensor.2d.global.shared::cta.bulk_group [%0, {%2, %3}], [%1];" ::"l"(m), "r"(src), "r"(x), "r"(y) : "memory");
}
DEVINL void bulk_store(void* dst, uint32_t src, uint32_t bytes) {
  asm volatile("cp.async.bulk.global.shared::cta.bulk_group [%0], [%1], %2;" ::"l"(dst), "r"(src), "r"(bytes) : "memory");
}
DEVINL void bulk_load(uint32_t dst, const void* src, uint32_t bytes, uint32_t bar, uint64_t pol) {
  asm volatile("cp.async.bulk.shared::cluster.global.mbarrier::complete_tx::bytes.L2::cache_hint [%0], [%1], %2, [%3], %4;" ::"r"(dst), "l"(src), "r"(bytes), "r"(bar), "l"(pol) : "memory");
}
template <int N> DEVINL void bulk_wait_read() { asm volatile("cp.async.bulk.wait_group.read %0;" ::"n"(N) : "memory"); }
DEVINL void pf_bulk(const void* p, uint32_t bytes) { asm volatile("cp.async.bulk.prefetch.L2.global [%0], %1;" ::"l"(p), "r"(bytes) : "memory"); }
DEVINL void bulk_commit() { asm volatile("cp.async.bulk.commit_group;" ::: "memory"); }
template <int N> DEVINL void bulk_wait() { asm volatile("cp.async.bulk.wait_group %0;" ::"n"(N) : "memory"); }
DEVINL void prefetch_tmap(const CUtensorMap* m) { asm volatile("prefetch.tensormap [%0];" ::"l"(m) : "memory"); }

DEVINL void wg_fence() { asm volatile("wgmma.fence.sync.aligned;" ::: "memory"); }
DEVINL void wg_commit() { asm volatile("wgmma.commit_group.sync.aligned;" ::: "memory"); }
template <int N> DEVINL void wg_wait() { asm volatile("wgmma.wait_group.sync.aligned %0;" ::"n"(N) : "memory"); }
DEVINL uint64_t make_desc(uint32_t addr, uint32_t lbo, uint32_t sbo, uint64_t sw = 1) {
  return (uint64_t)((addr & 0x3FFFF) >> 4) | ((uint64_t)(lbo >> 4) << 16) | ((uint64_t)(sbo >> 4) << 32) | (sw << 62);
}

#define R8(a, o) "+f"(a[o]), "+f"(a[o + 1]), "+f"(a[o + 2]), "+f"(a[o + 3]), "+f"(a[o + 4]), "+f"(a[o + 5]), "+f"(a[o + 6]), "+f"(a[o + 7])
#define R64(a, o) R8(a, o), R8(a, o + 8), R8(a, o + 16), R8(a, o + 24), R8(a, o + 32), R8(a, o + 40), R8(a, o + 48), R8(a, o + 56)
#define ACC64 "{%0, %1, %2, %3, %4, %5, %6, %7, %8, %9, %10, %11, %12, %13, %14, %15, "              \
              "%16, %17, %18, %19, %20, %21, %22, %23, %24, %25, %26, %27, %28, %29, %30, %31, "    \
              "%32, %33, %34, %35, %36, %37, %38, %39, %40, %41, %42, %43, %44, %45, %46, %47, "    \
              "%48, %49, %50, %51, %52, %53, %54, %55, %56, %57, %58, %59, %60, %61, %62, %63"
#define ACC128 ACC64 ", %64, %65, %66, %67, %68, %69, %70, %71, %72, %73, %74, %75, %76, %77, %78, %79, "      \
              "%80, %81, %82, %83, %84, %85, %86, %87, %88, %89, %90, %91, %92, %93, %94, %95, "               \
              "%96, %97, %98, %99, %100, %101, %102, %103, %104, %105, %106, %107, %108, %109, %110, %111, "   \
              "%112, %113, %114, %115, %116, %117, %118, %119, %120, %121, %122, %123, %124, %125, %126, %127"
template <int TB> DEVINL void wgmma_n256(float (&d)[128], uint64_t da, uint64_t db, int scale_d) {
  asm volatile("{\n.reg .pred p;\nsetp.ne.b32 p, %130, 0;\n"
               "wgmma.mma_async.sync.aligned.m64n256k16.f32.bf16.bf16 " ACC128 "}, %128, %129, p, 1, 1, 0, %131;\n}\n"
               : R64(d, 0), R64(d, 64) : "l"(da), "l"(db), "r"(scale_d), "n"(TB));
}
template <int TB> DEVINL void wgmma_n128(float (&d)[64], uint64_t da, uint64_t db) {
  asm volatile("wgmma.mma_async.sync.aligned.m64n128k16.f32.bf16.bf16 " ACC64 "}, %64, %65, 1, 1, 1, 0, %66;\n" : R64(d, 0) : "l"(da), "l"(db), "n"(TB));
}
template <int SC> DEVINL void wgmma_n128_rs(float (&d)[64], const uint32_t* a, uint64_t db) {
  asm volatile("{\n.reg .pred p;\nsetp.ne.b32 p, %69, 0;\n"
               "wgmma.mma_async.sync.aligned.m64n128k16.f32.bf16.bf16 " ACC64 "}, {%64, %65, %66, %67}, %68, p, 1, 1, 0;\n}\n"
               : R64(d, 0) : "r"(a[0]), "r"(a[1]), "r"(a[2]), "r"(a[3]), "l"(db), "n"(SC));
}
template <int N> DEVINL void reg_fence(float (&a)[N]) {
#pragma unroll
  for (int i = 0; i < N; i++) asm volatile("" : "+f"(a[i])::"memory");
}

DEVINL uint32_t pack_bf16(float lo, float hi) { uint32_t r; asm("cvt.rn.bf16x2.f32 %0, %1, %2;" : "=r"(r) : "f"(hi), "f"(lo)); return r; }
DEVINL uint32_t add_bf16x2(uint32_t a, uint32_t b) { uint32_t r; asm("add.rn.bf16x2 %0, %1, %2;" : "=r"(r) : "r"(a), "r"(b)); return r; }
DEVINL uint32_t mul_bf16x2(uint32_t a, uint32_t b) { uint32_t r; asm("mul.rn.bf16x2 %0, %1, %2;" : "=r"(r) : "r"(a), "r"(b)); return r; }
DEVINL uint32_t fma_bf16x2(uint32_t a, uint32_t b, uint32_t c) { uint32_t r; asm("fma.rn.bf16x2 %0, %1, %2, %3;" : "=r"(r) : "r"(a), "r"(b), "r"(c)); return r; }
DEVINL float bf_lo(uint32_t w) { return __uint_as_float(w << 16); }
DEVINL float bf_hi(uint32_t w) { return __uint_as_float(w & 0xFFFF0000u); }
DEVINL float round_bf16(float v) { return bf_lo(pack_bf16(v, 0.f)); }
DEVINL float sigmoid_f(float v) { float r; asm("rcp.approx.ftz.f32 %0, %1;" : "=f"(r) : "f"(1.f + __expf(-v))); return r; }
DEVINL float silu_f(float v) { return v * sigmoid_f(v); }
DEVINL void stsm_x4(uint32_t addr, const uint32_t* r) {
  asm volatile("stmatrix.sync.aligned.m8n8.x4.shared.b16 [%0], {%1, %2, %3, %4};" ::"r"(addr), "r"(r[0]), "r"(r[1]), "r"(r[2]), "r"(r[3]) : "memory");
}
DEVINL void ldsm_x4_t(uint32_t addr, uint32_t* r) {
  asm volatile("ldmatrix.sync.aligned.m8n8.x4.trans.shared.b16 {%0, %1, %2, %3}, [%4];" : "=r"(r[0]), "=r"(r[1]), "=r"(r[2]), "=r"(r[3]) : "r"(addr) : "memory");
}
DEVINL void mma_16816(float (&c)[4], const uint32_t* a, uint32_t b0, uint32_t b1) {
  asm("mma.sync.aligned.m16n8k16.row.col.f32.bf16.bf16.f32 {%0, %1, %2, %3}, {%4, %5, %6, %7}, {%8, %9}, {%0, %1, %2, %3};"
      : "+f"(c[0]), "+f"(c[1]), "+f"(c[2]), "+f"(c[3]) : "r"(a[0]), "r"(a[1]), "r"(a[2]), "r"(a[3]), "r"(b0), "r"(b1));
}
DEVINL float4 lds128(uint32_t a) { float4 v; asm volatile("ld.shared.v4.f32 {%0, %1, %2, %3}, [%4];" : "=f"(v.x), "=f"(v.y), "=f"(v.z), "=f"(v.w) : "r"(a)); return v; }
DEVINL uint4 lds128u(uint32_t a) { uint4 v; asm volatile("ld.shared.v4.u32 {%0, %1, %2, %3}, [%4];" : "=r"(v.x), "=r"(v.y), "=r"(v.z), "=r"(v.w) : "r"(a)); return v; }
DEVINL float2 lds64(uint32_t a) { float2 v; asm volatile("ld.shared.v2.f32 {%0, %1}, [%2];" : "=f"(v.x), "=f"(v.y) : "r"(a)); return v; }
DEVINL uint32_t lds32u(uint32_t a) { uint32_t v; asm volatile("ld.shared.u32 %0, [%1];" : "=r"(v) : "r"(a)); return v; }
DEVINL void sts128(uint32_t a, float x, float y, float z, float w) { asm volatile("st.shared.v4.f32 [%0], {%1, %2, %3, %4};" ::"r"(a), "f"(x), "f"(y), "f"(z), "f"(w) : "memory"); }
DEVINL void sts128u(uint32_t a, uint32_t x, uint32_t y, uint32_t z, uint32_t w) { asm volatile("st.shared.v4.u32 [%0], {%1, %2, %3, %4};" ::"r"(a), "r"(x), "r"(y), "r"(z), "r"(w) : "memory"); }
DEVINL void sts64u(uint32_t a, uint32_t x, uint32_t y) { asm volatile("st.shared.v2.u32 [%0], {%1, %2};" ::"r"(a), "r"(x), "r"(y) : "memory"); }
DEVINL void sts32v(uint32_t a, uint32_t v) { asm volatile("st.volatile.shared.u32 [%0], %1;" ::"r"(a), "r"(v) : "memory"); }
DEVINL void sts32(uint32_t a, float v) { asm volatile("st.shared.f32 [%0], %1;" ::"r"(a), "f"(v) : "memory"); }

DEVINL uint4 ld_msg(const void* p) {
  unsigned long long a, b;
  asm volatile("{\n.reg .b128 r;\nld.relaxed.gpu.global.b128 r, [%2];\nmov.b128 {%0, %1}, r;\n}" : "=l"(a), "=l"(b) : "l"(p) : "memory");
  return make_uint4((uint32_t)a, (uint32_t)(a >> 32), (uint32_t)b, (uint32_t)(b >> 32));
}
DEVINL void st_msg(void* p, uint32_t x, uint32_t y, uint32_t z, uint32_t w) {
  unsigned long long a = (unsigned long long)x | ((unsigned long long)y << 32), b = (unsigned long long)z | ((unsigned long long)w << 32);
  asm volatile("{\n.reg .b128 r;\nmov.b128 r, {%1, %2};\nst.relaxed.gpu.global.b128 [%0], r;\n}" ::"l"(p), "l"(a), "l"(b) : "memory");
}
DEVINL uint2 ld_msg8(const void* p) {
  unsigned long long a;
  asm volatile("ld.relaxed.gpu.global.b64 %0, [%1];" : "=l"(a) : "l"(p) : "memory");
  return make_uint2((uint32_t)a, (uint32_t)(a >> 32));
}
DEVINL void st_msg8(void* p, uint32_t x, uint32_t y) {
  asm volatile("st.relaxed.gpu.global.b64 [%0], %1;" ::"l"(p), "l"((unsigned long long)x | ((unsigned long long)y << 32)) : "memory");
}
DEVINL unsigned ld_rlx(const void* p) { unsigned v; asm volatile("ld.relaxed.gpu.global.u32 %0, [%1];" : "=r"(v) : "l"(p) : "memory"); return v; }
DEVINL void st_rlx(unsigned* p, unsigned v) { asm volatile("st.relaxed.gpu.global.u32 [%0], %1;" ::"l"(p), "r"(v) : "memory"); }
DEVINL void red_add(unsigned* p, unsigned v) { asm volatile("red.relaxed.gpu.global.add.u32 [%0], %1;" ::"l"(p), "r"(v) : "memory"); }
DEVINL uint4 ldg_nc(const void* p) {
  uint4 v;
  asm volatile("ld.global.nc.L1::no_allocate.v4.u32 {%0, %1, %2, %3}, [%4];" : "=r"(v.x), "=r"(v.y), "=r"(v.z), "=r"(v.w) : "l"(p));
  return v;
}
DEVINL float4 ldg_cg(const float* p) { float4 v; asm volatile("ld.global.cg.v4.f32 {%0, %1, %2, %3}, [%4];" : "=f"(v.x), "=f"(v.y), "=f"(v.z), "=f"(v.w) : "l"(p) : "memory"); return v; }
DEVINL void wait_cnt(const unsigned* p, unsigned target) {
  int it = 0;
  while ((int)(ld_rlx(p) - target) < 0) { SPIN_CHECK(it); __nanosleep(100); }
}

#define TRACE2(id)
#define TRACE(id)
#define TRACE_CLK(id)

#define STAMP(i)
DEVINL uint32_t fkey(float v) { const uint32_t u = __float_as_uint(v); return (u & 0x80000000u) ? ~u : (u | 0x80000000u); }
DEVINL float fkey_inv(uint32_t k) { return __uint_as_float((k & 0x80000000u) ? (k & 0x7FFFFFFFu) : ~k); }
DEVINL uint32_t redux_max(uint32_t v) { uint32_t r; asm volatile("redux.sync.max.u32 %0, %1, 0xffffffff;" : "=r"(r) : "r"(v)); return r; }
DEVINL void warp_top2(uint32_t key, uint32_t& k1, uint32_t& k2) { k1 = redux_max(key); k2 = redux_max(key == k1 ? 0u : key); }
DEVINL int key_row(uint32_t k) { return 2047 - (int)(k & 2047u); }
DEVINL int blk_src(int q, int cgrp) { const int f = q - 4, kk = (f * 37) >> 8, i = f - kk * 7; return f < 0 ? cgrp * 4 + q : (i + (i >= cgrp)) * 4 + kk; }
DEVINL uint32_t pstage(int kk) { return ((0xB4A4 >> (kk * 4)) & 15) * SLOT; }
DEVINL uint32_t buf_off(int u) { return ((0x42130 >> (u * 4)) & 15) * BUF; }
DEVINL int cnt_idx(int kb) { return kb < 4 ? (8 + kb) * 32 : (kb >> 2) * 32 + (kb & 3); }
DEVINL int perm32(int e) { return (e & ~30) | ((e >> 2) & 6) | ((e << 2) & 24); }

__global__ void __launch_bounds__(384, 1) __cluster_dims__(2, 1, 1)
fused_kernel(const __nv_bfloat16* __restrict__ x, Scratch* const S, __nv_bfloat16* __restrict__ out, const __nv_bfloat16* __restrict__ cvec,
             const __nv_bfloat16* __restrict__ wd_re, const __nv_bfloat16* __restrict__ wd_im, const __grid_constant__ Params prm) {
  extern __shared__ __align__(1024) uint8_t smem_raw[];
  const uint32_t sb = smem_u32(smem_raw);
  const int tid = threadIdx.x, lane = tid & 31;
  const int warp = __shfl_sync(~0u, tid >> 5, 0);
  const int cl = blockIdx.x >> 1;
  const int rank = blockIdx.x & 1, c7 = ((cl - 36) * 37) >> 8;
  const int grp = cl < 4 ? 0 : cl < 36 ? (cl - 4) & 7 : cl - 35 - c7 * 7, gi = cl < 4 ? cl + 4 : cl < 36 ? (cl - 4) >> 3 : c7 + 4;
  const int j = gi >> 2, m4 = gi & 3, t = grp * 2 + rank;
  const int cgrp = m4 * 2 + j;
  const int b = t * 8 + cgrp;
  const bool moe = gi < 7;
  const int eb0 = j ? 64 + grp * 6 : grp * 8, eb = eb0 + m4 * 2 + rank;
  auto BAR = [&](int i) { return sb + BAR_OFF + i * 8; };

  uint4 xr[8];
  if ((warp & ~1) == 2) {
    const uint4* src = reinterpret_cast<const uint4*>(x + (size_t)(blockIdx.x * 2 + warp - 2) * D_) + lane;
#pragma unroll
    for (int i = 0; i < 4; i++) xr[i] = ldg_nc(src + 32 * i);
  }
  if (tid == 0) TRACE(0);
  if ((warp & ~1) != 2 && elect_one()) {
    const int w = warp < 2 ? warp : warp - 2;
#pragma unroll
    for (int k = 0; k < 5; k++) {
      const int i = w + 10 * k;
      if (i < B_NUM) mbar_init(BAR(i), (uint32_t)((i < 16 ? CNT0 : i < 32 ? CNT1 : CNT2) >> ((i & 15) * 4)) & 15u);
    }
    if (w == 9) sts32v(sb + RDY_OFF, 15);
    if (w < 4) mbar_expect_tx(BAR(B_FULL + w), STAGE);
    asm volatile("fence.mbarrier_init.release.cluster;" ::: "memory");
    if (w == 0) tma_2d(sb, &prm.ws[j], 0, t * 128, BAR(B_FULL), pol<0>());
    else prefetch_tmap(&prm.ws[1] + w);
  }
  if ((warp & ~1) != 2) { named_bar<4, 320>(); asm volatile("bar.arrive 3, 384;" ::: "memory"); }
  asm volatile("barrier.cluster.arrive.relaxed.aligned;" ::: "memory");

  if (warp < 4) {
    auto touch_piece = [&](int p) {
      if (p < 64 || moe) {
        const int y = p < 64 ? eb0 >> 2 : 0, z = p < 64 ? (p & 31) * 32 + (m4 * 2 + rank) * 4 : eb * 128 + (p - 64) * 4;
        if ((p >= FK_PHOME) != (p >= FK_PTOUCH)) asm volatile("cp.async.bulk.prefetch.tensor.3d.L2.global [%0, {0, %1, %2}];" ::"l"(&prm.tch[p >> 5]), "r"(y), "r"(z) : "memory");
        else {
          asm volatile("mbarrier.expect_tx.relaxed.cta.shared::cta.b64 [%0], 128;" ::"r"(BAR(B_TAB)) : "memory");
          tma_3d(sb + DUMMY_OFF, &prm.tch[p >> 5], y, z, BAR(B_TAB), POL_NORMAL);
        }
      }
    };
    if (warp == 0) {
      const unsigned* flagAddr = &S->cntN[cnt_idx(lane)];
      const unsigned tgt = (ld_rlx(S->epoch) + 1) * 64u;
      asm volatile("barrier.cluster.wait.acquire.aligned;" ::: "memory");
      unsigned ready = 0;
      if (lane >= 4) sts32v(sb + POLL_OFF + lane * 4, tgt - 1);
#pragma unroll 1
      for (int g = 0; g < 32; g++) {
        const int s = g & 3;
        const uint32_t sa = sb + s * STAGE, fb = BAR(B_FULL + s);
        if (!((ready >> g) & 1)) {
          unsigned v;
          asm volatile("ld.volatile.shared.u32 %0, [%1];" : "=r"(v) : "r"(sb + POLL_OFF + lane * 4) : "memory");
          ready |= __ballot_sync(~0u, v == tgt) & ~15u;
          int it = 0;
          while (!((ready >> g) & 1)) {
            ready |= __ballot_sync(~0u, (lane >> 2) == (g >> 2) && ld_rlx(flagAddr) == tgt);
            SPIN_CHECK(it);
          }
          fence_async_global();
        }
        if (g >= 4) {
          mbar_wait(BAR(B_EMPTY + s), ((g >> 2) - 1) & 1);
          if (lane < 8 && ((~ready >> (lane * 4)) & 15))
            asm volatile("cp.async.cg.shared.global [%0], [%1], 16;" ::"r"(sb + POLL_OFF + lane * 16), "l"(&S->cntN[lane * 32]) : "memory");
          if (elect_one()) { TRACE2(128 + g); mbar_expect_tx(fb, STAGE); tma_2d(sa, &prm.ws[j], g * 64, t * 128, fb, pol<0>()); }
        }
        if (g >= 4) grid_wait();
        if (elect_one()) {
          tma_3d_mc(sa + SLOT + rank * SLOT, &prm.n, g * 64, m4 * 4 + rank * 2, fb, pol<4>());
          if (g > 0 && g < 4) tma_2d(sa, &prm.ws[j], g * 64, t * 128, fb, pol<0>());
          TRACE2(64 + g);
        }
        if ((unsigned)(g - FK_WSPF) < 4u)
          asm volatile("prefetch.global.L2 [%0];" ::"l"(prm.wsp[j] + (size_t)(t * 128 + m4 * 32 + (g - FK_WSPF) * 8 + (lane >> 2)) * 4096 + 3584 + (lane & 3) * 128));
      }
      asm volatile("cp.async.wait_all;" ::: "memory");
    }
    asm volatile("" ::: "memory");
    if (warp == 1) {
      const uint32_t tag = ld_rlx(S->epoch) + 1;
      const uint32_t rb = sb + (m4 * 32 + lane) * 128 + ((lane & 7) << 4);
      float a0 = 0.f, a1 = 0.f, a2 = 0.f, a3 = 0.f;
#pragma unroll 1
      for (int g = 0; g < 32; g++) {
        const int s = g & 3;
        mbar_wait(BAR(B_FULL + s), (g >> 2) & 1);
        uint4 u[8];
#pragma unroll
        for (int c = 0; c < 8; c++) u[c] = lds128u((rb + s * STAGE) ^ (c << 4));
        u[7].x = __shfl_sync(~0u, u[7].x, lane);
        if (elect_one()) {
          mbar_arrive(BAR(B_EMPTY + s)); TRACE2(160 + g);
          if (g >= FK_G0) {
#pragma unroll 1
            for (int i = 0; i < FK_N1; i++) touch_piece(FK_P0 + (g - FK_G0) * FK_N1 + i);
          }
        }
#pragma unroll
        for (int c = 0; c < 8; c++) {
          a0 += bf_lo(u[c].x) + bf_lo(u[c].y); a1 += bf_hi(u[c].x) + bf_hi(u[c].y);
          a2 += bf_lo(u[c].z) + bf_lo(u[c].w); a3 += bf_hi(u[c].z) + bf_hi(u[c].w);
        }
      }
      if (lane == 0) mbar_arrive(BAR(B_RSDONE));
      mbar_wait(BAR(B_RSDONE), 0);
      st_msg8(&S->rs[j * S_ + t * 128 + m4 * 32 + lane], __float_as_uint((a0 + a1) + (a2 + a3)), tag);
    }
    asm volatile("" ::: "memory");
    if (warp >= 2) {
      const uint32_t ring = sb + SP_OFF + (warp - 2) * 16384, mf = BAR(B_MF + (warp - 2) * 4);
      const int jw = b >> 6, e0 = (b & 63) * 16;
      const __nv_bfloat16* src = (jw ? wd_im : wd_re) + (size_t)e0 * D_;
      int nc = 0;
#pragma unroll 1
      for (int G = 0; G < 8; G += (G == 0 && warp == 2) + 1) {
        if (G) { mbar_wait(mf + (nc & 3) * 8, (nc >> 2) & 1); nc++; }
        const uint32_t stg = ring + (nc & 3) * 4096, sl = stg + (G ? (lane >> 4) * 2048 + (lane & 15) * 16 : lane * 16), st = G ? 256 : 512;
        if (G) {
#pragma unroll
          for (int k = 0; k < 8; k++) xr[k] = lds128u(sl + k * 256);
        }
        float s0 = 0.f, s1 = 0.f, q0 = 0.f, q1 = 0.f, s2 = 0.f, s3 = 0.f, q2 = 0.f, q3 = 0.f;
        float v[64];
#pragma unroll
        for (int h = 0; h < 2; h++)
          if (h == 0 || G) {
#pragma unroll
            for (int k = 4 * h; k < 4 * h + 4; k++) {
              float* u = v + 8 * k;
              u[0] = bf_lo(xr[k].x); u[1] = bf_hi(xr[k].x); u[2] = bf_lo(xr[k].y); u[3] = bf_hi(xr[k].y);
              u[4] = bf_lo(xr[k].z); u[5] = bf_hi(xr[k].z); u[6] = bf_lo(xr[k].w); u[7] = bf_hi(xr[k].w);
#pragma unroll
              for (int i = 0; i < 8; i += 4) {
                s0 += u[i]; s1 += u[i + 1]; s2 += u[i + 2]; s3 += u[i + 3];
                q0 = fmaf(u[i], u[i], q0); q1 = fmaf(u[i + 1], u[i + 1], q1); q2 = fmaf(u[i + 2], u[i + 2], q2); q3 = fmaf(u[i + 3], u[i + 3], q3);
              }
            }
          }
        float sum = (s0 + s1) + (s2 + s3), sq = (q0 + q1) + (q2 + q3);
#pragma unroll
        for (int o = 1; o < 32; o <<= 1)
          if (o < 16 || !G) { sum += __shfl_xor_sync(~0u, sum, o); sq += __shfl_xor_sync(~0u, sq, o); }
        const float mean = sum * (1.f / D_);
        const float rstd = rsqrtf(fmaxf(fmaf(-mean, mean, sq * (1.f / D_)), 0.f) + 1e-5f), nmr = -mean * rstd;
#pragma unroll
        for (int h = 0; h < 2; h++)
          if (h == 0 || G) {
#pragma unroll
            for (int k = 4 * h; k < 4 * h + 4; k++) {
              const float* u = v + 8 * k;
              sts128u(sl + k * st, pack_bf16(fmaf(u[0], rstd, nmr), fmaf(u[1], rstd, nmr)), pack_bf16(fmaf(u[2], rstd, nmr), fmaf(u[3], rstd, nmr)),
                      pack_bf16(fmaf(u[4], rstd, nmr), fmaf(u[5], rstd, nmr)), pack_bf16(fmaf(u[6], rstd, nmr), fmaf(u[7], rstd, nmr)));
            }
          }
        fence_async_smem();
        const int kq = blockIdx.x >> 5;
        if (elect_one()) {
          bulk_store(S->n + (size_t)(G * 256 + blockIdx.x * 2 + (G ? 0 : warp - 2)) * D_, stg, G ? 4096 : 2048); bulk_commit();
          if (G == 0) { bulk_wait<0>(); rel_fence<0>(); red_add(&S->cntN[cnt_idx(kq)], 1); TRACE(42 + warp); }
        }
        if (G == 0) named_bar<3, 384>();
        if (elect_one()) {
          if (G == 0 && warp == 2) mbar_wait(BAR(B_FULL), 0);
          if (G >= 4) { bulk_wait<1>(); red_add(&S->cntN[(G - 1) * 32 + kq], 2); }
#pragma unroll 1
          for (int k = G ? nc + 1 : 0; k < (warp == 2 ? nc + 2 : 1); k++) {
            mbar_expect_tx(mf + (k & 3) * 8, 4096);
            bulk_load(ring + ((k + 1) & 3) * 4096, k < 6 ? x + (size_t)((k + 4 - warp) * 256 + blockIdx.x * 2) * D_ : src + (k - 6) * 2 * D_, 4096, mf + (k & 3) * 8, k < 6 ? pol<7>() : pol<2>());
          }
          if (G == 1 || G == 2 || G == 7) { bulk_wait<0>(); rel_fence<1>(); red_add(&S->cntN[G * 32 + kq], 2); if (G > 1) TRACE(44 + (G & 3)); }
        }
        __syncwarp();
        if (warp == 3 && G) break;
      }
      const uint32_t tag = ld_rlx(S->epoch) + 1;
      float* const mod = S->mod[tag & 1];
      if (warp == 3) {
        const uint32_t stab = sb + TAB_OFF, stg = stab + 512;
        {
          const uint32_t cw = __ldg(reinterpret_cast<const uint32_t*>(cvec + t * 64) + lane);
          const uint32_t sp = pack_bf16(silu_f(bf_lo(cw)), silu_f(bf_hi(cw)));
          sts64u(stab + lane * 8, sp << 16, sp & 0xFFFF0000u);
        }
        float acc[8];
#pragma unroll
        for (int i = 0; i < 8; i++) acc[i] = 0.f;
#pragma unroll 1
        for (int n = -3; n < 24; n++) {
          if (n < 21 && elect_one()) {
            mbar_expect_tx(mf + (n & 3) * 8, 4096);
            tma_2d(ring + (n & 3) * 4096, &prm.wm, ((n + 3) >> 3) * 2048 + cgrp * 256, t * 64 + ((n + 3) & 7) * 8, mf + (n & 3) * 8, pol<1>());
          }
          if (n < 0) continue;
          const uint32_t sl = ring + ((n + 1) & 3) * 4096 + lane * 16;
          const float4 sv0 = lds128(stab + (n & 7) * 32), sv1 = lds128(stab + (n & 7) * 32 + 16);
          const float sc[8] = {sv0.x, sv0.y, sv0.z, sv0.w, sv1.x, sv1.y, sv1.z, sv1.w};
          mbar_wait(mf + ((n + 1) & 3) * 8, ((n + 1) >> 2) & 1);
          uint4 v[8];
#pragma unroll
          for (int u = 0; u < 8; u++) v[u] = lds128u(sl + u * 512);
#pragma unroll
          for (int u = 0; u < 8; u++) {
            acc[0] = fmaf(sc[u], bf_lo(v[u].x), acc[0]); acc[1] = fmaf(sc[u], bf_hi(v[u].x), acc[1]);
            acc[2] = fmaf(sc[u], bf_lo(v[u].y), acc[2]); acc[3] = fmaf(sc[u], bf_hi(v[u].y), acc[3]);
            acc[4] = fmaf(sc[u], bf_lo(v[u].z), acc[4]); acc[5] = fmaf(sc[u], bf_hi(v[u].z), acc[5]);
            acc[6] = fmaf(sc[u], bf_lo(v[u].w), acc[6]); acc[7] = fmaf(sc[u], bf_hi(v[u].w), acc[7]);
          }
          asm volatile("" : "+f"(acc[0]) :: "memory");
          if ((n & 7) == 7) {
            sts128(stg + lane * 32, acc[0], acc[1], acc[2], acc[3]); sts128(stg + lane * 32 + 16, acc[4], acc[5], acc[6], acc[7]);
#pragma unroll
            for (int i = 0; i < 8; i++) acc[i] = 0.f;
            fence_async_smem();
            if (elect_one()) {
              asm volatile("cp.reduce.async.bulk.global.shared::cta.bulk_group.add.f32 [%0], [%1], 1024;" ::"l"(mod + (n >> 3) * 2048 + cgrp * 256), "r"(stg) : "memory");
              bulk_commit();
              if (n != 15) { bulk_wait<0>(); rel_fence<2>(); red_add(&S->cntMod[n > 7 ? 32 : 0], 1); } else bulk_wait_read<0>();
              TRACE(n > 7 ? 34 + (n >> 3) : 9);
            }
          }
        }
      } else {
        wait_cnt(S->cntMod, tag * 128u);
        if (lane == 0) TRACE(10);
        float4 sa[8];
        {
          const float4 c0 = ldg_cg(mod + D_ + m4 * 256 + lane * 8), c1 = ldg_cg(mod + D_ + m4 * 256 + lane * 8 + 4);
#pragma unroll
          for (int i = 0; i < 8; i++) {
            const float4 sv = ldg_cg(mod + (i >> 1) * 256 + lane * 8 + (i & 1) * 4);
            const uint32_t s0 = pack_bf16(sv.x, sv.y), s1 = pack_bf16(sv.z, sv.w);
            sa[i] = make_float4(bf_lo(s0), bf_hi(s0), bf_lo(s1), bf_hi(s1));
          }
          const uint32_t cw[4] = {pack_bf16(c0.x, c0.y), pack_bf16(c0.z, c0.w), pack_bf16(c1.x, c1.y), pack_bf16(c1.z, c1.w)};
#pragma unroll
          for (int q = 0; q < 4; q++) sts32v(sb + T1_OFF + (lane >> 2) * 64 + q * 16 + (lane & 3) * 4, add_bf16x2(cw[q], 0x3F803F80u) ^ (j ? 0x80008000u : 0u));
        }
        float ul = 0.f;
#pragma unroll 1
        for (int r = 0; r < 8; r++) {
          if (r < 6 && elect_one()) {
            mbar_expect_tx(mf + ((nc + 2) & 3) * 8, 4096);
            bulk_load(ring + ((nc + 3) & 3) * 4096, src + (r + 2) * 2 * D_, 4096, mf + ((nc + 2) & 3) * 8, pol<2>());
          }
          mbar_wait(mf + (nc & 3) * 8, (nc >> 2) & 1); nc++;
          uint4 v[8];
          float u[4] = {0.f, 0.f, 0.f, 0.f};
#pragma unroll
          for (int i = 0; i < 8; i++) v[i] = lds128u(ring + (nc & 3) * 4096 + lane * 16 + i * 512);
#pragma unroll
          for (int i = 0; i < 8; i++) {
            const float4 s0 = sa[2 * (i & 3)], s1 = sa[2 * (i & 3) + 1];
            float &u0 = u[(i >> 2) * 2], &u1 = u[(i >> 2) * 2 + 1];
            u0 = fmaf(bf_lo(v[i].x), s0.x, u0); u1 = fmaf(bf_hi(v[i].x), s0.y, u1); u0 = fmaf(bf_lo(v[i].y), s0.z, u0); u1 = fmaf(bf_hi(v[i].y), s0.w, u1);
            u0 = fmaf(bf_lo(v[i].z), s1.x, u0); u1 = fmaf(bf_hi(v[i].z), s1.y, u1); u0 = fmaf(bf_lo(v[i].w), s1.z, u0); u1 = fmaf(bf_hi(v[i].w), s1.w, u1);
          }
          const float ua = u[0] + u[1], ub = u[2] + u[3];
          float us = ((lane & 1) ? ub : ua) + __shfl_xor_sync(~0u, (lane & 1) ? ua : ub, 1);
#pragma unroll
          for (int o = 16; o > 1; o >>= 1) us += __shfl_xor_sync(~0u, us, o);
          if ((lane >> 1) == r) ul = jw ? -us : us;
        }
        if (lane < 16) st_msg8(&S->u[jw * D_ + e0 + lane], __float_as_uint(ul), tag);
        if (lane == 0) TRACE(11);
#pragma unroll
        for (int i = 0; i < 4; i++) sts128u(ring + lane * 16 + i * 512, SENT, SENT, SENT, SENT);
        fence_async_smem();
        if (elect_one()) {
#pragma unroll 1
          for (int i = 0; i < 9; i++)
            bulk_store(i < 4 ? &S->part[b * 512 + i * 128] : i == 4 ? &S->stats[b * 128] : &S->rowsH[((i - 5) >> 1) * 4096 + (t * 2 + (i & 1)) * 128 + cgrp * 16], ring, i < 5 ? 2048 : 256);
          bulk_commit(); bulk_wait<0>(); rel_fence<4>();
          mbar_arrive(BAR(B_RSDONE)); TRACE(30);
        }
        if (lane < 12) reinterpret_cast<float4*>(S->mod[~tag & 1] + b * 48)[lane] = make_float4(0.f, 0.f, 0.f, 0.f);
      }
      named_bar<1, 64>();
    }
    asm volatile("setmaxnreg.dec.sync.aligned.u32 40;" ::: "memory");
    const uint32_t tag = ld_rlx(S->epoch) + 1;
    if (warp == 0) {
      unsigned ready = 15;
      int u = 0; uint32_t ph = 1;
#pragma unroll 1
      for (int q = 0; q < 32; q++) {
        const int sc = blk_src(q, cgrp), js = (sc >> 2) & 1, kc = (sc >> 3) * 256 + (sc & 3) * 64;
        const uint32_t sa = sb + buf_off(u), fb = BAR(B_FULL2 + u);
        if (!((ready >> q) & 1)) {
          int it = 0;
          do { asm volatile("ld.volatile.shared.u32 %0, [%1];" : "=r"(ready) : "r"(sb + RDY_OFF) : "memory"); SPIN_CHECK(it); } while (!((ready >> q) & 1));
          ready = __shfl_sync(~0u, ready, 0);
          fence_async_global();
        }
        if (q == 8) mbar_wait(BAR(B_PS + 1), 0);
        mbar_wait(BAR(q >= 5 ? B_EMPTY2 + u : q < 2 ? B_ADONE : q == 4 ? B_EMPTY + 3 : B_EMPTY + 1), q >= 2 ? ph : 0);
        if (elect_one()) {
          mbar_expect_tx(fb, q < 4 ? SLOT : BUF);
          tma_5d_mc(sa + SLOT + rank * 8192, &prm.wd[js], kc, cgrp * 4 + rank * 2, fb, pol<6>());
          if (q >= 4) tma_2d(sa, &prm.p, kc, js * S_ + t * 128, fb, pol<5>());
          if (q & 1) TRACE2(96 + (q >> 1));
        }
        if (++u == 5) { u = 0; ph ^= 1; }
      }
      if (elect_one()) {
        mbar_expect_tx(BAR(B_DN), moe ? 65536 : 0);
#pragma unroll 1
        for (int i = 0; i < 9; i++) {
          if ((i & 3) == 0) mbar_wait(BAR(B_EMPTY2 + 2 + (i >> 2)), 1);
          if (i == 0) mbar_arrive(BAR(B_B27));
          else if (moe)
            asm volatile("cp.async.bulk.tensor.5d.shared::cluster.global.mbarrier::complete_tx::bytes.L2::cache_hint [%0], [%1, {0, 0, 0, %3, %4}], [%2], %5;"
                         ::"r"(sb + RKA_OFF + (i + (i >> 3) * 4) * 8192), "l"(&prm.wdn), "r"(BAR(B_DN)), "r"(eb * 2), "r"(i * 2 - 2), "l"(pol<3>()) : "memory");
        }
      }
    }
    asm volatile("" ::: "memory");
    if (warp == 1) {
      if (elect_one()) {
#pragma unroll 1
        for (int kk = 0; kk < 4; kk++) {
          mbar_wait(BAR(B_PREADY + kk), 0);
          if (kk == 3 && FK_P3DELAY) spin(FK_P3DELAY);
          tma_store_2d(&prm.p, sb + pstage(kk), m4 * 256 + kk * 64, j * S_ + t * 128);
          bulk_commit(); bulk_wait<0>();
          if (!(kk & 1)) mbar_arrive(BAR(B_PS + (kk >> 1)));
          rel_fence<3>();
          st_rlx(&S->flagP[(b * 4 + kk) * 8], tag);
          TRACE(40 + kk);
        }
        prefetch_tmap(&prm.om);
        unsigned next = clk32();
#pragma unroll 1
        for (int n = 0; n < 16; n++) {
          const int r = n >> 2, i = n & 3;
          const uint32_t bar = BAR(B_EFULL - (r & 1)), dst = sb + ((r & 1) ? SP_OFF : E_OFF) + i * 8192;
          while ((int)(clk32() - next) < 0) __nanosleep(20);
          if (i == 0) { if (r) mbar_wait(BAR(B_TAKEN + r - 1), 0); mbar_expect_tx(bar, moe || r == 2 ? 32768 : 0); TRACE(60 + r); }
          if (r == 2) { tma_3d(dst, &prm.xm, t * 128 + i * 32, cgrp * 4, bar, pol<8>()); tma_3d(dst + 4096, &prm.xm, t * 128 + i * 32 + 16, cgrp * 4, bar, pol<8>()); }
          else if (moe) tma_5d(dst, r ? &prm.wu : &prm.wg, eb * 32, (r == 1 ? 0 : 16) + i * 4, bar);
          next = clk32() + FK_SPACE;
        }
      }
    }
    asm volatile("" ::: "memory");
    if (warp == 2) {
      unsigned ready = 15;
      if (elect_one()) {
        fence_async_smem();
        mbar_expect_tx(BAR(B_SPFULL), moe ? 32768 : 0);
        if (moe) {
#pragma unroll 1
          for (int i = 0; i < 4; i++) { tma_5d(sb + SP_OFF + i * 8192, &prm.wg, eb * 32, i * 4, BAR(B_SPFULL)); spin(500); }
        }
      }
      __syncwarp();
      const unsigned* flagAddr = &S->flagP[(t * 32 + blk_src(lane, cgrp)) * 8];
      mbar_wait(BAR(B_PREADY), 0);
      int it = 0;
      while (ready != ~0u) {
        ready |= __ballot_sync(~0u, !((ready >> lane) & 1) && lane < __ffs(~ready) + 8 && ld_rlx(flagAddr) == tag);
        if (lane == 0) sts32v(sb + RDY_OFF, ready);
        SPIN_CHECK(it);
      }
      wait_cnt(&S->cntMod[32], tag * 128u);
      mbar_wait(BAR(B_PREADY + 3), 0);
      {
        const float* mp = S->mod[tag & 1] + cgrp * 128 + lane * 4;
        const float4 ga = ldg_cg(mp + 2 * D_), sv = ldg_cg(mp + 3 * D_), cb = ldg_cg(mp + 4 * D_), gb = ldg_cg(mp + 5 * D_);
        const uint2 wr = __ldg(reinterpret_cast<const uint2*>(prm.w_r + cgrp * 128 + lane * 4));
        const uint32_t Aa = add_bf16x2(pack_bf16(cb.x, cb.y), 0x3F803F80u), Ab = add_bf16x2(pack_bf16(cb.z, cb.w), 0x3F803F80u);
        const uint32_t Sa = pack_bf16(sv.x, sv.y), Sb = pack_bf16(sv.z, sv.w), Ga = pack_bf16(gb.x, gb.y), Gb = pack_bf16(gb.z, gb.w);
        const float w0 = bf_lo(Aa) * bf_lo(wr.x), w1 = bf_hi(Aa) * bf_hi(wr.x), w2 = bf_lo(Ab) * bf_lo(wr.y), w3 = bf_hi(Ab) * bf_hi(wr.y);
        const uint32_t tb = sb + TAB_OFF + lane * 8, Wa = pack_bf16(w0, w1), Wb = pack_bf16(w2, w3);
        sts64u(tb, Wa, Wb);
        sts64u(tb + 320, 0x3F803F80u, 0x3F803F80u);
        sts64u(tb + 640, pack_bf16(w0 - bf_lo(Wa), w1 - bf_hi(Wa)), pack_bf16(w2 - bf_lo(Wb), w3 - bf_hi(Wb)));
        sts64u(tb + 960, pack_bf16(ga.x, ga.y), pack_bf16(ga.z, ga.w));
        sts64u(tb + 1280, Aa, Ab); sts64u(tb + 1600, Sa, Sb); sts64u(tb + 1920, Ga, Gb);
        float c1 = (w0 + w1) + (w2 + w3), c2 = (bf_lo(Sa) * bf_lo(wr.x) + bf_hi(Sa) * bf_hi(wr.x)) + (bf_lo(Sb) * bf_lo(wr.y) + bf_hi(Sb) * bf_hi(wr.y));
#pragma unroll 1
        for (int h = 0; h < 2; h++) {
#pragma unroll
          for (int o = 16; o; o >>= 1) { c1 += __shfl_xor_sync(~0u, c1, o); c2 += __shfl_xor_sync(~0u, c2, o); }
          if (h) break;
          if (t == 0 && lane == 0) st_msg(&S->cst[cgrp], __float_as_uint(c1), __float_as_uint(c2), tag, 0);
          uint4 cm; it = 0;
          while (true) {
            cm = ld_msg(&S->cst[lane & 7]);
            if (__all_sync(~0u, cm.z == tag)) break;
            SPIN_CHECK(it); __nanosleep(200);
          }
          c1 = 0.25f * __uint_as_float(cm.x); c2 = 0.25f * __uint_as_float(cm.y);
        }
        if (lane == 0) { sts128u(sb + CST_OFF, __float_as_uint(c1), __float_as_uint(c2), tag, 0); TRACE(27); }
      }
      uint32_t rk[16];
#pragma unroll
      for (int h = 0; h < 2; h++) {
        const uint2* src = (h ? &S->u[cgrp * 128] : &S->rs[t * 128]) + lane;
        uint2 m[8]; it = 0;
        while (true) {
          bool ok = true;
#pragma unroll
          for (int i = 0; i < 8; i++) { m[i] = ld_msg8(src + (i >> 1) * 32 + (i & 1) * (h ? D_ : S_)); ok &= m[i].y == tag; }
          if (ok) break;
          SPIN_CHECK(it);
        }
#pragma unroll
        for (int i = 0; i < 4; i++) {
          const float r0 = __uint_as_float(m[2 * i].x) * (h ? 0.5f : 1.f), r1 = __uint_as_float(m[2 * i + 1].x) * (h ? 0.5f : 1.f);
          const uint32_t hi = pack_bf16(r0, r1);
          rk[h * 8 + 2 * i] = hi; rk[h * 8 + 2 * i + 1] = pack_bf16(r0 - bf_lo(hi), r1 - bf_hi(hi));
        }
      }
      mbar_wait(BAR(B_B27), 0);
#pragma unroll
      for (int i = 0; i < 4; i++) {
        sts128u(sb + RKA_OFF + (i * 32 + lane) * 16, rk[2 * i], rk[2 * i], rk[2 * i + 1], 0);
        sts128u(sb + RKB_OFF + (i * 32 + perm32(lane)) * 16, rk[8 + 2 * i], rk[9 + 2 * i], rk[8 + 2 * i], 0);
      }
      fence_async_smem();
      __syncwarp();
      if (lane == 0) { mbar_arrive(BAR(B_TAB)); TRACE(26); }
    }
    asm volatile("" ::: "memory");
    if (warp == 3) {
      if (elect_one()) {
        unsigned next = clk32();
#pragma unroll 1
        for (int p = FK_P0 + (32 - FK_G0) * FK_N1; p < FK_PEND; p++) {
          touch_piece(p);
          next += FK_PACE;
          while ((int)(clk32() - next) < 0) __nanosleep(20);
        }
        mbar_arrive(BAR(B_TAB)); TRACE(37);
      }
      __syncwarp();
      mbar_wait(BAR(B_B27), 0);
      mbar_wait(BAR(B_EMPTY2 + 4), 1);
      uint4 m; int it = 0;
      while (true) {
        m = ld_msg(&S->cand[(lane >> 1) * 8]);
        if (__all_sync(~0u, m.z == tag)) break;
        SPIN_CHECK(it);
      }
      uint32_t k1, k2;
      const uint32_t key = (lane & 1) ? m.y : m.x;
      warp_top2(key, k1, k2);
      if (lane == 0) { sts64u(sb + SEL_OFF, k1, k2); mbar_arrive(BAR(B_SEL)); TRACE(14); }
    }
  } else {
    const int cw = (warp - 4) >> 2;
    const int cwarp = warp - 4;
    const int gq = lane >> 2, q4 = lane & 3;
    const bool elect = (tid & 127) == 0;
    auto release = [&](int bar, bool both) { if ((tid & 126) == 0) arrive_peer(BAR(bar), both ? tid & 1 : rank); };
    asm volatile("barrier.cluster.wait.acquire.aligned;" ::: "memory");

    uint32_t wf[64], uf[64], df[64];
    const int kr = (lane & 7) + (lane >> 4) * 8;
    const uint32_t wo = cwarp * 4096 + kr * 64 + ((((lane >> 3) & 1) ^ ((kr >> 1) & 3)) << 4);
    auto take = [&](uint32_t base, uint32_t* dst) {
#pragma unroll
      for (int i = 0; i < 8; i++) ldsm_x4_t(base + (wo ^ ((i & 1) << 5)) + (i >> 1) * 1024, dst + i * 4);
    };
    auto take_part = [&](uint32_t base, uint32_t* dst, int part) {
#pragma unroll
      for (int i = 0; i < 4; i++)
        asm volatile("{\n.reg .pred p;\nsetp.eq.s32 p, %10, %11;\n"
                     "@p ldmatrix.sync.aligned.m8n8.x4.trans.shared.b16 {%0, %1, %2, %3}, [%8];\n"
                     "@p ldmatrix.sync.aligned.m8n8.x4.trans.shared.b16 {%4, %5, %6, %7}, [%9];\n}"
                     : "+r"(dst[8 * i]), "+r"(dst[8 * i + 1]), "+r"(dst[8 * i + 2]), "+r"(dst[8 * i + 3]), "+r"(dst[8 * i + 4]), "+r"(dst[8 * i + 5]), "+r"(dst[8 * i + 6]), "+r"(dst[8 * i + 7])
                     : "r"(base + wo + i * 1024), "r"(base + (wo ^ 32) + i * 1024), "r"(part), "r"(i) : "memory");
    };
    uint32_t xw[32];
    const uint32_t slab = sb + E_OFF + cwarp * 4096;
    auto take_x = [&](int part) {
#pragma unroll
      for (int i = 0; i < 4; i++)
        asm volatile("{\n.reg .pred p;\nsetp.eq.s32 p, %9, %10;\n"
                     "@p ld.shared.v4.u32 {%0, %1, %2, %3}, [%8];\n@p ld.shared.v4.u32 {%4, %5, %6, %7}, [%8 + 512];\n}"
                     : "+r"(xw[8 * i]), "+r"(xw[8 * i + 1]), "+r"(xw[8 * i + 2]), "+r"(xw[8 * i + 3]), "+r"(xw[8 * i + 4]), "+r"(xw[8 * i + 5]), "+r"(xw[8 * i + 6]), "+r"(xw[8 * i + 7])
                     : "r"(slab + lane * 16 + i * 1024), "r"(part), "r"(i) : "memory");
    };
    const int row0 = cwarp * 16 + gq;
    float lo[64];
    {
      float pa[64], pb[64];
      {
        float acc[128];
#pragma unroll 1
        for (int g = 0; g < 28; g++) {
          const int s = g & 3;
          mbar_wait(BAR(B_FULL + s), (g >> 2) & 1);
          const uint32_t sa = sb + s * STAGE;
          const uint64_t da = make_desc(sa + cw * 8192, 16, 1024), db = make_desc(sa + SLOT, 8192, 1024);
          wg_fence();
          wgmma_n256<1>(acc, da, db, g > 0);
#pragma unroll
          for (int k = 1; k < 4; k++) wgmma_n256<1>(acc, da + k * 2, db + k * 128, 1);
          wg_commit();
          wg_wait<1>();
          if (g > 0) { release(B_EMPTY + ((g - 1) & 3), true); if (elect) TRACE2(191 + g + cw * 32); }
        }
        wg_wait<0>();
        release(B_EMPTY + 3, true);
#pragma unroll
        for (int i = 0; i < 64; i++) {
          asm volatile("mov.b32 %0, %1;" : "=f"(pa[i]) : "f"(acc[i]));
          asm volatile("mov.b32 %0, %1;" : "=f"(pb[i]) : "f"(acc[64 + i]));
        }
      }
      if (elect) TRACE(3 + tr);
      const uint64_t da0 = make_desc(sb + cw * 8192, 16, 1024), db0 = make_desc(sb + SLOT, 8192, 1024);
#pragma unroll 1
      for (int s = 0; s < 4; s++) {
        mbar_wait(BAR(B_FULL + s), 1);
        wg_fence();
#pragma unroll
        for (int k = 0; k < 4; k++) wgmma_n128<1>(pa, da0 + s * (STAGE >> 4) + k * 2, db0 + s * (STAGE >> 4) + k * 128);
        wg_commit();
        if (s == 2) { wg_wait<1>(); if (elect) mbar_arrive(BAR(B_A29)); }
      }
      auto b_block = [&](int s) {
        wg_fence();
#pragma unroll
        for (int k = 0; k < 4; k++) wgmma_n128<1>(pb, da0 + s * (STAGE >> 4) + k * 2, db0 + s * (STAGE >> 4) + 1024 + k * 128);
        wg_commit();
      };
      uint32_t pk[64];
      const uint32_t so = sb + (uint32_t)(cwarp * 16 + (lane & 15)) * 128 + (((lane >> 4) ^ (lane & 7)) << 4);
      auto stage_p = [&](int kk, const float* a, int slotFree, int parity) {
        const uint4 t0 = lds128u(sb + T1_OFF + kk * 128 + q4 * 16), t1 = lds128u(sb + T1_OFF + kk * 128 + 64 + q4 * 16);
        const uint32_t A[8] = {t0.x, t0.y, t0.z, t0.w, t1.x, t1.y, t1.z, t1.w};
#pragma unroll
        for (int i = 0; i < 16; i++) pk[kk * 16 + i] = mul_bf16x2(pack_bf16(a[2 * i], a[2 * i + 1]), A[i >> 1]);
        if (slotFree >= 0) mbar_wait(BAR(slotFree), parity);
#pragma unroll
        for (int k = 0; k < 4; k++) stsm_x4((so ^ (k << 5)) + pstage(kk), pk + kk * 16 + k * 4);
      };
      auto p_ready = [&](int kk) { fence_async_smem(); if (elect_one()) mbar_arrive(BAR(B_PREADY + kk)); };
      auto own_block = [&](int q) {
        mbar_wait(BAR(B_FULL2 + q), 0);
        const uint64_t db = make_desc(sb + buf_off(q) + SLOT, 16, 1024);
        wg_fence();
        if (q == 0) wgmma_n128_rs<0>(lo, pk, db); else wgmma_n128_rs<1>(lo, pk + q * 16, db);
#pragma unroll
        for (int k = 1; k < 4; k++) wgmma_n128_rs<1>(lo, pk + q * 16 + k * 4, db + k * 2);
        wg_commit();
      };
      b_block(0);
      mbar_wait(BAR(B_RSDONE), 0);
      asm volatile("setmaxnreg.inc.sync.aligned.u32 232;" ::: "memory");
      wg_wait<1>();
      reg_fence(pa);
      release(B_ADONE, true);
      if (elect) TRACE(4 + tr);
      stage_p(0, pa, B_A29, 0); p_ready(0);
      if (elect) TRACE(2 + tr);
      b_block(1);
      stage_p(1, pa + 32, B_ADONE, 0);
      wg_wait<1>(); release(B_EMPTY, true);
      b_block(2);
      p_ready(1);
      wg_wait<1>(); release(B_EMPTY + 1, true);
      b_block(3);
      wg_wait<1>(); release(B_EMPTY + 2, true);
      own_block(0);
      wg_wait<1>(); release(B_EMPTY + 3, true);
      reg_fence(pb);
      if (elect) TRACE(1 + tr);
      own_block(1);
      stage_p(2, pb, B_PS, 0);
      wg_wait<1>(); release(B_EMPTY2, true);
      own_block(2);
      p_ready(2);
      stage_p(3, pb + 32, B_EMPTY + 3, 1);
      wg_wait<1>(); release(B_EMPTY2 + 1, true);
      own_block(3);
      p_ready(3);
      wg_wait<1>(); release(B_EMPTY2 + 2, true);
    }
    {
      int u = 4, up = 3; uint32_t ph = 0;
#pragma unroll 1
      for (int q = 4; q < 32; q++) {
        mbar_wait(BAR(B_FULL2 + u), ph);
        const uint32_t sa = sb + buf_off(u);
        const uint64_t da = make_desc(sa + cw * 8192, 16, 1024), db = make_desc(sa + SLOT, 16, 1024);
        wg_fence();
#pragma unroll
        for (int k = 0; k < 4; k++) wgmma_n128<0>(lo, da + k * 2, db + k * 2);
        wg_commit();
        wg_wait<1>();
        if (q < 31) release(B_EMPTY2 + up, q < 28);
        const int r = (q >= FK_Q1) + (q >= FK_Q2) + (q >= FK_Q3), part = q - ((FK_QA | FK_Q1 << 8 | FK_Q2 << 16 | FK_Q3 << 24) >> (r * 8) & 255);
        if ((unsigned)part < 5u) {
          if (part == 0) mbar_wait(BAR(B_SPFULL + (r & 1)), r >> 1);
          if (part == 4) { if (r < 3) { fence_async_smem(); if (elect_one()) mbar_arrive(BAR(B_TAKEN + r)); } }
          else if (q >= FK_Q2) { if (q >= FK_Q3) take_x(part); else take_part(sb + SP_OFF, uf, part); }
          else { if (q >= FK_Q1) take_part(sb + E_OFF, wf + 32, part); else take_part(sb + SP_OFF, wf, part); }
        }
        up = u;
        if (++u == 5) { u = 0; ph ^= 1; }
      }
    }
    mbar_wait(BAR(B_TAB), 0);
    wg_fence();
    wgmma_n128<0>(lo, make_desc(sb + RKA_OFF + cw * 1024, 0, 128, 0), make_desc(sb + RKB_OFF, 0, 128, 0));
    wg_commit();
    const uint32_t tq = sb + TAB_OFF + q4 * 16;
    const bool odd = q4 & 1;
    {
      uint4 gw[4];
#pragma unroll
      for (int a = 0; a < 4; a++) gw[a] = lds128u(tq + 960 + a * 64);
      wg_wait<0>();
      reg_fence(lo);
      STAMP(0);
      if (elect) { TRACE(7 + tr); if (cw == 0) TRACE_CLK(121); }
      float c[2][4], e0[2][4], e1[2][4];
#pragma unroll
      for (int i = 0; i < 4; i++) c[0][i] = c[1][i] = e0[0][i] = e0[1][i] = e1[0][i] = e1[1][i] = 0.f;
#pragma unroll
      for (int a = 0; a < 4; a++) {
        const uint4 bw = lds128u(tq + (gq & 3) * 320 + a * 64);
        const uint32_t g[4] = {gw[a].x, gw[a].y, gw[a].z, gw[a].w};
#pragma unroll
        for (int i = 0; i < 8; i++) {
          const float* v = lo + a * 16 + (i & 3) * 4 + (i >> 2) * 2;
          xw[a * 8 + i] = fma_bf16x2(g[i & 3], pack_bf16(v[0], v[1]), xw[a * 8 + i]);
        }
#pragma unroll
        for (int h = 0; h < 2; h++) {
          const uint32_t* w = xw + a * 8 + h * 2;
          const uint32_t A[4] = {w[0], w[4], w[1], w[5]};
          mma_16816(e0[h], A, w[0], w[1]); mma_16816(e1[h], A, w[4], w[5]);
          mma_16816(c[h], A, h ? bw.z : bw.x, h ? bw.w : bw.y);
        }
      }
      const float c0 = c[0][0] + c[1][0], c2 = c[0][2] + c[1][2];
      const float q0 = (gq & 1) ? e0[0][1] + e0[1][1] : e0[0][0] + e0[1][0], q1 = (gq & 1) ? e1[0][3] + e1[1][3] : e1[0][2] + e1[1][2];
      const int dl = (lane & ~3) | (gq >> 1);
      const float da = (odd ? c2 : c0) + __shfl_xor_sync(~0u, odd ? c0 : c2, 1), s1 = __shfl_xor_sync(~0u, c[0][3] + c[1][3], 1);
      const float qa = __shfl_sync(~0u, q0, dl), qb = __shfl_sync(~0u, q1, dl);
      if (q4 < 2) st_msg(&S->stats[b * 128 + row0 + 8 * q4], __float_as_uint(odd ? s1 : c[0][1] + c[1][1]), __float_as_uint(odd ? qb : qa), __float_as_uint(da), 0);
    }
    if (elect) TRACE(8 + tr);
    STAMP(1);
    mbar_wait(BAR(B_SPFULL), 0);
    take(sb + SP_OFF, uf + 32);
    uint4 tA[4], tS[4];
#pragma unroll
    for (int a = 0; a < 4; a++) { tA[a] = lds128u(tq + 1280 + a * 64); tS[a] = lds128u(tq + 1600 + a * 64); }
    STAMP(2);
    uint32_t rh[2], rl[2], nm[2];
    uint32_t bk1, bk2;
    {
      uint4 m[4];
      const uint4* src = &S->stats[(t * 8 + (q4 >> 1) * 4) * 128 + row0 + 8 * (q4 & 1)];
      const float4 cst = lds128(sb + CST_OFF);
      int it = 0;
      while (true) {
#pragma unroll
        for (int i = 0; i < 4; i++) m[i] = ld_msg(src + 128 * i);
        if (__all_sync(~0u, (m[0].w | m[1].w | m[2].w | m[3].w) == 0)) break;
        SPIN_CHECK(it);
      }
      STAMP(3);
      float sa = (__uint_as_float(m[0].x) + __uint_as_float(m[1].x)) + (__uint_as_float(m[2].x) + __uint_as_float(m[3].x));
      float qa = (__uint_as_float(m[0].y) + __uint_as_float(m[1].y)) + (__uint_as_float(m[2].y) + __uint_as_float(m[3].y));
      float da = (__uint_as_float(m[0].z) + __uint_as_float(m[1].z)) + (__uint_as_float(m[2].z) + __uint_as_float(m[3].z));
      sa += __shfl_xor_sync(~0u, sa, 2); qa += __shfl_xor_sync(~0u, qa, 2); da += __shfl_xor_sync(~0u, da, 2);
      const float mean = sa * (1.f / D_);
      const float rs = rsqrtf(fmaxf(fmaf(-mean, mean, qa * (1.f / D_)), 0.f) + 1e-5f);
      const float r = fmaf(rs, fmaf(-mean, cst.x, da), cst.y);
      uint32_t k1, k2;
      warp_top2((fkey(r) & ~2047u) | (uint32_t)(2047 - (t * 128 + row0 + 8 * (q4 & 1))), k1, k2);
      if (lane == 0) sts64u(sb + TOP_OFF + cwarp * 8, k1, k2);
      const uint32_t h = pack_bf16(rs, rs), ln = pack_bf16(rs - bf_lo(h), -mean * rs), hx = __shfl_xor_sync(~0u, h, 1), lx = __shfl_xor_sync(~0u, ln, 1);
      rh[0] = odd ? hx : h; rh[1] = odd ? h : hx;
      rl[0] = __byte_perm(odd ? lx : ln, 0, 0x1010); rl[1] = __byte_perm(odd ? ln : lx, 0, 0x1010);
      nm[0] = __byte_perm(odd ? lx : ln, 0, 0x3232); nm[1] = __byte_perm(odd ? ln : lx, 0, 0x3232);
      if (tid == 128) TRACE(12 + 16);
      STAMP(4);
      named_bar<2, 256>();
      warp_top2(lds32u(sb + TOP_OFF + (lane & 15) * 4), bk1, bk2);
      if (tid == 128) { st_msg(&S->cand[t * 8], bk1, bk2, __float_as_uint(cst.z), 0); TRACE(13); }
      STAMP(5);
    }
    {
      const int lr1 = key_row(bk1) - t * 128, lr2 = key_row(bk2) - t * 128;
      uint4* cp[2]; bool cand[2];
#pragma unroll
      for (int r = 0; r < 2; r++) {
        const int lr = row0 + 8 * r;
        cand[r] = lr == lr1 || lr == lr2;
        cp[r] = &S->rowsH[(t * 2 + (lr == lr2)) * 128 + cgrp * 16 + q4];
      }
#pragma unroll
      for (int a = 0; a < 4; a++) {
        const uint4 tG = lds128u(tq + 1920 + a * 64);
        const uint32_t A[4] = {tA[a].x, tA[a].y, tA[a].z, tA[a].w}, B[4] = {tS[a].x, tS[a].y, tS[a].z, tS[a].w}, G[4] = {tG.x, tG.y, tG.z, tG.w};
#pragma unroll
        for (int r = 0; r < 2; r++) {
          uint32_t h[4], *w = xw + a * 8 + r * 4;
#pragma unroll
          for (int k = 0; k < 4; k++) h[k] = fma_bf16x2(fma_bf16x2(w[k], rh[r], fma_bf16x2(w[k], rl[r], nm[r])), A[k], B[k]);
          if (cand[r]) st_msg(cp[r] + a * 4, h[0], h[1], h[2], h[3]);
#pragma unroll
          for (int k = 0; k < 4; k++) w[k] = fma_bf16x2(G[k], h[k], w[k]);
          if (cand[r]) st_msg(cp[r] + 4096 + a * 4, w[0], w[1], w[2], w[3]);
          sts128u(slab + lane * 16 + (a * 2 + r) * 512, w[0], w[1], w[2], w[3]);
        }
      }
    }
    fence_async_smem();
    STAMP(6);
    mbar_wait(BAR(B_DN), 0);
    {
      const uint32_t db = sb + DN_OFF + (cwarp + (cwarp == 7) * 4) * 8192 + kr * 128 + ((((lane >> 3) & 1) ^ (lane & 7)) << 4);
#pragma unroll
      for (int i = 0; i < 16; i++) ldsm_x4_t((db ^ (((i >> 1) & 3) << 5)) + (i >> 3) * 4096 + (i & 1) * 2048, df + i * 4);
    }
    if (tid == 128) TRACE(15);
    STAMP(7);
    mbar_wait(BAR(B_SEL), 0);
    STAMP(8);
    const float2 selv = lds64(sb + SEL_OFF);
    const uint32_t key1 = __float_as_uint(selv.x), key2 = __float_as_uint(selv.y);
    const int t1 = key_row(key1) >> 7, t2 = key_row(key2) >> 7;
    const int slotA = t1 * 2, slotB = t2 * 2 + (t1 == t2 ? 1 : 0);
    const int fn = (lane >> 3) & 1, fcol = (b >> 1) * 16 + (b & 1) * 4 + q4 + ((lane >> 2) & 1) * 8;
    uint32_t fbase = SENT; float fgb = 0.f;
    const uint32_t* fbp = reinterpret_cast<const uint32_t*>(&S->rowsB[(fn ? slotB : slotA) * 128]) + (fcol >> 1);
    uint4 hb[4];
    const uint4* src = &S->rowsH[((gq & 1) ? slotB : slotA) * 128 + cwarp * 8 + q4];
    if (moe) {
#pragma unroll
      for (int i = 0; i < 4; i++) hb[i] = ld_msg(src + (i >> 1) * 64 + (i & 1) * 4);
    }
    if ((key_row(key1) >> 4) != t * 8 + cwarp && (key_row(key2) >> 4) != t * 8 + cwarp) {
      if (elect_one()) {
        asm volatile("cp.async.bulk.tensor.3d.global.shared::cta.bulk_group [%0, {0, %2, %3}], [%1];" ::"l"(&prm.om), "r"(slab), "r"(t * 128 + cwarp * 16), "r"(cgrp * 4) : "memory");
        bulk_commit();
      }
    } else {
#pragma unroll 1
      for (int i = 0; i < 8; i++) {
        const int row = t * 128 + row0 + 8 * (i & 1);
        const uint4 v = lds128u(slab + lane * 16 + i * 512);
        if (row != key_row(key1) && row != key_row(key2)) reinterpret_cast<uint4*>(out + (size_t)row * D_)[cgrp * 16 + (i >> 1) * 4 + q4] = v;
      }
    }
    STAMP(9);
    if (moe) {
      int it = 0;
      while (!__all_sync(~0u, hb[0].x != SENT && hb[1].x != SENT && hb[2].x != SENT && hb[3].x != SENT)) {
#pragma unroll
        for (int i = 0; i < 4; i++) hb[i] = ld_msg(src + (i >> 1) * 64 + (i & 1) * 4);
        SPIN_CHECK(it);
      }
      if (tid == 128) TRACE(16);
      STAMP(10);
      float c[4][4];
#pragma unroll
      for (int i = 0; i < 4; i++) c[i][0] = c[i][1] = c[i][2] = c[i][3] = 0.f;
#pragma unroll
      for (int ks = 0; ks < 8; ks++) {
        const uint32_t b0 = (ks & 1) ? hb[ks >> 1].z : hb[ks >> 1].x, b1 = (ks & 1) ? hb[ks >> 1].w : hb[ks >> 1].y;
        mma_16816(c[0], wf + ks * 8, b0, b1); mma_16816(c[1], wf + ks * 8 + 4, b0, b1);
        mma_16816(c[2], uf + ks * 8, b0, b1); mma_16816(c[3], uf + ks * 8 + 4, b0, b1);
      }
      {
        float v[4];
#pragma unroll
        for (int i = 0; i < 4; i++) v[i] = (q4 & 2) ? (odd ? c[3][i] : c[2][i]) : (odd ? c[1][i] : c[0][i]);
        sts128(sb + RED_OFF + cwarp * 512 + (q4 * 8 + (gq ^ (q4 * 2))) * 16, v[0], v[2], v[1], v[3]);
      }
    }
    STAMP(11);
    if (cwarp == 0) { fbase = ld_rlx(fbp); fgb = __uint_as_float(ld_rlx(S->mod[lds32u(sb + CST_OFF + 8) & 1] + 5 * D_ + fcol)); }
    if (moe) {
      named_bar<2, 256>();
      STAMP(12);
      float g0 = 0.f, g1 = 0.f, u0 = 0.f, u1 = 0.f;
#pragma unroll
      for (int w = 0; w < 8; w++) {
        const float2 gv = lds64(sb + RED_OFF + w * 512 + ((lane * 8) ^ ((lane & 16) * 2))), uv = lds64(sb + RED_OFF + w * 512 + 256 + ((lane * 8) ^ ((lane & 16) * 2) ^ 64));
        g0 += gv.x; g1 += gv.y; u0 += uv.x; u1 += uv.y;
      }
      const uint32_t gp = pack_bf16(g0, g1), up = pack_bf16(u0, u1), sp = pack_bf16(silu_f(bf_lo(gp)), silu_f(bf_hi(gp)));
      const uint32_t act = pack_bf16(bf_lo(sp) * bf_lo(up), bf_hi(sp) * bf_hi(up));
      uint32_t ab[4];
#pragma unroll
      for (int i = 0; i < 4; i++) ab[i] = __shfl_sync(~0u, act, i * 8 + q4 * 2 + (gq & 1));
      if (tid == 128) TRACE(31);
      STAMP(13);
#pragma unroll
      for (int T = 0; T < 2; T++) {
        float c[4][4];
#pragma unroll
        for (int i = 0; i < 4; i++) {
          c[i][0] = c[i][1] = c[i][2] = c[i][3] = 0.f;
          mma_16816(c[i], df + (T * 4 + i) * 8, ab[0], ab[1]); mma_16816(c[i], df + (T * 4 + i) * 8 + 4, ab[2], ab[3]);
        }
        float v[4];
#pragma unroll
        for (int i = 0; i < 4; i++) v[i] = (q4 & 2) ? (odd ? c[3][i] : c[2][i]) : (odd ? c[1][i] : c[0][i]);
        st_msg(&S->part[((cwarp * 16 + T * 8 + q4 * 2 + (gq >> 2)) * 128 + eb) * 4 + (gq & 3)], __float_as_uint(v[0]), __float_as_uint(v[1]), __float_as_uint(v[2]), __float_as_uint(v[3]));
      }
      if (tid == 128) TRACE(32);
      STAMP(14);
    }
    bulk_wait_read<0>();
    if (cwarp == 0) {
      const uint32_t fk = fn ? key2 : key1;
      const float sg = round_bf16(sigmoid_f(round_bf16(fkey_inv((fk & ~2047u) | 1024u))));
      int it = 0;
      while (fbase == SENT) { fbase = ld_rlx(fbp); SPIN_CHECK(it); }
      spin(moe ? FK_PDELAY : FK_PDELAY + 1200);
      uint4 m[14];
      while (true) {
        bool ok = true;
#pragma unroll
        for (int i = 0; i < 14; i++) { m[i] = ld_msg(&S->part[b * 512 + i * 32 + lane]); ok &= m[i].x != SENT; }
        if (__all_sync(~0u, ok)) break;
        SPIN_CHECK(it);
      }
      if (lane == 0) TRACE(33);
      STAMP(15);
      float y[4] = {0.f, 0.f, 0.f, 0.f};
#pragma unroll
      for (int i = 0; i < 14; i++) { y[0] += __uint_as_float(m[i].x); y[1] += __uint_as_float(m[i].y); y[2] += __uint_as_float(m[i].z); y[3] += __uint_as_float(m[i].w); }
      const bool b2 = lane & 4;
      float y0 = (b2 ? y[2] : y[0]) + __shfl_xor_sync(~0u, b2 ? y[0] : y[2], 4), y1 = (b2 ? y[3] : y[1]) + __shfl_xor_sync(~0u, b2 ? y[1] : y[3], 4);
      y0 = (fn ? y1 : y0) + __shfl_xor_sync(~0u, fn ? y0 : y1, 8);
      y0 += __shfl_xor_sync(~0u, y0, 16);
      const float upd = round_bf16(round_bf16(y0) * sg);
      if (lane < 16) out[(size_t)key_row(fk) * D_ + fcol] = __float2bfloat16_rn(fmaf(round_bf16(fgb), upd, (fcol & 1) ? bf_hi(fbase) : bf_lo(fbase)));
      if (lane == 0) {
        TRACE(34); TRACE_CLK(122);
        if (b == 0) S->epoch[0] = lds32u(sb + CST_OFF + 8);
      }
    }
  }
}

typedef CUresult (*PFN_encodeTiled)(CUtensorMap*, CUtensorMapDataType, cuuint32_t, void*, const cuuint64_t*, const cuuint64_t*,
                                    const cuuint32_t*, const cuuint32_t*, CUtensorMapInterleave, CUtensorMapSwizzle,
                                    CUtensorMapL2promotion, CUtensorMapFloatOOBfill);

static void mapnd(PFN_encodeTiled enc, CUtensorMap* m, const void* p, int nd, const cuuint64_t* dims, const cuuint64_t* str, const cuuint32_t* box,
                  CUtensorMapSwizzle sw, CUtensorMapL2promotion pr) {
  const cuuint32_t es[5] = {1, 1, 1, 1, 1};
  enc(m, CU_TENSOR_MAP_DATA_TYPE_BFLOAT16, nd, (void*)p, dims, str, box, es, CU_TENSOR_MAP_INTERLEAVE_NONE, sw, pr, CU_TENSOR_MAP_FLOAT_OOB_FILL_NONE);
}
static void map2d(PFN_encodeTiled enc, CUtensorMap* m, const void* p, uint64_t rows, uint64_t cols, uint32_t brows, uint32_t bcols,
                  CUtensorMapSwizzle sw = CU_TENSOR_MAP_SWIZZLE_128B, CUtensorMapL2promotion pr = CU_TENSOR_MAP_L2_PROMOTION_L2_128B) {
  const cuuint64_t dims[2] = {cols, rows}, str[1] = {cols * 2}; const cuuint32_t box[2] = {bcols, brows};
  mapnd(enc, m, p, 2, dims, str, box, sw, pr);
}
static void map3d(PFN_encodeTiled enc, CUtensorMap* m, const void* p, uint64_t rows, uint64_t cols, uint32_t brows, uint32_t bgroups) {
  const cuuint64_t dims[3] = {64, rows, cols / 64}, str[2] = {cols * 2, 128}; const cuuint32_t box[3] = {64, brows, bgroups};
  mapnd(enc, m, p, 3, dims, str, box, CU_TENSOR_MAP_SWIZZLE_128B, CU_TENSOR_MAP_L2_PROMOTION_L2_128B);
}
static void map5d(PFN_encodeTiled enc, CUtensorMap* m, const void* p, uint64_t cols, uint32_t bcols, uint32_t bgroups, CUtensorMapSwizzle sw) {
  const cuuint64_t rb = cols * 2, dims[5] = {cols, 2, 4, 4, 32}, str[4] = {rb, 8 * rb, 2 * rb, 32 * rb}; const cuuint32_t box[5] = {bcols, 2, 4, 4, bgroups};
  mapnd(enc, m, p, 5, dims, str, box, sw, CU_TENSOR_MAP_L2_PROMOTION_L2_128B);
}

}

extern "C" void kernel_launch(void* const* d_in, const int* in_sizes, int n_in, void* d_out, int out_size) {
  using namespace fk;
  (void)in_sizes; (void)n_in; (void)out_size;
  static PFN_encodeTiled enc = nullptr;
  static Scratch* scr = nullptr;
  if (!enc) {
    void* fn = nullptr; cudaDriverEntryPointQueryResult qr;
    cudaGetDriverEntryPoint("cuTensorMapEncodeTiled", &fn, cudaEnableDefault, &qr);
    enc = (PFN_encodeTiled)fn;
    cudaGetSymbolAddress((void**)&scr, g_scr);
    cudaFuncSetAttribute(fused_kernel, cudaFuncAttributeMaxDynamicSharedMemorySize, SMEM_BYTES);
  }
  typedef const __nv_bfloat16* bp;
  Params prm;
  prm.w_r = (bp)d_in[6];
  prm.wsp[0] = (const char*)d_in[1]; prm.wsp[1] = (const char*)d_in[2];
  map2d(enc, &prm.ws[0], d_in[1], S_, S_, 128, 64);
  map2d(enc, &prm.ws[1], d_in[2], S_, S_, 128, 64);
  map3d(enc, &prm.n, scr->n, S_, D_, 64, 2);
  map2d(enc, &prm.wm, d_in[11], D_, 6 * D_, 8, 256, CU_TENSOR_MAP_SWIZZLE_NONE, CU_TENSOR_MAP_L2_PROMOTION_L2_256B);
  map2d(enc, &prm.p, scr->P, 2 * S_, D_, 128, 64);
  map5d(enc, &prm.wd[0], d_in[3], D_, 64, 2, CU_TENSOR_MAP_SWIZZLE_128B);
  map5d(enc, &prm.wd[1], d_in[4], D_, 64, 2, CU_TENSOR_MAP_SWIZZLE_128B);
  map5d(enc, &prm.wg, d_in[7], F_, 32, 4, CU_TENSOR_MAP_SWIZZLE_64B);
  map5d(enc, &prm.wu, d_in[8], F_, 32, 4, CU_TENSOR_MAP_SWIZZLE_64B);
  for (int i = 0; i < 3; i++) {
    const cuuint64_t dims[3] = {128, i < 2 ? 28u : 2u, i < 2 ? 1024u : 14336u}, str[2] = {256, i < 2 ? 7168u : 512u}; const cuuint32_t box[3] = {8, 2, 4};
    mapnd(enc, &prm.tch[i], d_in[7 + i], 3, dims, str, box, CU_TENSOR_MAP_SWIZZLE_NONE, CU_TENSOR_MAP_L2_PROMOTION_L2_256B);
  }
  for (int i = 0; i < 2; i++) {
    const cuuint64_t dims[3] = {32, S_, 32}, str[2] = {2048, 64}; const cuuint32_t box[3] = {32, 16, 4};
    mapnd(enc, i ? &prm.om : &prm.xm, i ? d_out : d_in[0], 3, dims, str, box, CU_TENSOR_MAP_SWIZZLE_NONE, CU_TENSOR_MAP_L2_PROMOTION_L2_128B);
  }
  {
    const cuuint64_t dims[5] = {64, 2, 8, 224, 16}, str[4] = {8 * 2048, 2048, 16 * 2048, 128}; const cuuint32_t box[5] = {64, 2, 8, 2, 2};
    mapnd(enc, &prm.wdn, d_in[9], 5, dims, str, box, CU_TENSOR_MAP_SWIZZLE_128B, CU_TENSOR_MAP_L2_PROMOTION_L2_128B);
  }

  fused_kernel<<<NCTA, 384, SMEM_BYTES, cudaStreamPerThread>>>((bp)d_in[0], scr, (__nv_bfloat16*)d_out, (bp)d_in[10], (bp)d_in[3], (bp)d_in[4], prm);
}
```

```cpp
#include <cuda_runtime.h>
#include <cuda_bf16.h>
#include <cuda.h>
#include <stdint.h>

#define DEVINL __device__ __forceinline__

namespace fk {

constexpr int S_ = 2048, D_ = 1024, F_ = 3584;
constexpr int NCTA = 128;
constexpr int SLOT = 16384;
constexpr int STAGE = 3 * SLOT;
constexpr int BUF = 2 * SLOT;
constexpr int E_OFF = 5 * BUF;
constexpr int SP_OFF = 4 * STAGE;
constexpr int MISC_OFF = SP_OFF + 32768;
constexpr int SMEM_BYTES = MISC_OFF + 3072;
constexpr int BAR_OFF = MISC_OFF;
constexpr int SEL_OFF = MISC_OFF + 352;
constexpr int RDY_OFF = MISC_OFF + 360;
constexpr int CST_OFF = MISC_OFF + 368;
constexpr int DUMMY_OFF = MISC_OFF + 384;
constexpr int TAB_OFF = MISC_OFF + 512;
enum { T_WH = 0, T_ONE = 320, T_WL = 576, T_GA = 896, T_A = 1152, T_S = 1408, T_G = 1664 };
constexpr int KEY_OFF = TAB_OFF + 2048;
constexpr int POLL_OFF = TAB_OFF + 256;
constexpr int T1_OFF = TAB_OFF + 1536;
constexpr int RKA_OFF = BUF;
constexpr int RKB_OFF = RKA_OFF + 2048;
constexpr int RED_OFF = RKB_OFF + 2048;
constexpr int DN_OFF = RED_OFF + 4096;

enum { B_FULL = 0, B_EMPTY = 4, B_PREADY = 8, B_MF = 12  , B_FULL2 = 20  , B_EMPTY2 = 25  , B_A29 = 30, B_ADONE = 31,
       B_RSDONE = 32, B_TAB = 33, B_B27 = 34, B_SEL = 35, B_DN = 36, B_SPFULL = 37, B_EFULL = 38, B_TAKEN = 39  , B_PS = 42  , B_NUM = 44 };
constexpr unsigned long long CNT0 = 0x1111888855551111ull, CNT1 = 0x4244444111111111ull, CNT2 = 0x1111118881111122ull;

#define FK_REL 0x14
#define FK_WSPF 22
#define FK_G0 32
#define FK_N1 2
#define FK_P0 16
#define FK_PACE 250
#define FK_PHOME 0
#define FK_PTOUCH 96
#define FK_PEND 96
#define FK_Q1 14
#define FK_Q2 20
#define FK_Q3 27
#define FK_QA 5
#define FK_P3DELAY 1000
#define FK_SPACE 450
#define FK_OSPACE 400
#define FK_PDELAY 500
constexpr int SPIN_LIMIT = 1 << 20;
constexpr uint32_t SENT = 0xFFFFFFFFu;

struct Scratch {
  uint4 part[128 * 128 * 4];
  uint4 stats[128 * 128];
  uint4 rowsH[32 * 128];
  uint4 rowsB[32 * 128];
  uint4 cand[16 * 8];
  uint2 rs[2 * S_];
  uint4 cst[8];
  float mod[2][6 * D_];
  uint2 u[2 * D_];
  unsigned flagP[128 * 4 * 8];
  unsigned cntN[12 * 32];
  unsigned cntMod[2 * 32];
  unsigned epoch[32];
  alignas(1024) __nv_bfloat16 n[S_ * D_];
  __nv_bfloat16 P[2 * S_ * D_];
};
__device__ __align__(1024) Scratch g_scr;

struct Params {
  CUtensorMap ws[2];
  CUtensorMap n;
  CUtensorMap wm;
  CUtensorMap p;
  CUtensorMap wg, wu;
  CUtensorMap xm;
  CUtensorMap wdn;
  CUtensorMap wd[2];
  CUtensorMap om;
  CUtensorMap tch[3];
  const __nv_bfloat16* w_r;
  const char* wsp[2];
};

DEVINL uint32_t smem_u32(const void* p) { return (uint32_t)__cvta_generic_to_shared(p); }
DEVINL void mbar_init(uint32_t bar, uint32_t cnt) { asm volatile("mbarrier.init.shared::cta.b64 [%0], %1;" ::"r"(bar), "r"(cnt) : "memory"); }
DEVINL void mbar_expect_tx(uint32_t bar, uint32_t bytes) { asm volatile("mbarrier.arrive.expect_tx.shared::cta.b64 _, [%0], %1;" ::"r"(bar), "r"(bytes) : "memory"); }
DEVINL void mbar_arrive(uint32_t bar) { asm volatile("mbarrier.arrive.shared::cta.b64 _, [%0];" ::"r"(bar) : "memory"); }
DEVINL void arrive_peer(uint32_t bar, uint32_t cta) {
  asm volatile("{\n.reg .b32 ra;\nmapa.shared::cluster.u32 ra, %0, %1;\nmbarrier.arrive.shared::cluster.b64 _, [ra];\n}" ::"r"(bar), "r"(cta) : "memory");
}
DEVINL void mbar_wait(uint32_t bar, uint32_t parity) {
  asm volatile("{\n.reg .pred p;\n.reg .u32 c;\nmov.u32 c, 0;\n"
               "LW:\nmbarrier.try_wait.parity.shared::cta.b64 p, [%0], %1;\n@p bra LD;\n"
               "add.u32 c, c, 1;\nsetp.lt.u32 p, c, 1048576;\n@p bra LW;\ntrap;\nLD:\n}" ::"r"(bar), "r"(parity) : "memory");
}
DEVINL void mbar_wait_cluster(uint32_t bar, uint32_t parity) {
  asm volatile("{\n.reg .pred p;\n.reg .u32 c;\nmov.u32 c, 0;\n"
               "LW:\nmbarrier.try_wait.parity.acquire.cluster.shared::cta.b64 p, [%0], %1;\n@p bra LD;\n"
               "add.u32 c, c, 1;\nsetp.lt.u32 p, c, 1048576;\n@p bra LW;\ntrap;\nLD:\n}" ::"r"(bar), "r"(parity) : "memory");
}
#define SPIN_CHECK(it) if (++(it) > SPIN_LIMIT) __trap()
DEVINL void fence_async_smem() { asm volatile("fence.proxy.async.shared::cta;" ::: "memory"); }
DEVINL void fence_async_global() { asm volatile("fence.proxy.async.global;" ::: "memory"); }
template <int BIT> DEVINL void rel_fence() { if ((FK_REL >> BIT) & 1) asm volatile("fence.acq_rel.gpu;" ::: "memory"); }
DEVINL void fence_gpu() { asm volatile("fence.acq_rel.gpu;" ::: "memory"); }
template <int ID, int N> DEVINL void named_bar() { asm volatile("bar.sync %0, %1;" ::"n"(ID), "n"(N) : "memory"); }
DEVINL bool elect_one() { uint32_t p; asm volatile("{\n.reg .pred e;\nelect.sync _|e, 0xffffffff;\nselp.u32 %0, 1, 0, e;\n}" : "=r"(p)); return p; }
DEVINL unsigned clk32() { unsigned c; asm volatile("mov.u32 %0, %%clock;" : "=r"(c)); return c; }
#define FK_GRIDW 32
#define FK_GRID 0
DEVINL void grid_wait() {
  if (FK_GRID) {
    unsigned t0, t1;
    asm volatile("mov.u32 %0, %%globaltimer_lo;" : "=r"(t0));
    do { asm volatile("mov.u32 %0, %%globaltimer_lo;" : "=r"(t1)); } while (((t0 - FK_GRIDW) ^ t1) < FK_GRID + 0u + !FK_GRID);
  }
}
DEVINL void spin(unsigned n) { const unsigned c = clk32(); while (clk32() - c < n) {} }

constexpr uint64_t POL_NORMAL = 0x1000000000000000ull, POL_FIRST = 0x12F0000000000000ull;
#define FK_HINTS 0x11B
template <int BIT> DEVINL constexpr uint64_t pol() { return ((FK_HINTS >> BIT) & 1) ? POL_FIRST : POL_NORMAL; }
DEVINL void tma_2d(uint32_t dst, const CUtensorMap* m, int x, int y, uint32_t bar, uint64_t pol) {
  asm volatile("cp.async.bulk.tensor.2d.shared::cluster.global.mbarrier::complete_tx::bytes.L2::cache_hint [%0], [%1, {%3, %4}], [%2], %5;"
               ::"r"(dst), "l"(m), "r"(bar), "r"(x), "r"(y), "l"(pol) : "memory");
}
DEVINL void tma_3d(uint32_t dst, const CUtensorMap* m, int y, int z, uint32_t bar, uint64_t pol) {
  asm volatile("cp.async.bulk.tensor.3d.shared::cluster.global.mbarrier::complete_tx::bytes.L2::cache_hint [%0], [%1, {0, %3, %4}], [%2], %5;"
               ::"r"(dst), "l"(m), "r"(bar), "r"(y), "r"(z), "l"(pol) : "memory");
}
DEVINL void tma_3d_mc(uint32_t dst, const CUtensorMap* m, int y, int z, uint32_t bar, uint64_t pol) {
  asm volatile("cp.async.bulk.tensor.3d.shared::cluster.global.mbarrier::complete_tx::bytes.multicast::cluster.L2::cache_hint [%0], [%1, {0, %3, %4}], [%2], %5, %6;"
               ::"r"(dst), "l"(m), "r"(bar), "r"(y), "r"(z), "h"((unsigned short)3), "l"(pol) : "memory");
}
DEVINL void tma_2d_mc(uint32_t dst, const CUtensorMap* m, int x, int y, uint32_t bar, uint64_t pol) {
  asm volatile("cp.async.bulk.tensor.2d.shared::cluster.global.mbarrier::complete_tx::bytes.multicast::cluster.L2::cache_hint [%0], [%1, {%3, %4}], [%2], %5, %6;"
               ::"r"(dst), "l"(m), "r"(bar), "r"(x), "r"(y), "h"((unsigned short)3), "l"(pol) : "memory");
}
DEVINL void tma_store_2d(const CUtensorMap* m, uint32_t src, int x, int y) {
  asm volatile("cp.async.bulk.tensor.2d.global.shared::cta.bulk_group [%0, {%2, %3}], [%1];" ::"l"(m), "r"(src), "r"(x), "r"(y) : "memory");
}
DEVINL void bulk_store(void* dst, uint32_t src, uint32_t bytes) {
  asm volatile("cp.async.bulk.global.shared::cta.bulk_group [%0], [%1], %2;" ::"l"(dst), "r"(src), "r"(bytes) : "memory");
}
DEVINL void bulk_load(uint32_t dst, const void* src, uint32_t bytes, uint32_t bar, uint64_t pol) {
  asm volatile("cp.async.bulk.shared::cluster.global.mbarrier::complete_tx::bytes.L2::cache_hint [%0], [%1], %2, [%3], %4;" ::"r"(dst), "l"(src), "r"(bytes), "r"(bar), "l"(pol) : "memory");
}
template <int N> DEVINL void bulk_wait_read() { asm volatile("cp.async.bulk.wait_group.read %0;" ::"n"(N) : "memory"); }
DEVINL void pf_bulk(const void* p, uint32_t bytes) { asm volatile("cp.async.bulk.prefetch.L2.global [%0], %1;" ::"l"(p), "r"(bytes) : "memory"); }
DEVINL void bulk_commit() { asm volatile("cp.async.bulk.commit_group;" ::: "memory"); }
template <int N> DEVINL void bulk_wait() { asm volatile("cp.async.bulk.wait_group %0;" ::"n"(N) : "memory"); }
DEVINL void prefetch_tmap(const CUtensorMap* m) { asm volatile("prefetch.tensormap [%0];" ::"l"(m) : "memory"); }

DEVINL void wg_fence() { asm volatile("wgmma.fence.sync.aligned;" ::: "memory"); }
DEVINL void wg_commit() { asm volatile("wgmma.commit_group.sync.aligned;" ::: "memory"); }
template <int N> DEVINL void wg_wait() { asm volatile("wgmma.wait_group.sync.aligned %0;" ::"n"(N) : "memory"); }
DEVINL uint64_t make_desc(uint32_t addr, uint32_t lbo, uint32_t sbo, uint64_t sw = 1) {
  return (uint64_t)((addr & 0x3FFFF) >> 4) | ((uint64_t)(lbo >> 4) << 16) | ((uint64_t)(sbo >> 4) << 32) | (sw << 62);
}

#define R8(a, o) "+f"(a[o]), "+f"(a[o + 1]), "+f"(a[o + 2]), "+f"(a[o + 3]), "+f"(a[o + 4]), "+f"(a[o + 5]), "+f"(a[o + 6]), "+f"(a[o + 7])
#define R64(a, o) R8(a, o), R8(a, o + 8), R8(a, o + 16), R8(a, o + 24), R8(a, o + 32), R8(a, o + 40), R8(a, o + 48), R8(a, o + 56)
#define ACC64 "{%0, %1, %2, %3, %4, %5, %6, %7, %8, %9, %10, %11, %12, %13, %14, %15, "              \
              "%16, %17, %18, %19, %20, %21, %22, %23, %24, %25, %26, %27, %28, %29, %30, %31, "    \
              "%32, %33, %34, %35, %36, %37, %38, %39, %40, %41, %42, %43, %44, %45, %46, %47, "    \
              "%48, %49, %50, %51, %52, %53, %54, %55, %56, %57, %58, %59, %60, %61, %62, %63"
#define ACC128 ACC64 ", %64, %65, %66, %67, %68, %69, %70, %71, %72, %73, %74, %75, %76, %77, %78, %79, "      \
              "%80, %81, %82, %83, %84, %85, %86, %87, %88, %89, %90, %91, %92, %93, %94, %95, "               \
              "%96, %97, %98, %99, %100, %101, %102, %103, %104, %105, %106, %107, %108, %109, %110, %111, "   \
              "%112, %113, %114, %115, %116, %117, %118, %119, %120, %121, %122, %123, %124, %125, %126, %127"
template <int TB> DEVINL void wgmma_n256(float (&d)[128], uint64_t da, uint64_t db, int scale_d) {
  asm volatile("{\n.reg .pred p;\nsetp.ne.b32 p, %130, 0;\n"
               "wgmma.mma_async.sync.aligned.m64n256k16.f32.bf16.bf16 " ACC128 "}, %128, %129, p, 1, 1, 0, %131;\n}\n"
               : R64(d, 0), R64(d, 64) : "l"(da), "l"(db), "r"(scale_d), "n"(TB));
}
template <int TB> DEVINL void wgmma_n128(float (&d)[64], uint64_t da, uint64_t db) {
  asm volatile("wgmma.mma_async.sync.aligned.m64n128k16.f32.bf16.bf16 " ACC64 "}, %64, %65, 1, 1, 1, 0, %66;\n" : R64(d, 0) : "l"(da), "l"(db), "n"(TB));
}
template <int SC> DEVINL void wgmma_n128_rs(float (&d)[64], const uint32_t* a, uint64_t db) {
  asm volatile("{\n.reg .pred p;\nsetp.ne.b32 p, %69, 0;\n"
               "wgmma.mma_async.sync.aligned.m64n128k16.f32.bf16.bf16 " ACC64 "}, {%64, %65, %66, %67}, %68, p, 1, 1, 0;\n}\n"
               : R64(d, 0) : "r"(a[0]), "r"(a[1]), "r"(a[2]), "r"(a[3]), "l"(db), "n"(SC));
}
template <int N> DEVINL void reg_fence(float (&a)[N]) {
#pragma unroll
  for (int i = 0; i < N; i++) asm volatile("" : "+f"(a[i])::"memory");
}

DEVINL uint32_t pack_bf16(float lo, float hi) { uint32_t r; asm("cvt.rn.bf16x2.f32 %0, %1, %2;" : "=r"(r) : "f"(hi), "f"(lo)); return r; }
DEVINL uint32_t add_bf16x2(uint32_t a, uint32_t b) { uint32_t r; asm("add.rn.bf16x2 %0, %1, %2;" : "=r"(r) : "r"(a), "r"(b)); return r; }
DEVINL uint32_t mul_bf16x2(uint32_t a, uint32_t b) { uint32_t r; asm("mul.rn.bf16x2 %0, %1, %2;" : "=r"(r) : "r"(a), "r"(b)); return r; }
DEVINL uint32_t fma_bf16x2(uint32_t a, uint32_t b, uint32_t c) { uint32_t r; asm("fma.rn.bf16x2 %0, %1, %2, %3;" : "=r"(r) : "r"(a), "r"(b), "r"(c)); return r; }
DEVINL float bf_lo(uint32_t w) { return __uint_as_float(w << 16); }
DEVINL float bf_hi(uint32_t w) { return __uint_as_float(w & 0xFFFF0000u); }
DEVINL float round_bf16(float v) { return bf_lo(pack_bf16(v, 0.f)); }
DEVINL float sigmoid_f(float v) { float r; asm("rcp.approx.ftz.f32 %0, %1;" : "=f"(r) : "f"(1.f + __expf(-v))); return r; }
DEVINL float rsqrt_f(float v) { float r; asm("rsqrt.approx.ftz.f32 %0, %1;" : "=f"(r) : "f"(v)); return r; }
DEVINL float silu_f(float v) { return v * sigmoid_f(v); }
DEVINL void stsm_x4(uint32_t addr, const uint32_t* r) {
  asm volatile("stmatrix.sync.aligned.m8n8.x4.shared.b16 [%0], {%1, %2, %3, %4};" ::"r"(addr), "r"(r[0]), "r"(r[1]), "r"(r[2]), "r"(r[3]) : "memory");
}
DEVINL void ldsm_x4_t(uint32_t addr, uint32_t* r) {
  asm volatile("ldmatrix.sync.aligned.m8n8.x4.trans.shared.b16 {%0, %1, %2, %3}, [%4];" : "=r"(r[0]), "=r"(r[1]), "=r"(r[2]), "=r"(r[3]) : "r"(addr) : "memory");
}
DEVINL void mma_16816(float (&c)[4], const uint32_t* a, uint32_t b0, uint32_t b1) {
  asm("mma.sync.aligned.m16n8k16.row.col.f32.bf16.bf16.f32 {%0, %1, %2, %3}, {%4, %5, %6, %7}, {%8, %9}, {%0, %1, %2, %3};"
      : "+f"(c[0]), "+f"(c[1]), "+f"(c[2]), "+f"(c[3]) : "r"(a[0]), "r"(a[1]), "r"(a[2]), "r"(a[3]), "r"(b0), "r"(b1));
}
DEVINL void mma_1688(float (&c)[4], uint32_t a0, uint32_t a1, uint32_t b0) {
  asm("mma.sync.aligned.m16n8k8.row.col.f32.bf16.bf16.f32 {%0, %1, %2, %3}, {%4, %5}, {%6}, {%0, %1, %2, %3};"
      : "+f"(c[0]), "+f"(c[1]), "+f"(c[2]), "+f"(c[3]) : "r"(a0), "r"(a1), "r"(b0));
}
DEVINL float4 lds128(uint32_t a) { float4 v; asm volatile("ld.shared.v4.f32 {%0, %1, %2, %3}, [%4];" : "=f"(v.x), "=f"(v.y), "=f"(v.z), "=f"(v.w) : "r"(a)); return v; }
DEVINL uint4 lds128u(uint32_t a) { uint4 v; asm volatile("ld.shared.v4.u32 {%0, %1, %2, %3}, [%4];" : "=r"(v.x), "=r"(v.y), "=r"(v.z), "=r"(v.w) : "r"(a)); return v; }
DEVINL float2 lds64(uint32_t a) { float2 v; asm volatile("ld.shared.v2.f32 {%0, %1}, [%2];" : "=f"(v.x), "=f"(v.y) : "r"(a)); return v; }
DEVINL uint32_t lds32u(uint32_t a) { uint32_t v; asm volatile("ld.shared.u32 %0, [%1];" : "=r"(v) : "r"(a)); return v; }
DEVINL void sts128(uint32_t a, float x, float y, float z, float w) { asm volatile("st.shared.v4.f32 [%0], {%1, %2, %3, %4};" ::"r"(a), "f"(x), "f"(y), "f"(z), "f"(w) : "memory"); }
DEVINL void sts128u(uint32_t a, uint32_t x, uint32_t y, uint32_t z, uint32_t w) { asm volatile("st.shared.v4.u32 [%0], {%1, %2, %3, %4};" ::"r"(a), "r"(x), "r"(y), "r"(z), "r"(w) : "memory"); }
DEVINL void sts64u(uint32_t a, uint32_t x, uint32_t y) { asm volatile("st.shared.v2.u32 [%0], {%1, %2};" ::"r"(a), "r"(x), "r"(y) : "memory"); }
DEVINL void sts32v(uint32_t a, uint32_t v) { asm volatile("st.volatile.shared.u32 [%0], %1;" ::"r"(a), "r"(v) : "memory"); }
DEVINL void sts32(uint32_t a, float v) { asm volatile("st.shared.f32 [%0], %1;" ::"r"(a), "f"(v) : "memory"); }

DEVINL uint4 ld_msg(const void* p) {
  unsigned long long a, b;
  asm volatile("{\n.reg .b128 r;\nld.relaxed.gpu.global.b128 r, [%2];\nmov.b128 {%0, %1}, r;\n}" : "=l"(a), "=l"(b) : "l"(p) : "memory");
  return make_uint4((uint32_t)a, (uint32_t)(a >> 32), (uint32_t)b, (uint32_t)(b >> 32));
}
DEVINL void st_msg(void* p, uint32_t x, uint32_t y, uint32_t z, uint32_t w) {
  unsigned long long a = (unsigned long long)x | ((unsigned long long)y << 32), b = (unsigned long long)z | ((unsigned long long)w << 32);
  asm volatile("{\n.reg .b128 r;\nmov.b128 r, {%1, %2};\nst.relaxed.gpu.global.b128 [%0], r;\n}" ::"l"(p), "l"(a), "l"(b) : "memory");
}
DEVINL uint2 ld_msg8(const void* p) {
  unsigned long long a;
  asm volatile("ld.relaxed.gpu.global.b64 %0, [%1];" : "=l"(a) : "l"(p) : "memory");
  return make_uint2((uint32_t)a, (uint32_t)(a >> 32));
}
DEVINL void st_msg8(void* p, uint32_t x, uint32_t y) {
  asm volatile("st.relaxed.gpu.global.b64 [%0], %1;" ::"l"(p), "l"((unsigned long long)x | ((unsigned long long)y << 32)) : "memory");
}
DEVINL unsigned ld_rlx(const void* p) { unsigned v; asm volatile("ld.relaxed.gpu.global.u32 %0, [%1];" : "=r"(v) : "l"(p) : "memory"); return v; }
DEVINL void st_rlx(unsigned* p, unsigned v) { asm volatile("st.relaxed.gpu.global.u32 [%0], %1;" ::"l"(p), "r"(v) : "memory"); }
DEVINL void red_add(unsigned* p, unsigned v) { asm volatile("red.relaxed.gpu.global.add.u32 [%0], %1;" ::"l"(p), "r"(v) : "memory"); }
DEVINL uint4 ldg_nc(const void* p) {
  uint4 v;
  asm volatile("ld.global.nc.L1::no_allocate.v4.u32 {%0, %1, %2, %3}, [%4];" : "=r"(v.x), "=r"(v.y), "=r"(v.z), "=r"(v.w) : "l"(p));
  return v;
}
DEVINL float4 ldg_cg(const float* p) { float4 v; asm volatile("ld.global.cg.v4.f32 {%0, %1, %2, %3}, [%4];" : "=f"(v.x), "=f"(v.y), "=f"(v.z), "=f"(v.w) : "l"(p) : "memory"); return v; }
DEVINL void wait_cnt(const unsigned* p, unsigned target) {
  int it = 0;
  while ((int)(ld_rlx(p) - target) < 0) { SPIN_CHECK(it); __nanosleep(100); }
}

#define TRACE2(id)
#define TRACE(id)
#define TRACE_CLK(id)

#define STAMP(i)
DEVINL uint32_t fkey(float v) { const uint32_t u = __float_as_uint(v); return (u & 0x80000000u) ? ~u : (u | 0x80000000u); }
DEVINL float fkey_inv(uint32_t k) { return __uint_as_float((k & 0x80000000u) ? (k & 0x7FFFFFFFu) : ~k); }
DEVINL uint32_t redux_max(uint32_t v) { uint32_t r; asm volatile("redux.sync.max.u32 %0, %1, 0xffffffff;" : "=r"(r) : "r"(v)); return r; }
DEVINL void warp_top2(uint32_t key, uint32_t& k1, uint32_t& k2) { k1 = redux_max(key); k2 = redux_max(key == k1 ? 0u : key); }
DEVINL int key_row(uint32_t k) { return 2047 - (int)(k & 2047u); }
DEVINL int blk_src(int q, int cgrp) { const int f = q - 4, kk = (f * 37) >> 8, i = f - kk * 7; return f < 0 ? cgrp * 4 + q : (i + (i >= cgrp)) * 4 + kk; }
DEVINL uint32_t pstage(int kk) { return ((0xB4A4 >> (kk * 4)) & 15) * SLOT; }
DEVINL uint32_t buf_off(int u) { return ((0x42130 >> (u * 4)) & 15) * BUF; }
DEVINL int cnt_idx(int kb) { return kb < 4 ? (8 + kb) * 32 : (kb >> 2) * 32 + (kb & 3); }

__global__ void __launch_bounds__(384, 1) __cluster_dims__(2, 1, 1)
fused_kernel(const __nv_bfloat16* __restrict__ x, Scratch* const S, __nv_bfloat16* __restrict__ out, const __nv_bfloat16* __restrict__ cvec,
             const __nv_bfloat16* __restrict__ wd_re, const __nv_bfloat16* __restrict__ wd_im, const __grid_constant__ Params prm) {
  extern __shared__ __align__(1024) uint8_t smem_raw[];
  const uint32_t sb = smem_u32(smem_raw);
  const int tid = threadIdx.x, lane = tid & 31;
  const int warp = __shfl_sync(~0u, tid >> 5, 0);
  const int cl = blockIdx.x >> 1;
  const int rank = blockIdx.x & 1, c7 = ((cl - 36) * 37) >> 8;
  const int grp = cl < 4 ? 0 : cl < 36 ? (cl - 4) & 7 : cl - 35 - c7 * 7, gi = cl < 4 ? cl + 4 : cl < 36 ? (cl - 4) >> 3 : c7 + 4;
  const int j = gi >> 2, m4 = gi & 3, t = grp * 2 + rank;
  const int cgrp = m4 * 2 + j;
  const int b = t * 8 + cgrp;
  const bool moe = gi < 7;
  const int eb0 = j ? 64 + grp * 6 : grp * 8, eb = eb0 + m4 * 2 + rank;
  auto BAR = [&](int i) { return sb + BAR_OFF + i * 8; };

  uint4 xr[8];
  if ((warp & ~1) == 2) {
    const uint4* src = reinterpret_cast<const uint4*>(x + (size_t)(blockIdx.x * 2 + warp - 2) * D_) + lane;
#pragma unroll
    for (int i = 0; i < 4; i++) xr[i] = ldg_nc(src + 32 * i);
  }
  if (tid == 0) TRACE(0);
  if ((warp & ~1) != 2 && elect_one()) {
    const int w = warp < 2 ? warp : warp - 2;
#pragma unroll
    for (int k = 0; k < 5; k++) {
      const int i = w + 10 * k;
      if (i < B_NUM) mbar_init(BAR(i), (uint32_t)((i < 16 ? CNT0 : i < 32 ? CNT1 : CNT2) >> ((i & 15) * 4)) & 15u);
    }
    if (w == 9) sts32v(sb + RDY_OFF, 15);
    if (w < 4) mbar_expect_tx(BAR(B_FULL + w), STAGE);
    asm volatile("fence.mbarrier_init.release.cluster;" ::: "memory");
    if (w == 0) tma_2d(sb, &prm.ws[j], 0, t * 128, BAR(B_FULL), pol<0>());
    else prefetch_tmap(&prm.ws[1] + w);
  }
  if ((warp & ~1) != 2) { named_bar<4, 320>(); asm volatile("bar.arrive 3, 384;" ::: "memory"); }
  asm volatile("barrier.cluster.arrive.relaxed.aligned;" ::: "memory");

  if (warp < 4) {
    auto touch_piece = [&](int p) {
      if (p < 64 || moe) {
        const int y = p < 64 ? eb0 >> 2 : 0, z = p < 64 ? (p & 31) * 32 + (m4 * 2 + rank) * 4 : eb * 128 + (p - 64) * 4;
        if ((p >= FK_PHOME) != (p >= FK_PTOUCH)) asm volatile("cp.async.bulk.prefetch.tensor.3d.L2.global [%0, {0, %1, %2}];" ::"l"(&prm.tch[p >> 5]), "r"(y), "r"(z) : "memory");
        else {
          asm volatile("mbarrier.expect_tx.relaxed.cta.shared::cta.b64 [%0], 128;" ::"r"(BAR(B_TAB)) : "memory");
          tma_3d(sb + DUMMY_OFF, &prm.tch[p >> 5], y, z, BAR(B_TAB), POL_NORMAL);
        }
      }
    };
    if (warp == 0) {
      const unsigned* flagAddr = &S->cntN[cnt_idx(lane)];
      const unsigned tgt = (ld_rlx(S->epoch) + 1) * 64u;
      asm volatile("barrier.cluster.wait.acquire.aligned;" ::: "memory");
      unsigned ready = 0;
      if (lane >= 4) sts32v(sb + POLL_OFF + lane * 4, tgt - 1);
#pragma unroll 1
      for (int g = 0; g < 32; g++) {
        const int s = g & 3;
        const uint32_t sa = sb + s * STAGE, fb = BAR(B_FULL + s);
        if (!((ready >> g) & 1)) {
          unsigned v;
          asm volatile("ld.volatile.shared.u32 %0, [%1];" : "=r"(v) : "r"(sb + POLL_OFF + lane * 4) : "memory");
          ready |= __ballot_sync(~0u, v == tgt) & ~15u;
          int it = 0;
          while (!((ready >> g) & 1)) {
            ready |= __ballot_sync(~0u, (lane >> 2) == (g >> 2) && ld_rlx(flagAddr) == tgt);
            SPIN_CHECK(it);
          }
          fence_async_global();
        }
        if (g >= 4) {
          mbar_wait(BAR(B_EMPTY + s), ((g >> 2) - 1) & 1);
          if (lane < 8 && ((~ready >> (lane * 4)) & 15))
            asm volatile("cp.async.cg.shared.global [%0], [%1], 16;" ::"r"(sb + POLL_OFF + lane * 16), "l"(&S->cntN[lane * 32]) : "memory");
          if (elect_one()) { TRACE2(128 + g); mbar_expect_tx(fb, STAGE); tma_2d(sa, &prm.ws[j], g * 64, t * 128, fb, pol<0>()); }
        }
        if (g >= 4) grid_wait();
        if (elect_one()) {
          tma_3d_mc(sa + SLOT + rank * SLOT, &prm.n, g * 64, m4 * 4 + rank * 2, fb, pol<4>());
          if (g > 0 && g < 4) tma_2d(sa, &prm.ws[j], g * 64, t * 128, fb, pol<0>());
          TRACE2(64 + g);
        }
        if ((unsigned)(g - FK_WSPF) < 4u)
          asm volatile("prefetch.global.L2 [%0];" ::"l"(prm.wsp[j] + (size_t)(t * 128 + m4 * 32 + (g - FK_WSPF) * 8 + (lane >> 2)) * 4096 + 3584 + (lane & 3) * 128));
      }
      asm volatile("cp.async.wait_all;" ::: "memory");
    }
    asm volatile("" ::: "memory");
    if (warp == 1) {
      const uint32_t tag = ld_rlx(S->epoch) + 1;
      const uint32_t rb = sb + (m4 * 32 + lane) * 128 + ((lane & 7) << 4);
      float a0 = 0.f, a1 = 0.f, a2 = 0.f, a3 = 0.f;
#pragma unroll 1
      for (int g = 0; g < 32; g++) {
        const int s = g & 3;
        mbar_wait(BAR(B_FULL + s), (g >> 2) & 1);
        uint4 u[8];
#pragma unroll
        for (int c = 0; c < 8; c++) u[c] = lds128u((rb + s * STAGE) ^ (c << 4));
        u[7].x = __shfl_sync(~0u, u[7].x, lane);
        if (elect_one()) {
          mbar_arrive(BAR(B_EMPTY + s)); TRACE2(160 + g);
          if (g >= FK_G0) {
#pragma unroll 1
            for (int i = 0; i < FK_N1; i++) touch_piece(FK_P0 + (g - FK_G0) * FK_N1 + i);
          }
        }
#pragma unroll
        for (int c = 0; c < 8; c++) {
          a0 += bf_lo(u[c].x) + bf_lo(u[c].y); a1 += bf_hi(u[c].x) + bf_hi(u[c].y);
          a2 += bf_lo(u[c].z) + bf_lo(u[c].w); a3 += bf_hi(u[c].z) + bf_hi(u[c].w);
        }
      }
      if (lane == 0) mbar_arrive(BAR(B_RSDONE));
      mbar_wait(BAR(B_RSDONE), 0);
      st_msg8(&S->rs[j * S_ + t * 128 + m4 * 32 + lane], __float_as_uint((a0 + a1) + (a2 + a3)), tag);
    }
    asm volatile("" ::: "memory");
    if (warp >= 2) {
      const uint32_t ring = sb + SP_OFF + (warp - 2) * 16384, mf = BAR(B_MF + (warp - 2) * 4);
      const int jw = b >> 6, e0 = (b & 63) * 16;
      const __nv_bfloat16* src = (jw ? wd_im : wd_re) + (size_t)e0 * D_;
      int nc = 0;
#pragma unroll 1
      for (int G = 0; G < 8; G += (G == 0 && warp == 2) + 1) {
        if (G) { mbar_wait(mf + (nc & 3) * 8, (nc >> 2) & 1); nc++; }
        const uint32_t stg = ring + (nc & 3) * 4096, sl = stg + (G ? (lane >> 4) * 2048 + (lane & 15) * 16 : lane * 16), st = G ? 256 : 512;
        if (G) {
#pragma unroll
          for (int k = 0; k < 8; k++) xr[k] = lds128u(sl + k * 256);
        }
        float s0 = 0.f, s1 = 0.f, q0 = 0.f, q1 = 0.f, s2 = 0.f, s3 = 0.f, q2 = 0.f, q3 = 0.f;
        float v[64];
#pragma unroll
        for (int h = 0; h < 2; h++)
          if (h == 0 || G) {
#pragma unroll
            for (int k = 4 * h; k < 4 * h + 4; k++) {
              float* u = v + 8 * k;
              u[0] = bf_lo(xr[k].x); u[1] = bf_hi(xr[k].x); u[2] = bf_lo(xr[k].y); u[3] = bf_hi(xr[k].y);
              u[4] = bf_lo(xr[k].z); u[5] = bf_hi(xr[k].z); u[6] = bf_lo(xr[k].w); u[7] = bf_hi(xr[k].w);
#pragma unroll
              for (int i = 0; i < 8; i += 4) {
                s0 += u[i]; s1 += u[i + 1]; s2 += u[i + 2]; s3 += u[i + 3];
                q0 = fmaf(u[i], u[i], q0); q1 = fmaf(u[i + 1], u[i + 1], q1); q2 = fmaf(u[i + 2], u[i + 2], q2); q3 = fmaf(u[i + 3], u[i + 3], q3);
              }
            }
          }
        float sum = (s0 + s1) + (s2 + s3), sq = (q0 + q1) + (q2 + q3);
#pragma unroll
        for (int o = 1; o < 32; o <<= 1)
          if (o < 16 || !G) { sum += __shfl_xor_sync(~0u, sum, o); sq += __shfl_xor_sync(~0u, sq, o); }
        const float mean = sum * (1.f / D_);
        const float rstd = rsqrt_f(fmaxf(fmaf(-mean, mean, sq * (1.f / D_)), 0.f) + 1e-5f), nmr = -mean * rstd;
#pragma unroll
        for (int h = 0; h < 2; h++)
          if (h == 0 || G) {
#pragma unroll
            for (int k = 4 * h; k < 4 * h + 4; k++) {
              const float* u = v + 8 * k;
              sts128u(sl + k * st, pack_bf16(fmaf(u[0], rstd, nmr), fmaf(u[1], rstd, nmr)), pack_bf16(fmaf(u[2], rstd, nmr), fmaf(u[3], rstd, nmr)),
                      pack_bf16(fmaf(u[4], rstd, nmr), fmaf(u[5], rstd, nmr)), pack_bf16(fmaf(u[6], rstd, nmr), fmaf(u[7], rstd, nmr)));
            }
          }
        fence_async_smem();
        const int kq = blockIdx.x >> 5;
        if (elect_one()) {
          bulk_store(S->n + (size_t)(G * 256 + blockIdx.x * 2 + (G ? 0 : warp - 2)) * D_, stg, G ? 4096 : 2048); bulk_commit();
          if (G == 0) { bulk_wait<0>(); rel_fence<0>(); red_add(&S->cntN[cnt_idx(kq)], 1); TRACE(42 + warp); }
        }
        if (G == 0) named_bar<3, 384>();
        if (elect_one()) {
          if (G == 0 && warp == 2) mbar_wait(BAR(B_FULL), 0);
          if (G >= 4) { bulk_wait<1>(); red_add(&S->cntN[(G - 1) * 32 + kq], 2); }
#pragma unroll 1
          for (int k = G ? nc + 1 : 0; k < (warp == 2 ? nc + 2 : 1); k++) {
            mbar_expect_tx(mf + (k & 3) * 8, 4096);
            bulk_load(ring + ((k + 1) & 3) * 4096, k < 6 ? x + (size_t)((k + 4 - warp) * 256 + blockIdx.x * 2) * D_ : src + (k - 6) * 2 * D_, 4096, mf + (k & 3) * 8, k < 6 ? pol<7>() : pol<2>());
          }
          if (G == 1 || G == 2 || G == 7) { bulk_wait<0>(); rel_fence<1>(); red_add(&S->cntN[G * 32 + kq], 2); if (G > 1) TRACE(44 + (G & 3)); }
        }
        __syncwarp();
        if (warp == 3 && G) break;
      }
      const uint32_t tag = ld_rlx(S->epoch) + 1;
      float* const mod = S->mod[tag & 1];
      if (warp == 3) {
        const uint32_t stab = sb + TAB_OFF, stg = stab + 512;
        {
          const uint32_t cw = __ldg(reinterpret_cast<const uint32_t*>(cvec + t * 64) + lane);
          const uint32_t sp = pack_bf16(silu_f(bf_lo(cw)), silu_f(bf_hi(cw)));
          sts64u(stab + lane * 8, sp << 16, sp & 0xFFFF0000u);
        }
        float acc[8];
#pragma unroll
        for (int i = 0; i < 8; i++) acc[i] = 0.f;
#pragma unroll 1
        for (int n = -3; n < 24; n++) {
          if (n < 21 && elect_one()) {
            mbar_expect_tx(mf + (n & 3) * 8, 4096);
            tma_2d(ring + (n & 3) * 4096, &prm.wm, ((n + 3) >> 3) * 2048 + cgrp * 256, t * 64 + ((n + 3) & 7) * 8, mf + (n & 3) * 8, pol<1>());
          }
          if (n < 0) continue;
          const uint32_t sl = ring + ((n + 1) & 3) * 4096 + lane * 16;
          const float4 sv0 = lds128(stab + (n & 7) * 32), sv1 = lds128(stab + (n & 7) * 32 + 16);
          const float sc[8] = {sv0.x, sv0.y, sv0.z, sv0.w, sv1.x, sv1.y, sv1.z, sv1.w};
          mbar_wait(mf + ((n + 1) & 3) * 8, ((n + 1) >> 2) & 1);
          uint4 v[8];
#pragma unroll
          for (int u = 0; u < 8; u++) v[u] = lds128u(sl + u * 512);
#pragma unroll
          for (int u = 0; u < 8; u++) {
            acc[0] = fmaf(sc[u], bf_lo(v[u].x), acc[0]); acc[1] = fmaf(sc[u], bf_hi(v[u].x), acc[1]);
            acc[2] = fmaf(sc[u], bf_lo(v[u].y), acc[2]); acc[3] = fmaf(sc[u], bf_hi(v[u].y), acc[3]);
            acc[4] = fmaf(sc[u], bf_lo(v[u].z), acc[4]); acc[5] = fmaf(sc[u], bf_hi(v[u].z), acc[5]);
            acc[6] = fmaf(sc[u], bf_lo(v[u].w), acc[6]); acc[7] = fmaf(sc[u], bf_hi(v[u].w), acc[7]);
          }
          asm volatile("" : "+f"(acc[0]) :: "memory");
          if ((n & 7) == 7) {
            sts128(stg + lane * 32, acc[0], acc[1], acc[2], acc[3]); sts128(stg + lane * 32 + 16, acc[4], acc[5], acc[6], acc[7]);
#pragma unroll
            for (int i = 0; i < 8; i++) acc[i] = 0.f;
            fence_async_smem();
            if (elect_one()) {
              asm volatile("cp.reduce.async.bulk.global.shared::cta.bulk_group.add.f32 [%0], [%1], 1024;" ::"l"(mod + (n >> 3) * 2048 + cgrp * 256), "r"(stg) : "memory");
              bulk_commit();
              if (n != 15) { bulk_wait<0>(); rel_fence<2>(); red_add(&S->cntMod[n > 7 ? 32 : 0], 1); } else bulk_wait_read<0>();
              TRACE(n > 7 ? 34 + (n >> 3) : 9);
            }
          }
        }
      } else {
        wait_cnt(S->cntMod, tag * 128u);
        if (lane == 0) TRACE(10);
        float4 sa[8];
        {
          const float4 c0 = ldg_cg(mod + D_ + m4 * 256 + lane * 8), c1 = ldg_cg(mod + D_ + m4 * 256 + lane * 8 + 4);
#pragma unroll
          for (int i = 0; i < 8; i++) {
            const float4 sv = ldg_cg(mod + (i >> 1) * 256 + lane * 8 + (i & 1) * 4);
            const uint32_t s0 = pack_bf16(sv.x, sv.y), s1 = pack_bf16(sv.z, sv.w);
            sa[i] = make_float4(bf_lo(s0), bf_hi(s0), bf_lo(s1), bf_hi(s1));
          }
          const uint32_t cw[4] = {pack_bf16(c0.x, c0.y), pack_bf16(c0.z, c0.w), pack_bf16(c1.x, c1.y), pack_bf16(c1.z, c1.w)};
#pragma unroll
          for (int q = 0; q < 4; q++) sts32v(sb + T1_OFF + (lane >> 2) * 64 + q * 16 + (lane & 3) * 4, add_bf16x2(cw[q], 0x3F803F80u) ^ (j ? 0x80008000u : 0u));
        }
        float ul = 0.f;
#pragma unroll 1
        for (int r = 0; r < 8; r++) {
          if (r < 6 && elect_one()) {
            mbar_expect_tx(mf + ((nc + 2) & 3) * 8, 4096);
            bulk_load(ring + ((nc + 3) & 3) * 4096, src + (r + 2) * 2 * D_, 4096, mf + ((nc + 2) & 3) * 8, pol<2>());
          }
          mbar_wait(mf + (nc & 3) * 8, (nc >> 2) & 1); nc++;
          uint4 v[8];
          float u[4] = {0.f, 0.f, 0.f, 0.f};
#pragma unroll
          for (int i = 0; i < 8; i++) v[i] = lds128u(ring + (nc & 3) * 4096 + lane * 16 + i * 512);
#pragma unroll
          for (int i = 0; i < 8; i++) {
            const float4 s0 = sa[2 * (i & 3)], s1 = sa[2 * (i & 3) + 1];
            float &u0 = u[(i >> 2) * 2], &u1 = u[(i >> 2) * 2 + 1];
            u0 = fmaf(bf_lo(v[i].x), s0.x, u0); u1 = fmaf(bf_hi(v[i].x), s0.y, u1); u0 = fmaf(bf_lo(v[i].y), s0.z, u0); u1 = fmaf(bf_hi(v[i].y), s0.w, u1);
            u0 = fmaf(bf_lo(v[i].z), s1.x, u0); u1 = fmaf(bf_hi(v[i].z), s1.y, u1); u0 = fmaf(bf_lo(v[i].w), s1.z, u0); u1 = fmaf(bf_hi(v[i].w), s1.w, u1);
          }
          const float ua = u[0] + u[1], ub = u[2] + u[3];
          float us = ((lane & 1) ? ub : ua) + __shfl_xor_sync(~0u, (lane & 1) ? ua : ub, 1);
#pragma unroll
          for (int o = 16; o > 1; o >>= 1) us += __shfl_xor_sync(~0u, us, o);
          if ((lane >> 1) == r) ul = jw ? -us : us;
        }
        if (lane < 16) st_msg8(&S->u[jw * D_ + e0 + lane], __float_as_uint(ul), tag);
        if (lane == 0) TRACE(11);
#pragma unroll
        for (int i = 0; i < 4; i++) sts128u(ring + lane * 16 + i * 512, SENT, SENT, SENT, SENT);
        fence_async_smem();
        if (elect_one()) {
#pragma unroll 1
          for (int i = 0; i < 9; i++)
            bulk_store(i < 4 ? &S->part[b * 512 + i * 128] : i == 4 ? &S->stats[b * 128] : &S->rowsH[((i - 5) >> 1) * 4096 + (t * 2 + (i & 1)) * 128 + cgrp * 16], ring, i < 5 ? 2048 : 256);
          bulk_commit(); bulk_wait<0>(); rel_fence<4>();
          mbar_arrive(BAR(B_RSDONE)); TRACE(30);
        }
        if (lane < 12) reinterpret_cast<float4*>(S->mod[~tag & 1] + b * 48)[lane] = make_float4(0.f, 0.f, 0.f, 0.f);
      }
      named_bar<1, 64>();
    }
    asm volatile("setmaxnreg.dec.sync.aligned.u32 40;" ::: "memory");
    const uint32_t tag = ld_rlx(S->epoch) + 1;
    if (warp == 0) {
      unsigned ready = 15;
      int u = 0; uint32_t ph = 1;
#pragma unroll 1
      for (int q = 0; q < 32; q++) {
        const int sc = blk_src(q, cgrp), js = (sc >> 2) & 1, kc = (sc >> 3) * 256 + (sc & 3) * 64;
        const uint32_t sa = sb + buf_off(u), fb = BAR(B_FULL2 + u);
        if (!((ready >> q) & 1)) {
          int it = 0;
          do { asm volatile("ld.volatile.shared.u32 %0, [%1];" : "=r"(ready) : "r"(sb + RDY_OFF) : "memory"); SPIN_CHECK(it); } while (!((ready >> q) & 1));
          ready = __shfl_sync(~0u, ready, 0);
          fence_async_global();
        }
        if (q == 8) mbar_wait(BAR(B_PS + 1), 0);
        mbar_wait(BAR(q >= 5 ? B_EMPTY2 + u : q < 2 ? B_ADONE : q == 4 ? B_EMPTY + 3 : B_EMPTY + 1), q >= 2 ? ph : 0);
        if (elect_one()) {
          mbar_expect_tx(fb, q < 4 ? SLOT : BUF);
          tma_2d_mc(sa + SLOT + rank * 8192, &prm.wd[js], kc, cgrp * 128 + rank * 64, fb, pol<6>());
          if (q >= 4) tma_2d(sa, &prm.p, kc, js * S_ + t * 128, fb, pol<5>());
          if (q & 1) TRACE2(96 + (q >> 1));
        }
        if (++u == 5) { u = 0; ph ^= 1; }
      }
      if (elect_one()) {
        mbar_expect_tx(BAR(B_DN), moe ? 65536 : 0);
#pragma unroll 1
        for (int i = 0; i < 9; i++) {
          if ((i & 3) == 0) mbar_wait(BAR(B_EMPTY2 + 2 + (i >> 2)), 1);
          if (i == 0) mbar_arrive(BAR(B_B27));
          else if (moe)
            asm volatile("cp.async.bulk.tensor.5d.shared::cluster.global.mbarrier::complete_tx::bytes.L2::cache_hint [%0], [%1, {0, 0, 0, %3, %4}], [%2], %5;"
                         ::"r"(sb + RKA_OFF + (i + (i >> 3) * 4) * 8192), "l"(&prm.wdn), "r"(BAR(B_DN)), "r"(eb * 2), "r"(i * 2 - 2), "l"(pol<3>()) : "memory");
        }
      }
    }
    asm volatile("" ::: "memory");
    if (warp == 1) {
      if (elect_one()) {
#pragma unroll 1
        for (int kk = 0; kk < 4; kk++) {
          mbar_wait(BAR(B_PREADY + kk), 0);
          if (kk == 3 && FK_P3DELAY) spin(FK_P3DELAY);
          tma_store_2d(&prm.p, sb + pstage(kk), m4 * 256 + kk * 64, j * S_ + t * 128);
          bulk_commit(); bulk_wait<0>();
          if (!(kk & 1)) mbar_arrive(BAR(B_PS + (kk >> 1)));
          rel_fence<3>();
          st_rlx(&S->flagP[(b * 4 + kk) * 8], tag);
          TRACE(40 + kk);
        }
        prefetch_tmap(&prm.om);
        unsigned next = clk32();
#pragma unroll 1
        for (int n = 0; n < 16; n++) {
          const int r = n >> 2, i = n & 3;
          const uint32_t bar = BAR(B_EFULL - (r & 1)), dst = sb + ((r & 1) ? SP_OFF : E_OFF) + i * 8192;
          while ((int)(clk32() - next) < 0) __nanosleep(20);
          if (i == 0) { if (r) mbar_wait(BAR(B_TAKEN + r - 1), 0); mbar_expect_tx(bar, moe || r == 2 ? 32768 : 0); TRACE(60 + r); }
          if (r == 2) { tma_3d(dst, &prm.xm, t * 128 + i * 32, cgrp * 2, bar, pol<8>()); tma_3d(dst + 4096, &prm.xm, t * 128 + i * 32 + 16, cgrp * 2, bar, pol<8>()); }
          else if (moe) tma_2d(dst, r ? &prm.wu : &prm.wg, eb * 32, (r == 1 ? 0 : 512) + i * 128, bar, pol<3>());
          next = clk32() + FK_SPACE;
        }
      }
      __syncwarp();
      mbar_wait(BAR(B_PREADY), 1);
      const float2 bk = lds64(sb + DUMMY_OFF);
      const unsigned cmask = (1u << ((key_row(__float_as_uint(bk.x)) >> 4) & 7)) | (1u << ((key_row(__float_as_uint(bk.y)) >> 4) & 7));
      int r1 = -1, r2 = -1;
      unsigned next = clk32() + (m4 * 2 + rank) * (FK_OSPACE / 8);
#pragma unroll 1
      for (int i = 0; i < 16; i++) {
        if (i == 8) { mbar_wait(BAR(B_SEL), 0); const float2 sk = lds64(sb + SEL_OFF); r1 = key_row(__float_as_uint(sk.x)); r2 = key_row(__float_as_uint(sk.y)); }
        if (((cmask >> (i & 7)) & 1) != (i >> 3)) continue;
        while ((int)(clk32() - next) < 0) {}
        next += FK_OSPACE;
        const uint32_t slab = sb + E_OFF + (i & 7) * 4096;
        const int row = t * 128 + (i & 7) * 16;
        if ((r1 >> 4) != (row >> 4) && (r2 >> 4) != (row >> 4)) {
          if (elect_one()) asm volatile("cp.async.bulk.tensor.3d.global.shared::cta.bulk_group [%0, {0, %2, %3}], [%1];" ::"l"(&prm.om), "r"(slab), "r"(row), "r"(cgrp * 2) : "memory");
        } else {
#pragma unroll 1
          for (int r = lane >> 4; r < 16; r += 2) {
            const uint4 v = lds128u(slab + (lane & 8) * 256 + r * 128 + (((lane ^ r) & 7) << 4));
            if (row + r != r1 && row + r != r2) reinterpret_cast<uint4*>(out + (size_t)(row + r) * D_)[cgrp * 16 + (lane & 15)] = v;
          }
        }
      }
      if (elect_one()) { bulk_commit(); bulk_wait_read<0>(); TRACE(29); }
    }
    asm volatile("" ::: "memory");
    if (warp == 2) {
      unsigned ready = 15;
      if (elect_one()) {
        fence_async_smem();
        mbar_expect_tx(BAR(B_SPFULL), moe ? 32768 : 0);
        if (moe) {
#pragma unroll 1
          for (int i = 0; i < 4; i++) { tma_2d(sb + SP_OFF + i * 8192, &prm.wg, eb * 32, i * 128, BAR(B_SPFULL), pol<3>()); spin(500); }
        }
      }
      __syncwarp();
      const unsigned* flagAddr = &S->flagP[(t * 32 + blk_src(lane, cgrp)) * 8];
      mbar_wait(BAR(B_PREADY), 0);
      int it = 0;
      while (ready != ~0u) {
        ready |= __ballot_sync(~0u, !((ready >> lane) & 1) && lane < __ffs(~ready) + 8 && ld_rlx(flagAddr) == tag);
        if (lane == 0) sts32v(sb + RDY_OFF, ready);
        SPIN_CHECK(it);
      }
      wait_cnt(&S->cntMod[32], tag * 128u);
      mbar_wait(BAR(B_PREADY + 3), 0);
      {
        const float* mp = S->mod[tag & 1] + cgrp * 128 + lane * 4;
        const float4 ga = ldg_cg(mp + 2 * D_), sv = ldg_cg(mp + 3 * D_), cb = ldg_cg(mp + 4 * D_), gb = ldg_cg(mp + 5 * D_);
        const uint2 wr = __ldg(reinterpret_cast<const uint2*>(prm.w_r + cgrp * 128 + lane * 4));
        const uint32_t Aa = add_bf16x2(pack_bf16(cb.x, cb.y), 0x3F803F80u), Ab = add_bf16x2(pack_bf16(cb.z, cb.w), 0x3F803F80u);
        const uint32_t Sa = pack_bf16(sv.x, sv.y), Sb = pack_bf16(sv.z, sv.w), Ga = pack_bf16(gb.x, gb.y), Gb = pack_bf16(gb.z, gb.w);
        const float w0 = bf_lo(Aa) * bf_lo(wr.x), w1 = bf_hi(Aa) * bf_hi(wr.x), w2 = bf_lo(Ab) * bf_lo(wr.y), w3 = bf_hi(Ab) * bf_hi(wr.y);
        const uint32_t tb = sb + TAB_OFF + (lane >> 3) * 64 + (lane & 1) * 32 + ((lane >> 1) & 3) * 4, Wa = pack_bf16(w0, w1), Wb = pack_bf16(w2, w3);
        auto put = [&](int off, uint32_t a, uint32_t c) { sts32v(tb + off, a); sts32v(tb + off + 16, c); };
        put(T_WH, Wa, Wb); put(T_ONE, 0x3F803F80u, 0x3F803F80u);
        put(T_WL, pack_bf16(w0 - bf_lo(Wa), w1 - bf_hi(Wa)), pack_bf16(w2 - bf_lo(Wb), w3 - bf_hi(Wb)));
        put(T_GA, pack_bf16(ga.x, ga.y), pack_bf16(ga.z, ga.w)); put(T_A, Aa, Ab); put(T_S, Sa, Sb); put(T_G, Ga, Gb);
        float c1 = (w0 + w1) + (w2 + w3), c2 = (bf_lo(Sa) * bf_lo(wr.x) + bf_hi(Sa) * bf_hi(wr.x)) + (bf_lo(Sb) * bf_lo(wr.y) + bf_hi(Sb) * bf_hi(wr.y));
#pragma unroll 1
        for (int h = 0; h < 2; h++) {
#pragma unroll
          for (int o = 16; o; o >>= 1) { c1 += __shfl_xor_sync(~0u, c1, o); c2 += __shfl_xor_sync(~0u, c2, o); }
          if (h) break;
          if (t == 0 && lane == 0) st_msg(&S->cst[cgrp], __float_as_uint(c1), __float_as_uint(c2), tag, 0);
          uint4 cm; it = 0;
          while (true) {
            cm = ld_msg(&S->cst[lane & 7]);
            if (__all_sync(~0u, cm.z == tag)) break;
            SPIN_CHECK(it); __nanosleep(200);
          }
          c1 = 0.25f * __uint_as_float(cm.x); c2 = 0.25f * __uint_as_float(cm.y);
        }
        if (lane == 0) { sts128u(sb + CST_OFF, __float_as_uint(c1), __float_as_uint(c2), tag, 0); TRACE(27); }
      }
      uint32_t rk[16];
#pragma unroll
      for (int h = 0; h < 2; h++) {
        const uint2* src = (h ? &S->u[cgrp * 128] : &S->rs[t * 128]) + lane;
        uint2 m[8]; it = 0;
        while (true) {
          bool ok = true;
#pragma unroll
          for (int i = 0; i < 8; i++) { m[i] = ld_msg8(src + (i >> 1) * 32 + (i & 1) * (h ? D_ : S_)); ok &= m[i].y == tag; }
          if (ok) break;
          SPIN_CHECK(it);
        }
#pragma unroll
        for (int i = 0; i < 4; i++) {
          const float r0 = __uint_as_float(m[2 * i].x) * (h ? 0.5f : 1.f), r1 = __uint_as_float(m[2 * i + 1].x) * (h ? 0.5f : 1.f);
          const uint32_t hi = pack_bf16(r0, r1);
          rk[h * 8 + 2 * i] = hi; rk[h * 8 + 2 * i + 1] = pack_bf16(r0 - bf_lo(hi), r1 - bf_hi(hi));
        }
      }
      mbar_wait(BAR(B_B27), 0);
#pragma unroll
      for (int i = 0; i < 4; i++) {
        sts128u(sb + RKA_OFF + (i * 32 + lane) * 16, rk[2 * i], rk[2 * i], rk[2 * i + 1], 0);
        sts128u(sb + RKB_OFF + (i * 32 + lane) * 16, rk[8 + 2 * i], rk[9 + 2 * i], rk[8 + 2 * i], 0);
      }
      fence_async_smem();
      __syncwarp();
      if (lane == 0) { mbar_arrive(BAR(B_TAB)); TRACE(26); }
    }
    asm volatile("" ::: "memory");
    if (warp == 3) {
      if (elect_one()) {
        unsigned next = clk32();
#pragma unroll 1
        for (int p = FK_P0 + (32 - FK_G0) * FK_N1; p < FK_PEND; p++) {
          touch_piece(p);
          next += FK_PACE;
          while ((int)(clk32() - next) < 0) __nanosleep(20);
        }
        mbar_arrive(BAR(B_TAB)); TRACE(37);
      }
      __syncwarp();
      mbar_wait(BAR(B_B27), 0);
      mbar_wait(BAR(B_EMPTY2 + 4), 1);
      uint4 m; int it = 0;
      while (true) {
        m = ld_msg(&S->cand[(lane >> 1) * 8]);
        if (__all_sync(~0u, m.z == tag)) break;
        SPIN_CHECK(it);
      }
      uint32_t k1, k2;
      const uint32_t key = (lane & 1) ? m.y : m.x;
      warp_top2(key, k1, k2);
      if (lane == 0) { sts64u(sb + SEL_OFF, k1, k2); mbar_arrive(BAR(B_SEL)); TRACE(14); }
    }
  } else {
    const int cw = (warp - 4) >> 2;
    const int cwarp = warp - 4;
    const int gq = lane >> 2, q4 = lane & 3;
    const bool elect = (tid & 127) == 0;
    auto release = [&](int bar, bool both) { if ((tid & 126) == 0) arrive_peer(BAR(bar), both ? tid & 1 : rank); };
    asm volatile("barrier.cluster.wait.acquire.aligned;" ::: "memory");

    uint32_t wf[64], uf[64], df[64];
    const int kr = (lane & 7) + (lane >> 4) * 8;
    const uint32_t wo = cwarp * 4096 + kr * 64 + ((((lane >> 3) & 1) ^ ((kr >> 1) & 3)) << 4);
    auto take = [&](uint32_t base, uint32_t* dst) {
#pragma unroll
      for (int i = 0; i < 8; i++) ldsm_x4_t(base + (wo ^ ((i & 1) << 5)) + (i >> 1) * 1024, dst + i * 4);
    };
    auto take_part = [&](uint32_t base, uint32_t* dst, int part) {
#pragma unroll
      for (int i = 0; i < 4; i++)
        asm volatile("{\n.reg .pred p;\nsetp.eq.s32 p, %10, %11;\n"
                     "@p ldmatrix.sync.aligned.m8n8.x4.trans.shared.b16 {%0, %1, %2, %3}, [%8];\n"
                     "@p ldmatrix.sync.aligned.m8n8.x4.trans.shared.b16 {%4, %5, %6, %7}, [%9];\n}"
                     : "+r"(dst[8 * i]), "+r"(dst[8 * i + 1]), "+r"(dst[8 * i + 2]), "+r"(dst[8 * i + 3]), "+r"(dst[8 * i + 4]), "+r"(dst[8 * i + 5]), "+r"(dst[8 * i + 6]), "+r"(dst[8 * i + 7])
                     : "r"(base + wo + i * 1024), "r"(base + (wo ^ 32) + i * 1024), "r"(part), "r"(i) : "memory");
    };
    uint32_t xw[32];
    const uint32_t slab = sb + E_OFF + cwarp * 4096, xo = slab + (lane & 15) * 128 + (((lane >> 4) ^ (lane & 7)) << 4);
    auto take_x = [&](int part) {
#pragma unroll
      for (int i = 0; i < 4; i++)
        asm volatile("{\n.reg .pred p;\nsetp.eq.s32 p, %9, %10;\n"
                     "@p ldmatrix.sync.aligned.m8n8.x4.shared.b16 {%0, %1, %2, %3}, [%8];\n"
                     "@p ldmatrix.sync.aligned.m8n8.x4.shared.b16 {%4, %5, %6, %7}, [%8 + 2048];\n}"
                     : "+r"(xw[4 * i]), "+r"(xw[4 * i + 1]), "+r"(xw[4 * i + 2]), "+r"(xw[4 * i + 3]), "+r"(xw[4 * i + 16]), "+r"(xw[4 * i + 17]), "+r"(xw[4 * i + 18]), "+r"(xw[4 * i + 19])
                     : "r"(xo ^ (part << 5)), "r"(part), "r"(i) : "memory");
    };
    const int row0 = cwarp * 16 + gq;
    float lo[64];
    {
      float pa[64], pb[64];
      {
        float acc[128];
#pragma unroll 1
        for (int g = 0; g < 28; g++) {
          const int s = g & 3;
          mbar_wait(BAR(B_FULL + s), (g >> 2) & 1);
          const uint32_t sa = sb + s * STAGE;
          const uint64_t da = make_desc(sa + cw * 8192, 16, 1024), db = make_desc(sa + SLOT, 8192, 1024);
          wg_fence();
          wgmma_n256<1>(acc, da, db, g > 0);
#pragma unroll
          for (int k = 1; k < 4; k++) wgmma_n256<1>(acc, da + k * 2, db + k * 128, 1);
          wg_commit();
          wg_wait<1>();
          if (g > 0) { release(B_EMPTY + ((g - 1) & 3), true); if (elect) TRACE2(191 + g + cw * 32); }
        }
        wg_wait<0>();
        release(B_EMPTY + 3, true);
#pragma unroll
        for (int i = 0; i < 64; i++) {
          asm volatile("mov.b32 %0, %1;" : "=f"(pa[i]) : "f"(acc[i]));
          asm volatile("mov.b32 %0, %1;" : "=f"(pb[i]) : "f"(acc[64 + i]));
        }
      }
      if (elect) TRACE(3 + tr);
      const uint64_t da0 = make_desc(sb + cw * 8192, 16, 1024), db0 = make_desc(sb + SLOT, 8192, 1024);
#pragma unroll 1
      for (int s = 0; s < 4; s++) {
        mbar_wait(BAR(B_FULL + s), 1);
        wg_fence();
#pragma unroll
        for (int k = 0; k < 4; k++) wgmma_n128<1>(pa, da0 + s * (STAGE >> 4) + k * 2, db0 + s * (STAGE >> 4) + k * 128);
        wg_commit();
        if (s == 2) { wg_wait<1>(); if (elect) mbar_arrive(BAR(B_A29)); }
      }
      auto b_block = [&](int s) {
        wg_fence();
#pragma unroll
        for (int k = 0; k < 4; k++) wgmma_n128<1>(pb, da0 + s * (STAGE >> 4) + k * 2, db0 + s * (STAGE >> 4) + 1024 + k * 128);
        wg_commit();
      };
      uint32_t pk[64];
      const uint32_t so = sb + (uint32_t)(cwarp * 16 + (lane & 15)) * 128 + (((lane >> 4) ^ (lane & 7)) << 4);
      auto stage_p = [&](int kk, const float* a, int slotFree, int parity) {
        const uint4 t0 = lds128u(sb + T1_OFF + kk * 128 + q4 * 16), t1 = lds128u(sb + T1_OFF + kk * 128 + 64 + q4 * 16);
        const uint32_t A[8] = {t0.x, t0.y, t0.z, t0.w, t1.x, t1.y, t1.z, t1.w};
#pragma unroll
        for (int i = 0; i < 16; i++) pk[kk * 16 + i] = mul_bf16x2(pack_bf16(a[2 * i], a[2 * i + 1]), A[i >> 1]);
        if (slotFree >= 0) mbar_wait(BAR(slotFree), parity);
#pragma unroll
        for (int k = 0; k < 4; k++) stsm_x4((so ^ (k << 5)) + pstage(kk), pk + kk * 16 + k * 4);
      };
      auto p_ready = [&](int kk) { fence_async_smem(); if (elect_one()) mbar_arrive(BAR(B_PREADY + kk)); };
      auto own_block = [&](int q) {
        mbar_wait(BAR(B_FULL2 + q), 0);
        const uint64_t db = make_desc(sb + buf_off(q) + SLOT, 16, 1024);
        wg_fence();
        if (q == 0) wgmma_n128_rs<0>(lo, pk, db); else wgmma_n128_rs<1>(lo, pk + q * 16, db);
#pragma unroll
        for (int k = 1; k < 4; k++) wgmma_n128_rs<1>(lo, pk + q * 16 + k * 4, db + k * 2);
        wg_commit();
      };
      b_block(0);
      mbar_wait(BAR(B_RSDONE), 0);
      asm volatile("setmaxnreg.inc.sync.aligned.u32 232;" ::: "memory");
      wg_wait<1>();
      reg_fence(pa);
      release(B_ADONE, true);
      if (elect) TRACE(4 + tr);
      stage_p(0, pa, B_A29, 0); p_ready(0);
      if (elect) TRACE(2 + tr);
      b_block(1);
      stage_p(1, pa + 32, B_ADONE, 0);
      wg_wait<1>(); release(B_EMPTY, true);
      b_block(2);
      p_ready(1);
      wg_wait<1>(); release(B_EMPTY + 1, true);
      b_block(3);
      wg_wait<1>(); release(B_EMPTY + 2, true);
      own_block(0);
      wg_wait<1>(); release(B_EMPTY + 3, true);
      reg_fence(pb);
      if (elect) TRACE(1 + tr);
      own_block(1);
      stage_p(2, pb, B_PS, 0);
      wg_wait<1>(); release(B_EMPTY2, true);
      own_block(2);
      p_ready(2);
      stage_p(3, pb + 32, B_EMPTY + 3, 1);
      wg_wait<1>(); release(B_EMPTY2 + 1, true);
      own_block(3);
      p_ready(3);
      wg_wait<1>(); release(B_EMPTY2 + 2, true);
    }
    {
      int u = 4, up = 3; uint32_t ph = 0;
#pragma unroll 1
      for (int q = 4; q < 32; q++) {
        mbar_wait(BAR(B_FULL2 + u), ph);
        const uint32_t sa = sb + buf_off(u);
        const uint64_t da = make_desc(sa + cw * 8192, 16, 1024), db = make_desc(sa + SLOT, 16, 1024);
        wg_fence();
#pragma unroll
        for (int k = 0; k < 4; k++) wgmma_n128<0>(lo, da + k * 2, db + k * 2);
        wg_commit();
        wg_wait<1>();
        if (q < 31) release(B_EMPTY2 + up, q < 28);
        const int r = (q >= FK_Q1) + (q >= FK_Q2) + (q >= FK_Q3), part = q - ((FK_QA | FK_Q1 << 8 | FK_Q2 << 16 | FK_Q3 << 24) >> (r * 8) & 255);
        if ((unsigned)part < 5u) {
          if (part == 0) mbar_wait(BAR(B_SPFULL + (r & 1)), r >> 1);
          if (part == 4) { if (r < 3) { fence_async_smem(); if (elect_one()) mbar_arrive(BAR(B_TAKEN + r)); } }
          else if (q >= FK_Q2) { if (q >= FK_Q3) take_x(part); else take_part(sb + SP_OFF, uf, part); }
          else { if (q >= FK_Q1) take_part(sb + E_OFF, wf + 32, part); else take_part(sb + SP_OFF, wf, part); }
        }
        up = u;
        if (++u == 5) { u = 0; ph ^= 1; }
      }
    }
    mbar_wait(BAR(B_TAB), 0);
    wg_fence();
    wgmma_n128<0>(lo, make_desc(sb + RKA_OFF + cw * 1024, 0, 128, 0), make_desc(sb + RKB_OFF, 0, 128, 0));
    wg_commit();
    uint32_t tq = sb + TAB_OFF + q4 * 16, tb = tq + (gq & 1) * T_ONE + (gq & 2) * (T_WL / 2);
    const bool odd = q4 & 1;
    const uint4* src = &S->stats[(t * 8 + (q4 >> 1) * 4) * 128 + row0 + 8 * (q4 & 1)];
    uint4* sdst = &S->stats[b * 128 + row0 + 8 * q4];
    asm volatile("" : "+r"(tq), "+r"(tb), "+l"(src), "+l"(sdst));
    {
      uint4 gw[4];
#pragma unroll
      for (int a = 0; a < 4; a++) gw[a] = lds128u(tq + T_GA + a * 64);
      wg_wait<0>();
      reg_fence(lo);
      STAMP(0);
      if (elect) { TRACE(7 + tr); if (cw == 0) TRACE_CLK(121); }
      float c[2][4], e0[2][4], e1[2][4];
#pragma unroll
      for (int i = 0; i < 4; i++) c[0][i] = c[1][i] = e0[0][i] = e0[1][i] = e1[0][i] = e1[1][i] = 0.f;
#pragma unroll
      for (int a = 0; a < 4; a++) {
        const uint4 bw = lds128u(tb + a * 64);
        const uint32_t g[4] = {gw[a].x, gw[a].y, gw[a].z, gw[a].w};
#pragma unroll
        for (int i = 0; i < 8; i++) xw[a * 8 + i] = fma_bf16x2(g[i >> 1], pack_bf16(lo[a * 16 + 2 * i], lo[a * 16 + 2 * i + 1]), xw[a * 8 + i]);
#pragma unroll
        for (int h = 0; h < 2; h++) {
          const uint32_t* w = xw + a * 8 + h * 4;
          mma_1688(e0[0], w[0], w[1], w[0]); mma_1688(e1[0], w[0], w[1], w[1]); mma_1688(e0[1], w[2], w[3], w[2]); mma_1688(e1[1], w[2], w[3], w[3]);
          mma_16816(c[h], w, h ? bw.z : bw.x, h ? bw.w : bw.y);
        }
      }
      const float c0 = c[0][0] + c[1][0], c2 = c[0][2] + c[1][2];
      const float q0 = (gq & 1) ? e0[0][1] + e0[1][1] : e0[0][0] + e0[1][0], q1 = (gq & 1) ? e1[0][3] + e1[1][3] : e1[0][2] + e1[1][2];
      const int dl = (lane & ~3) | (gq >> 1);
      const float da = (odd ? c2 : c0) + __shfl_xor_sync(~0u, odd ? c0 : c2, 1), s1 = __shfl_xor_sync(~0u, c[0][3] + c[1][3], 1);
      const float qa = __shfl_sync(~0u, q0, dl), qb = __shfl_sync(~0u, q1, dl);
      if (q4 < 2) st_msg(sdst, __float_as_uint(odd ? s1 : c[0][1] + c[1][1]), __float_as_uint(odd ? qb : qa), __float_as_uint(da), 0);
    }
    if (elect) TRACE(8 + tr);
    STAMP(1);
    uint32_t rh[2], rl[2], nm[2];
    uint32_t bk1, bk2;
    uint4 tA[4], tS[4];
    {
      uint4 m[4];
      mbar_wait(BAR(B_SPFULL), 0);
#pragma unroll
      for (int i = 0; i < 4; i++) m[i] = ld_msg(src + 128 * i);
      const float4 cst = lds128(sb + CST_OFF);
      take(sb + SP_OFF, uf + 32);
#pragma unroll
      for (int a = 0; a < 4; a++) { tA[a] = lds128u(tq + T_A + a * 64); tS[a] = lds128u(tq + T_S + a * 64); }
      STAMP(2);
      int it = 0;
      while (!__all_sync(~0u, (m[0].w | m[1].w | m[2].w | m[3].w) == 0)) {
#pragma unroll
        for (int i = 0; i < 4; i++) m[i] = ld_msg(src + 128 * i);
        SPIN_CHECK(it);
      }
      STAMP(3);
      float sa = (__uint_as_float(m[0].x) + __uint_as_float(m[1].x)) + (__uint_as_float(m[2].x) + __uint_as_float(m[3].x));
      float qa = (__uint_as_float(m[0].y) + __uint_as_float(m[1].y)) + (__uint_as_float(m[2].y) + __uint_as_float(m[3].y));
      float da = (__uint_as_float(m[0].z) + __uint_as_float(m[1].z)) + (__uint_as_float(m[2].z) + __uint_as_float(m[3].z));
      sa += __shfl_xor_sync(~0u, sa, 2); qa += __shfl_xor_sync(~0u, qa, 2); da += __shfl_xor_sync(~0u, da, 2);
      const float mean = sa * (1.f / D_);
      const float rs = rsqrt_f(fmaxf(fmaf(-mean, mean, qa * (1.f / D_)), 0.f) + 1e-5f);
      const float r = fmaf(rs, fmaf(-mean, cst.x, da), cst.y);
      if (q4 < 2) sts32v(sb + KEY_OFF + (row0 + 8 * q4) * 4, (fkey(r) & ~2047u) | (uint32_t)(2047 - (t * 128 + row0 + 8 * q4)));
      if (tid == 128) TRACE(12 + 16);
      STAMP(4);
      named_bar<2, 256>();
      const uint4 k4 = lds128u(sb + KEY_OFF + lane * 16);
      const uint32_t ka = max(k4.x, k4.y), kb = max(k4.z, k4.w), m1 = max(ka, kb), m2 = max(min(ka, kb), ka > kb ? min(k4.x, k4.y) : min(k4.z, k4.w));
      bk1 = redux_max(m1); bk2 = redux_max(m1 == bk1 ? m2 : m1);
      if (tid == 128) { st_msg(&S->cand[t * 8], bk1, bk2, __float_as_uint(cst.z), 0); sts64u(sb + DUMMY_OFF, bk1, bk2); TRACE(13); }
      const uint32_t h = pack_bf16(rs, rs), ln = pack_bf16(rs - bf_lo(h), -mean * rs), hx = __shfl_xor_sync(~0u, h, 1), lx = __shfl_xor_sync(~0u, ln, 1);
      rh[0] = odd ? hx : h; rh[1] = odd ? h : hx;
      rl[0] = __byte_perm(odd ? lx : ln, 0, 0x1010); rl[1] = __byte_perm(odd ? ln : lx, 0, 0x1010);
      nm[0] = __byte_perm(odd ? lx : ln, 0, 0x3232); nm[1] = __byte_perm(odd ? ln : lx, 0, 0x3232);
      STAMP(5);
    }
    auto slab_row = [&](int r) { return lds128u(slab + (lane & 8) * 256 + r * 128 + (((lane ^ r) & 7) << 4)); };
    {
      const int lr1 = key_row(bk1) - t * 128, lr2 = key_row(bk2) - t * 128;
      uint4* cp[2]; bool cand[2];
#pragma unroll
      for (int r = 0; r < 2; r++) {
        const int lr = row0 + 8 * r;
        cand[r] = lr == lr1 || lr == lr2;
        cp[r] = &S->rowsH[(t * 2 + (lr == lr2)) * 128 + cgrp * 16 + q4];
      }
#pragma unroll
      for (int a = 0; a < 4; a++) {
        const uint4 tG = lds128u(tq + T_G + a * 64);
        const uint32_t A[4] = {tA[a].x, tA[a].y, tA[a].z, tA[a].w}, B[4] = {tS[a].x, tS[a].y, tS[a].z, tS[a].w}, G[4] = {tG.x, tG.y, tG.z, tG.w};
#pragma unroll
        for (int r = 0; r < 2; r++) {
          uint32_t h[4], *w = xw + a * 8 + r;
#pragma unroll
          for (int k = 0; k < 4; k++) h[k] = fma_bf16x2(fma_bf16x2(w[2 * k], rh[r], fma_bf16x2(w[2 * k], rl[r], nm[r])), A[k], B[k]);
          if (cand[r]) st_msg(cp[r] + a * 4, h[0], h[1], h[2], h[3]);
#pragma unroll
          for (int k = 0; k < 4; k++) w[2 * k] = fma_bf16x2(G[k], h[k], w[2 * k]);
        }
#pragma unroll
        for (int h = 0; h < 2; h++) stsm_x4((xo ^ ((((a & 1) * 2) + h) << 5)) + (a >> 1) * 2048, xw + a * 8 + h * 4);
      }
      const int lr = lane < 16 ? lr1 : lr2;
      __syncwarp();
      if ((lr >> 4) == cwarp) { const uint4 v = slab_row(lr & 15); st_msg(&S->rowsB[(t * 2 + (lane >> 4)) * 128 + cgrp * 16 + (lane & 15)], v.x, v.y, v.z, v.w); }
    }
    fence_async_smem();
    if (elect_one()) mbar_arrive(BAR(B_PREADY));
    STAMP(6);
    if (tid == 128) TRACE(15);
    STAMP(7);
    mbar_wait(BAR(B_SEL), 0);
    STAMP(8);
    const float2 selv = lds64(sb + SEL_OFF);
    const uint32_t key1 = __float_as_uint(selv.x), key2 = __float_as_uint(selv.y);
    const int t1 = key_row(key1) >> 7, t2 = key_row(key2) >> 7;
    const int slotA = t1 * 2, slotB = t2 * 2 + (t1 == t2 ? 1 : 0);
    const int fn = b & 1, fcol = (b >> 1) * 16 + q4 * 2 + ((lane >> 2) & 1) + (lane & 8);
    uint32_t fbase = SENT; float fgb = 0.f;
    const uint32_t* fbp = reinterpret_cast<const uint32_t*>(&S->rowsB[(fn ? slotB : slotA) * 128]) + (fcol >> 1);
    uint4 hb[4];
    src = &S->rowsH[((gq & 1) ? slotB : slotA) * 128 + cwarp * 8 + q4];
    if (moe) {
#pragma unroll
      for (int i = 0; i < 4; i++) hb[i] = ld_msg(src + (i >> 1) * 64 + (i & 1) * 4);
    }
    STAMP(9);
    mbar_wait(BAR(B_DN), 0);
    {
      const uint32_t db = sb + DN_OFF + (cwarp + (cwarp == 7) * 4) * 8192 + kr * 128 + ((((lane >> 3) & 1) ^ (lane & 7)) << 4);
#pragma unroll
      for (int i = 0; i < 16; i++) ldsm_x4_t((db ^ (((i >> 1) & 3) << 5)) + (i >> 3) * 4096 + (i & 1) * 2048, df + i * 4);
    }
    if (moe) {
      int it = 0;
      while (!__all_sync(~0u, hb[0].x != SENT && hb[1].x != SENT && hb[2].x != SENT && hb[3].x != SENT)) {
#pragma unroll
        for (int i = 0; i < 4; i++) hb[i] = ld_msg(src + (i >> 1) * 64 + (i & 1) * 4);
        SPIN_CHECK(it);
      }
      if (tid == 128) TRACE(16);
      STAMP(10);
      float c[4][4];
#pragma unroll
      for (int i = 0; i < 4; i++) c[i][0] = c[i][1] = c[i][2] = c[i][3] = 0.f;
#pragma unroll
      for (int ks = 0; ks < 8; ks++) {
        const uint32_t b0 = (ks & 1) ? hb[ks >> 1].z : hb[ks >> 1].x, b1 = (ks & 1) ? hb[ks >> 1].w : hb[ks >> 1].y;
        mma_16816(c[0], wf + ks * 8, b0, b1); mma_16816(c[1], wf + ks * 8 + 4, b0, b1);
        mma_16816(c[2], uf + ks * 8, b0, b1); mma_16816(c[3], uf + ks * 8 + 4, b0, b1);
      }
      {
        float v[4];
#pragma unroll
        for (int i = 0; i < 4; i++) v[i] = (q4 & 2) ? (odd ? c[3][i] : c[2][i]) : (odd ? c[1][i] : c[0][i]);
        sts128(sb + RED_OFF + cwarp * 512 + (q4 * 8 + (gq ^ (q4 * 2))) * 16, v[0], v[2], v[1], v[3]);
      }
    }
    STAMP(11);
    if (cwarp == 0) { fbase = ld_rlx(fbp); fgb = __uint_as_float(ld_rlx(S->mod[lds32u(sb + CST_OFF + 8) & 1] + 5 * D_ + fcol)); }
    if (moe) {
      named_bar<2, 256>();
      STAMP(12);
      float g0 = 0.f, g1 = 0.f, u0 = 0.f, u1 = 0.f;
#pragma unroll
      for (int w = 0; w < 8; w++) {
        const float2 gv = lds64(sb + RED_OFF + w * 512 + ((lane * 8) ^ ((lane & 16) * 2))), uv = lds64(sb + RED_OFF + w * 512 + 256 + ((lane * 8) ^ ((lane & 16) * 2) ^ 64));
        g0 += gv.x; g1 += gv.y; u0 += uv.x; u1 += uv.y;
      }
      const uint32_t gp = pack_bf16(g0, g1), up = pack_bf16(u0, u1), sp = pack_bf16(silu_f(bf_lo(gp)), silu_f(bf_hi(gp)));
      const uint32_t act = pack_bf16(bf_lo(sp) * bf_lo(up), bf_hi(sp) * bf_hi(up));
      uint32_t ab[4];
#pragma unroll
      for (int i = 0; i < 4; i++) ab[i] = __shfl_sync(~0u, act, i * 8 + q4 * 2 + (gq & 1));
      if (tid == 128) TRACE(31);
      STAMP(13);
#pragma unroll
      for (int T = 0; T < 2; T++) {
        float c[4][4];
#pragma unroll
        for (int i = 0; i < 4; i++) {
          c[i][0] = c[i][1] = c[i][2] = c[i][3] = 0.f;
          mma_16816(c[i], df + (T * 4 + i) * 8, ab[0], ab[1]); mma_16816(c[i], df + (T * 4 + i) * 8 + 4, ab[2], ab[3]);
        }
        float v[4];
#pragma unroll
        for (int i = 0; i < 4; i++) v[i] = (q4 & 2) ? (odd ? c[3][i] : c[2][i]) : (odd ? c[1][i] : c[0][i]);
        uint2* pp = reinterpret_cast<uint2*>(&S->part[((cwarp * 16 + T * 8 + q4 * 2) * 128 + eb) * 4]) + gq;
        st_msg8(pp, __float_as_uint(v[0]), __float_as_uint(v[2])); st_msg8(pp + 1024, __float_as_uint(v[1]), __float_as_uint(v[3]));
      }
      if (tid == 128) TRACE(32);
      STAMP(14);
    }
    if (cwarp == 0) {
      const uint32_t fk = fn ? key2 : key1;
      const float sg = round_bf16(sigmoid_f(round_bf16(fkey_inv((fk & ~2047u) | 1024u))));
      int it = 0;
      while (fbase == SENT) { fbase = ld_rlx(fbp); SPIN_CHECK(it); }
      spin(moe ? FK_PDELAY : FK_PDELAY + 1200);
      uint4 m[14];
      while (true) {
        bool ok = true;
#pragma unroll
        for (int i = 0; i < 14; i++) { m[i] = ld_msg(&S->part[b * 512 + i * 32 + lane]); ok &= m[i].x != SENT && m[i].z != SENT; }
        if (__all_sync(~0u, ok)) break;
        SPIN_CHECK(it);
      }
      if (lane == 0) TRACE(33);
      STAMP(15);
      float y[4] = {0.f, 0.f, 0.f, 0.f};
#pragma unroll
      for (int i = 0; i < 14; i++) { y[0] += __uint_as_float(m[i].x); y[1] += __uint_as_float(m[i].y); y[2] += __uint_as_float(m[i].z); y[3] += __uint_as_float(m[i].w); }
      const bool b2 = lane & 4;
      float y0 = (b2 ? y[2] : y[0]) + __shfl_xor_sync(~0u, b2 ? y[0] : y[2], 4), y1 = (b2 ? y[3] : y[1]) + __shfl_xor_sync(~0u, b2 ? y[1] : y[3], 4);
      y0 = ((lane & 8) ? y1 : y0) + __shfl_xor_sync(~0u, (lane & 8) ? y0 : y1, 8);
      y0 += __shfl_xor_sync(~0u, y0, 16);
      const float upd = round_bf16(round_bf16(y0) * sg);
      if (lane < 16) out[(size_t)key_row(fk) * D_ + fcol] = __float2bfloat16_rn(fmaf(round_bf16(fgb), upd, (fcol & 1) ? bf_hi(fbase) : bf_lo(fbase)));
      if (lane == 0) {
        TRACE(34); TRACE_CLK(122);
        if (b == 0) S->epoch[0] = lds32u(sb + CST_OFF + 8);
      }
    }
  }
}

typedef CUresult (*PFN_encodeTiled)(CUtensorMap*, CUtensorMapDataType, cuuint32_t, void*, const cuuint64_t*, const cuuint64_t*,
                                    const cuuint32_t*, const cuuint32_t*, CUtensorMapInterleave, CUtensorMapSwizzle,
                                    CUtensorMapL2promotion, CUtensorMapFloatOOBfill);

static void mapnd(PFN_encodeTiled enc, CUtensorMap* m, const void* p, int nd, const cuuint64_t* dims, const cuuint64_t* str, const cuuint32_t* box,
                  CUtensorMapSwizzle sw, CUtensorMapL2promotion pr) {
  const cuuint32_t es[5] = {1, 1, 1, 1, 1};
  enc(m, CU_TENSOR_MAP_DATA_TYPE_BFLOAT16, nd, (void*)p, dims, str, box, es, CU_TENSOR_MAP_INTERLEAVE_NONE, sw, pr, CU_TENSOR_MAP_FLOAT_OOB_FILL_NONE);
}
static void map2d(PFN_encodeTiled enc, CUtensorMap* m, const void* p, uint64_t rows, uint64_t cols, uint32_t brows, uint32_t bcols,
                  CUtensorMapSwizzle sw = CU_TENSOR_MAP_SWIZZLE_128B, CUtensorMapL2promotion pr = CU_TENSOR_MAP_L2_PROMOTION_L2_128B) {
  const cuuint64_t dims[2] = {cols, rows}, str[1] = {cols * 2}; const cuuint32_t box[2] = {bcols, brows};
  mapnd(enc, m, p, 2, dims, str, box, sw, pr);
}
static void map3d(PFN_encodeTiled enc, CUtensorMap* m, const void* p, uint64_t rows, uint64_t cols, uint32_t brows, uint32_t bgroups) {
  const cuuint64_t dims[3] = {64, rows, cols / 64}, str[2] = {cols * 2, 128}; const cuuint32_t box[3] = {64, brows, bgroups};
  mapnd(enc, m, p, 3, dims, str, box, CU_TENSOR_MAP_SWIZZLE_128B, CU_TENSOR_MAP_L2_PROMOTION_L2_128B);
}

}

extern "C" void kernel_launch(void* const* d_in, const int* in_sizes, int n_in, void* d_out, int out_size) {
  using namespace fk;
  (void)in_sizes; (void)n_in; (void)out_size;
  static PFN_encodeTiled enc = nullptr;
  static Scratch* scr = nullptr;
  if (!enc) {
    void* fn = nullptr; cudaDriverEntryPointQueryResult qr;
    cudaGetDriverEntryPoint("cuTensorMapEncodeTiled", &fn, cudaEnableDefault, &qr);
    enc = (PFN_encodeTiled)fn;
    cudaGetSymbolAddress((void**)&scr, g_scr);
    cudaFuncSetAttribute(fused_kernel, cudaFuncAttributeMaxDynamicSharedMemorySize, SMEM_BYTES);
  }
  typedef const __nv_bfloat16* bp;
  Params prm;
  prm.w_r = (bp)d_in[6];
  prm.wsp[0] = (const char*)d_in[1]; prm.wsp[1] = (const char*)d_in[2];
  map2d(enc, &prm.ws[0], d_in[1], S_, S_, 128, 64);
  map2d(enc, &prm.ws[1], d_in[2], S_, S_, 128, 64);
  map3d(enc, &prm.n, scr->n, S_, D_, 64, 2);
  map2d(enc, &prm.wm, d_in[11], D_, 6 * D_, 8, 256, CU_TENSOR_MAP_SWIZZLE_NONE, CU_TENSOR_MAP_L2_PROMOTION_L2_256B);
  map2d(enc, &prm.p, scr->P, 2 * S_, D_, 128, 64);
  map2d(enc, &prm.wd[0], d_in[3], D_, D_, 64, 64);
  map2d(enc, &prm.wd[1], d_in[4], D_, D_, 64, 64);
  map2d(enc, &prm.wg, d_in[7], D_, F_, 128, 32, CU_TENSOR_MAP_SWIZZLE_64B);
  map2d(enc, &prm.wu, d_in[8], D_, F_, 128, 32, CU_TENSOR_MAP_SWIZZLE_64B);
  for (int i = 0; i < 3; i++) {
    const cuuint64_t dims[3] = {128, i < 2 ? 28u : 2u, i < 2 ? 1024u : 14336u}, str[2] = {256, i < 2 ? 7168u : 512u}; const cuuint32_t box[3] = {8, 2, 4};
    mapnd(enc, &prm.tch[i], d_in[7 + i], 3, dims, str, box, CU_TENSOR_MAP_SWIZZLE_NONE, CU_TENSOR_MAP_L2_PROMOTION_L2_256B);
  }
  map3d(enc, &prm.xm, d_in[0], S_, D_, 16, 2);
  map3d(enc, &prm.om, d_out, S_, D_, 16, 2);
  {
    const cuuint64_t dims[5] = {64, 2, 8, 224, 16}, str[4] = {8 * 2048, 2048, 16 * 2048, 128}; const cuuint32_t box[5] = {64, 2, 8, 2, 2};
    mapnd(enc, &prm.wdn, d_in[9], 5, dims, str, box, CU_TENSOR_MAP_SWIZZLE_128B, CU_TENSOR_MAP_L2_PROMOTION_L2_128B);
  }

  fused_kernel<<<NCTA, 384, SMEM_BYTES, cudaStreamPerThread>>>((bp)d_in[0], scr, (__nv_bfloat16*)d_out, (bp)d_in[10], (bp)d_in[3], (bp)d_in[4], prm);
}
```

```cpp
#include <cuda_runtime.h>
#include <cuda_bf16.h>
#include <cuda.h>
#include <stdint.h>

#define DEVINL __device__ __forceinline__

namespace fk {

constexpr int S_ = 2048, D_ = 1024, F_ = 3584;
constexpr int NCTA = 128;
constexpr int SLOT = 16384;
constexpr int STAGE = 3 * SLOT;
constexpr int BUF = 2 * SLOT;
constexpr int E_OFF = 5 * BUF;
constexpr int SP_OFF = 4 * STAGE;
constexpr int MISC_OFF = SP_OFF + 32768;
constexpr int SMEM_BYTES = MISC_OFF + 3072;
constexpr int BAR_OFF = MISC_OFF;
constexpr int SEL_OFF = MISC_OFF + 352;
constexpr int BK_OFF = MISC_OFF + 360;
constexpr int CST_OFF = MISC_OFF + 368;
constexpr int PFLAG_OFF = MISC_OFF + 384;
constexpr int TAB_OFF = MISC_OFF + 512;
enum { T_WH = 0, T_ONE = 320, T_WL = 576, T_GA = 896, T_A = 1152, T_S = 1408, T_G = 1664 };
constexpr int KEY_OFF = TAB_OFF + 2048;
constexpr int POLL_OFF = TAB_OFF + 256;
constexpr int T1_OFF = TAB_OFF + 1536;
constexpr int RKA_OFF = BUF;
constexpr int RKB_OFF = RKA_OFF + 2048;
constexpr int RED_OFF = RKB_OFF + 2048;
constexpr int DN_OFF = RED_OFF + 4096;

enum { B_FULL = 0, B_EMPTY = 4, B_PREADY = 8, B_MF = 12  , B_FULL2 = 20  , B_EMPTY2 = 25  , B_A29 = 30, B_ADONE = 31,
       B_RSDONE = 32, B_TAB = 33, B_B27 = 34, B_SEL = 35, B_DN = 36, B_EFULL = 37, B_PS = 38  , B_WF = 40  , B_NUM = 44 };
constexpr unsigned long long CNT0 = 0x1111888855551111ull, CNT1 = 0x4244444222221111ull, CNT2 = 0x1111111111111112ull;

#define FK_REL 0x14
#define FK_WSPF 22
#define FK_SPACE 300
#define FK_OSPACE 100
#define FK_NOMC 4
#define FK_TR0 0
#define FK_G0 32
#define FK_NA 8
#define FK_PACE 800
#define FK_QP 7
#define FK_SG 0
#define FK_PSPACE 200
#define FK_PDELAY 700
constexpr int SPIN_LIMIT = 1 << 20;
constexpr uint32_t SENT = 0xFFFFFFFFu;

struct Scratch {
  uint4 part[128 * 128 * 4];
  uint4 stats[128 * 128];
  uint4 rowsH[32 * 128];
  uint4 rowsB[32 * 128];
  uint4 cand[16 * 8];
  uint2 rs[2 * S_];
  uint4 cst[8];
  float mod[2][6 * D_];
  uint2 u[2 * D_];
  unsigned flagP[128 * 4 * 8];
  unsigned cntN[12 * 32];
  unsigned cntMod[2 * 32];
  unsigned epoch[32];
  alignas(1024) __nv_bfloat16 n[S_ * D_];
  __nv_bfloat16 P[2 * S_ * D_];
};
__device__ __align__(1024) Scratch g_scr;

struct Params {
  CUtensorMap ws[2];
  CUtensorMap n;
  CUtensorMap wm;
  CUtensorMap p;
  CUtensorMap wg, wu;
  CUtensorMap xm;
  CUtensorMap wdn;
  CUtensorMap wd[2];
  CUtensorMap om;
  CUtensorMap ps;
  const __nv_bfloat16* w_r;
  const char* wsp[2];
  const char* we[3];
};

DEVINL uint32_t smem_u32(const void* p) { return (uint32_t)__cvta_generic_to_shared(p); }
DEVINL void mbar_init(uint32_t bar, uint32_t cnt) { asm volatile("mbarrier.init.shared::cta.b64 [%0], %1;" ::"r"(bar), "r"(cnt) : "memory"); }
DEVINL void mbar_expect_tx(uint32_t bar, uint32_t bytes) { asm volatile("mbarrier.arrive.expect_tx.shared::cta.b64 _, [%0], %1;" ::"r"(bar), "r"(bytes) : "memory"); }
DEVINL void mbar_arrive(uint32_t bar) { asm volatile("mbarrier.arrive.shared::cta.b64 _, [%0];" ::"r"(bar) : "memory"); }
DEVINL void mbar_wait(uint32_t bar, uint32_t parity) {
  asm volatile("{\n.reg .pred p;\n.reg .u32 c;\nmov.u32 c, 0;\n"
               "LW:\nmbarrier.try_wait.parity.shared::cta.b64 p, [%0], %1;\n@p bra LD;\n"
               "add.u32 c, c, 1;\nsetp.lt.u32 p, c, 1048576;\n@p bra LW;\ntrap;\nLD:\n}" ::"r"(bar), "r"(parity) : "memory");
}
DEVINL void mbar_wait_cluster(uint32_t bar, uint32_t parity) {
  asm volatile("{\n.reg .pred p;\n.reg .u32 c;\nmov.u32 c, 0;\n"
               "LW:\nmbarrier.try_wait.parity.acquire.cluster.shared::cta.b64 p, [%0], %1;\n@p bra LD;\n"
               "add.u32 c, c, 1;\nsetp.lt.u32 p, c, 1048576;\n@p bra LW;\ntrap;\nLD:\n}" ::"r"(bar), "r"(parity) : "memory");
}
#define SPIN_CHECK(it) if (++(it) > SPIN_LIMIT) __trap()
DEVINL void fence_async_smem() { asm volatile("fence.proxy.async.shared::cta;" ::: "memory"); }
DEVINL void fence_async_global() { asm volatile("fence.proxy.async.global;" ::: "memory"); }
template <int BIT> DEVINL void rel_fence() { if ((FK_REL >> BIT) & 1) asm volatile("fence.acq_rel.gpu;" ::: "memory"); }
DEVINL void fence_gpu() { asm volatile("fence.acq_rel.gpu;" ::: "memory"); }
template <int ID, int N> DEVINL void named_bar() { asm volatile("bar.sync %0, %1;" ::"n"(ID), "n"(N) : "memory"); }
DEVINL bool elect_one() { uint32_t p; asm volatile("{\n.reg .pred e;\nelect.sync _|e, 0xffffffff;\nselp.u32 %0, 1, 0, e;\n}" : "=r"(p)); return p; }
DEVINL unsigned clk32() { unsigned c; asm volatile("mov.u32 %0, %%clock;" : "=r"(c)); return c; }
#define FK_GRIDW 32
#define FK_GRID 0
DEVINL void grid_wait() {
  if (FK_GRID) {
    unsigned t0, t1;
    asm volatile("mov.u32 %0, %%globaltimer_lo;" : "=r"(t0));
    do { asm volatile("mov.u32 %0, %%globaltimer_lo;" : "=r"(t1)); } while (((t0 - FK_GRIDW) ^ t1) < FK_GRID + 0u + !FK_GRID);
  }
}
DEVINL void spin(unsigned n) { const unsigned c = clk32(); while (clk32() - c < n) {} }

constexpr uint64_t POL_NORMAL = 0x1000000000000000ull, POL_FIRST = 0x12F0000000000000ull;
#define FK_HINTS 0x11B
template <int BIT> DEVINL constexpr uint64_t pol() { return ((FK_HINTS >> BIT) & 1) ? POL_FIRST : POL_NORMAL; }
DEVINL void tma_2d(uint32_t dst, const CUtensorMap* m, int x, int y, uint32_t bar, uint64_t pol) {
  asm volatile("cp.async.bulk.tensor.2d.shared::cluster.global.mbarrier::complete_tx::bytes.L2::cache_hint [%0], [%1, {%3, %4}], [%2], %5;"
               ::"r"(dst), "l"(m), "r"(bar), "r"(x), "r"(y), "l"(pol) : "memory");
}
DEVINL void tma_3d(uint32_t dst, const CUtensorMap* m, int y, int z, uint32_t bar, uint64_t pol) {
  asm volatile("cp.async.bulk.tensor.3d.shared::cluster.global.mbarrier::complete_tx::bytes.L2::cache_hint [%0], [%1, {0, %3, %4}], [%2], %5;"
               ::"r"(dst), "l"(m), "r"(bar), "r"(y), "r"(z), "l"(pol) : "memory");
}
DEVINL void tma_3d_mc(uint32_t dst, const CUtensorMap* m, int y, int z, uint32_t bar, uint64_t pol) {
  asm volatile("cp.async.bulk.tensor.3d.shared::cluster.global.mbarrier::complete_tx::bytes.multicast::cluster.L2::cache_hint [%0], [%1, {0, %3, %4}], [%2], %5, %6;"
               ::"r"(dst), "l"(m), "r"(bar), "r"(y), "r"(z), "h"((unsigned short)3), "l"(pol) : "memory");
}
DEVINL void tma_2d_mc(uint32_t dst, const CUtensorMap* m, int x, int y, uint32_t bar, uint64_t pol) {
  asm volatile("cp.async.bulk.tensor.2d.shared::cluster.global.mbarrier::complete_tx::bytes.multicast::cluster.L2::cache_hint [%0], [%1, {%3, %4}], [%2], %5, %6;"
               ::"r"(dst), "l"(m), "r"(bar), "r"(x), "r"(y), "h"((unsigned short)3), "l"(pol) : "memory");
}
DEVINL void tma_store_2d(const CUtensorMap* m, uint32_t src, int x, int y) {
  asm volatile("cp.async.bulk.tensor.2d.global.shared::cta.bulk_group [%0, {%2, %3}], [%1];" ::"l"(m), "r"(src), "r"(x), "r"(y) : "memory");
}
DEVINL void bulk_store(void* dst, uint32_t src, uint32_t bytes) {
  asm volatile("cp.async.bulk.global.shared::cta.bulk_group [%0], [%1], %2;" ::"l"(dst), "r"(src), "r"(bytes) : "memory");
}
DEVINL void bulk_load(uint32_t dst, const void* src, uint32_t bytes, uint32_t bar, uint64_t pol) {
  asm volatile("cp.async.bulk.shared::cluster.global.mbarrier::complete_tx::bytes.L2::cache_hint [%0], [%1], %2, [%3], %4;" ::"r"(dst), "l"(src), "r"(bytes), "r"(bar), "l"(pol) : "memory");
}
template <int N> DEVINL void bulk_wait_read() { asm volatile("cp.async.bulk.wait_group.read %0;" ::"n"(N) : "memory"); }
DEVINL void pf_bulk(const void* p, uint32_t bytes) { asm volatile("cp.async.bulk.prefetch.L2.global [%0], %1;" ::"l"(p), "r"(bytes) : "memory"); }
DEVINL void bulk_commit() { asm volatile("cp.async.bulk.commit_group;" ::: "memory"); }
template <int N> DEVINL void bulk_wait() { asm volatile("cp.async.bulk.wait_group %0;" ::"n"(N) : "memory"); }
DEVINL void prefetch_tmap(const CUtensorMap* m) { asm volatile("prefetch.tensormap [%0];" ::"l"(m) : "memory"); }

DEVINL void wg_fence() { asm volatile("wgmma.fence.sync.aligned;" ::: "memory"); }
DEVINL void wg_commit() { asm volatile("wgmma.commit_group.sync.aligned;" ::: "memory"); }
template <int N> DEVINL void wg_wait() { asm volatile("wgmma.wait_group.sync.aligned %0;" ::"n"(N) : "memory"); }
DEVINL uint32_t desc_lo(uint32_t addr, uint32_t lbo) { return ((addr & 0x3FFFF) >> 4) | ((lbo >> 4) << 16); }

#define R8(a, o) "+f"(a[o]), "+f"(a[o + 1]), "+f"(a[o + 2]), "+f"(a[o + 3]), "+f"(a[o + 4]), "+f"(a[o + 5]), "+f"(a[o + 6]), "+f"(a[o + 7])
#define R64(a, o) R8(a, o), R8(a, o + 8), R8(a, o + 16), R8(a, o + 24), R8(a, o + 32), R8(a, o + 40), R8(a, o + 48), R8(a, o + 56)
#define ACC64 "{%0, %1, %2, %3, %4, %5, %6, %7, %8, %9, %10, %11, %12, %13, %14, %15, "              \
              "%16, %17, %18, %19, %20, %21, %22, %23, %24, %25, %26, %27, %28, %29, %30, %31, "    \
              "%32, %33, %34, %35, %36, %37, %38, %39, %40, %41, %42, %43, %44, %45, %46, %47, "    \
              "%48, %49, %50, %51, %52, %53, %54, %55, %56, %57, %58, %59, %60, %61, %62, %63"
#define ACC128 ACC64 ", %64, %65, %66, %67, %68, %69, %70, %71, %72, %73, %74, %75, %76, %77, %78, %79, "      \
              "%80, %81, %82, %83, %84, %85, %86, %87, %88, %89, %90, %91, %92, %93, %94, %95, "               \
              "%96, %97, %98, %99, %100, %101, %102, %103, %104, %105, %106, %107, %108, %109, %110, %111, "   \
              "%112, %113, %114, %115, %116, %117, %118, %119, %120, %121, %122, %123, %124, %125, %126, %127"
template <int TB> DEVINL void wgmma_n256(float (&d)[128], uint32_t da, uint32_t db, int scale_d) {
  asm volatile("{\n.reg .pred p;\n.reg .b64 a, b;\nsetp.ne.b32 p, %130, 0;\nmov.b64 a, {%128, 0x40000040};\nmov.b64 b, {%129, 0x40000040};\n"
               "wgmma.mma_async.sync.aligned.m64n256k16.f32.bf16.bf16 " ACC128 "}, a, b, p, 1, 1, 0, %131;\n}\n"
               : R64(d, 0), R64(d, 64) : "r"(da), "r"(db), "r"(scale_d), "n"(TB));
}
template <int TB, int HI = 0x40000040> DEVINL void wgmma_n128(float (&d)[64], uint32_t da, uint32_t db) {
  asm volatile("{\n.reg .b64 a, b;\nmov.b64 a, {%64, %67};\nmov.b64 b, {%65, %67};\n"
               "wgmma.mma_async.sync.aligned.m64n128k16.f32.bf16.bf16 " ACC64 "}, a, b, 1, 1, 1, 0, %66;\n}\n" : R64(d, 0) : "r"(da), "r"(db), "n"(TB), "n"(HI));
}
template <int SC> DEVINL void wgmma_n128_rs(float (&d)[64], const uint32_t* a, uint32_t db) {
  asm volatile("{\n.reg .pred p;\n.reg .b64 b;\nsetp.ne.b32 p, %69, 0;\nmov.b64 b, {%68, 0x40000040};\n"
               "wgmma.mma_async.sync.aligned.m64n128k16.f32.bf16.bf16 " ACC64 "}, {%64, %65, %66, %67}, b, p, 1, 1, 0;\n}\n"
               : R64(d, 0) : "r"(a[0]), "r"(a[1]), "r"(a[2]), "r"(a[3]), "r"(db), "n"(SC));
}
template <int N> DEVINL void reg_fence(float (&a)[N]) {
#pragma unroll
  for (int i = 0; i < N; i++) asm volatile("" : "+f"(a[i])::"memory");
}

DEVINL uint32_t pack_bf16(float lo, float hi) { uint32_t r; asm("cvt.rn.bf16x2.f32 %0, %1, %2;" : "=r"(r) : "f"(hi), "f"(lo)); return r; }
DEVINL uint32_t add_bf16x2(uint32_t a, uint32_t b) { uint32_t r; asm("add.rn.bf16x2 %0, %1, %2;" : "=r"(r) : "r"(a), "r"(b)); return r; }
DEVINL uint32_t mul_bf16x2(uint32_t a, uint32_t b) { uint32_t r; asm("mul.rn.bf16x2 %0, %1, %2;" : "=r"(r) : "r"(a), "r"(b)); return r; }
DEVINL uint32_t fma_bf16x2(uint32_t a, uint32_t b, uint32_t c) { uint32_t r; asm("fma.rn.bf16x2 %0, %1, %2, %3;" : "=r"(r) : "r"(a), "r"(b), "r"(c)); return r; }
DEVINL float bf_lo(uint32_t w) { return __uint_as_float(w << 16); }
DEVINL float bf_hi(uint32_t w) { return __uint_as_float(w & 0xFFFF0000u); }
DEVINL float round_bf16(float v) { return bf_lo(pack_bf16(v, 0.f)); }
DEVINL float sigmoid_f(float v) { float r; asm("rcp.approx.ftz.f32 %0, %1;" : "=f"(r) : "f"(1.f + __expf(-v))); return r; }
DEVINL float rsqrt_f(float v) { float r; asm("rsqrt.approx.ftz.f32 %0, %1;" : "=f"(r) : "f"(v)); return r; }
DEVINL float silu_f(float v) { return v * sigmoid_f(v); }
DEVINL void stsm_x4(uint32_t addr, const uint32_t* r) {
  asm volatile("stmatrix.sync.aligned.m8n8.x4.shared.b16 [%0], {%1, %2, %3, %4};" ::"r"(addr), "r"(r[0]), "r"(r[1]), "r"(r[2]), "r"(r[3]) : "memory");
}
DEVINL void ldsm_x4_t(uint32_t addr, uint32_t* r) {
  asm volatile("ldmatrix.sync.aligned.m8n8.x4.trans.shared.b16 {%0, %1, %2, %3}, [%4];" : "=r"(r[0]), "=r"(r[1]), "=r"(r[2]), "=r"(r[3]) : "r"(addr) : "memory");
}
DEVINL void mma_16816(float (&c)[4], const uint32_t* a, uint32_t b0, uint32_t b1) {
  asm("mma.sync.aligned.m16n8k16.row.col.f32.bf16.bf16.f32 {%0, %1, %2, %3}, {%4, %5, %6, %7}, {%8, %9}, {%0, %1, %2, %3};"
      : "+f"(c[0]), "+f"(c[1]), "+f"(c[2]), "+f"(c[3]) : "r"(a[0]), "r"(a[1]), "r"(a[2]), "r"(a[3]), "r"(b0), "r"(b1));
}
DEVINL void mma_1688(float (&c)[4], uint32_t a0, uint32_t a1, uint32_t b0) {
  asm("mma.sync.aligned.m16n8k8.row.col.f32.bf16.bf16.f32 {%0, %1, %2, %3}, {%4, %5}, {%6}, {%0, %1, %2, %3};"
      : "+f"(c[0]), "+f"(c[1]), "+f"(c[2]), "+f"(c[3]) : "r"(a0), "r"(a1), "r"(b0));
}
DEVINL float4 lds128(uint32_t a) { float4 v; asm volatile("ld.shared.v4.f32 {%0, %1, %2, %3}, [%4];" : "=f"(v.x), "=f"(v.y), "=f"(v.z), "=f"(v.w) : "r"(a)); return v; }
DEVINL uint4 lds128u(uint32_t a) { uint4 v; asm volatile("ld.shared.v4.u32 {%0, %1, %2, %3}, [%4];" : "=r"(v.x), "=r"(v.y), "=r"(v.z), "=r"(v.w) : "r"(a)); return v; }
DEVINL float2 lds64(uint32_t a) { float2 v; asm volatile("ld.shared.v2.f32 {%0, %1}, [%2];" : "=f"(v.x), "=f"(v.y) : "r"(a)); return v; }
DEVINL uint32_t lds32u(uint32_t a) { uint32_t v; asm volatile("ld.shared.u32 %0, [%1];" : "=r"(v) : "r"(a)); return v; }
DEVINL void sts128(uint32_t a, float x, float y, float z, float w) { asm volatile("st.shared.v4.f32 [%0], {%1, %2, %3, %4};" ::"r"(a), "f"(x), "f"(y), "f"(z), "f"(w) : "memory"); }
DEVINL void sts128u(uint32_t a, uint32_t x, uint32_t y, uint32_t z, uint32_t w) { asm volatile("st.shared.v4.u32 [%0], {%1, %2, %3, %4};" ::"r"(a), "r"(x), "r"(y), "r"(z), "r"(w) : "memory"); }
DEVINL void sts64u(uint32_t a, uint32_t x, uint32_t y) { asm volatile("st.shared.v2.u32 [%0], {%1, %2};" ::"r"(a), "r"(x), "r"(y) : "memory"); }
DEVINL void sts32v(uint32_t a, uint32_t v) { asm volatile("st.volatile.shared.u32 [%0], %1;" ::"r"(a), "r"(v) : "memory"); }
DEVINL void sts32(uint32_t a, float v) { asm volatile("st.shared.f32 [%0], %1;" ::"r"(a), "f"(v) : "memory"); }

DEVINL uint4 ld_msg(const void* p) {
  unsigned long long a, b;
  asm volatile("{\n.reg .b128 r;\nld.relaxed.gpu.global.b128 r, [%2];\nmov.b128 {%0, %1}, r;\n}" : "=l"(a), "=l"(b) : "l"(p) : "memory");
  return make_uint4((uint32_t)a, (uint32_t)(a >> 32), (uint32_t)b, (uint32_t)(b >> 32));
}
DEVINL void st_msg(void* p, uint32_t x, uint32_t y, uint32_t z, uint32_t w) {
  unsigned long long a = (unsigned long long)x | ((unsigned long long)y << 32), b = (unsigned long long)z | ((unsigned long long)w << 32);
  asm volatile("{\n.reg .b128 r;\nmov.b128 r, {%1, %2};\nst.relaxed.gpu.global.b128 [%0], r;\n}" ::"l"(p), "l"(a), "l"(b) : "memory");
}
DEVINL uint2 ld_msg8(const void* p) {
  unsigned long long a;
  asm volatile("ld.relaxed.gpu.global.b64 %0, [%1];" : "=l"(a) : "l"(p) : "memory");
  return make_uint2((uint32_t)a, (uint32_t)(a >> 32));
}
DEVINL void st_msg8(void* p, uint32_t x, uint32_t y) {
  asm volatile("st.relaxed.gpu.global.b64 [%0], %1;" ::"l"(p), "l"((unsigned long long)x | ((unsigned long long)y << 32)) : "memory");
}
DEVINL unsigned ld_rlx(const void* p) { unsigned v; asm volatile("ld.relaxed.gpu.global.u32 %0, [%1];" : "=r"(v) : "l"(p) : "memory"); return v; }
DEVINL void st_rlx(unsigned* p, unsigned v) { asm volatile("st.relaxed.gpu.global.u32 [%0], %1;" ::"l"(p), "r"(v) : "memory"); }
DEVINL void red_add(unsigned* p, unsigned v) { asm volatile("red.relaxed.gpu.global.add.u32 [%0], %1;" ::"l"(p), "r"(v) : "memory"); }
DEVINL uint4 ldg_nc(const void* p) {
  uint4 v;
  asm volatile("ld.global.nc.L1::no_allocate.v4.u32 {%0, %1, %2, %3}, [%4];" : "=r"(v.x), "=r"(v.y), "=r"(v.z), "=r"(v.w) : "l"(p));
  return v;
}
DEVINL float4 ldg_cg(const float* p) { float4 v; asm volatile("ld.global.cg.v4.f32 {%0, %1, %2, %3}, [%4];" : "=f"(v.x), "=f"(v.y), "=f"(v.z), "=f"(v.w) : "l"(p) : "memory"); return v; }
DEVINL void wait_cnt(const unsigned* p, unsigned target) {
  int it = 0;
  while ((int)(ld_rlx(p) - target) < 0) { SPIN_CHECK(it); __nanosleep(100); }
}

#define TRACE2(id)
#define TRACE3(id)
#define TRACE(id)
#define TRACE_CLK(id)

#define STAMP2(i)
#define STAMP(i)
DEVINL uint32_t fkey(float v) { const uint32_t u = __float_as_uint(v); return (u & 0x80000000u) ? ~u : (u | 0x80000000u); }
DEVINL float fkey_inv(uint32_t k) { return __uint_as_float((k & 0x80000000u) ? (k & 0x7FFFFFFFu) : ~k); }
DEVINL uint32_t redux_max(uint32_t v) { uint32_t r; asm volatile("redux.sync.max.u32 %0, %1, 0xffffffff;" : "=r"(r) : "r"(v)); return r; }
DEVINL void warp_top2(uint32_t key, uint32_t& k1, uint32_t& k2) { k1 = redux_max(key); k2 = redux_max(key == k1 ? 0u : key); }
DEVINL int key_row(uint32_t k) { return 2047 - (int)(k & 2047u); }
DEVINL int blk_src(int q, int cgrp) { const int f = q - 4, kk = (f * 37) >> 8, i = f - kk * 7; return f < 0 ? cgrp * 4 + q : (i + (i >= cgrp)) * 4 + kk; }
DEVINL uint32_t pstage(int kk) { return ((0xABA4 >> (kk * 4)) & 15) * SLOT; }
DEVINL uint32_t buf_off(int u) { return ((0x42130 >> (u * 4)) & 15) * BUF; }
DEVINL int cnt_idx(int kb) { return kb < 4 ? (8 + kb) * 32 : (kb >> 2) * 32 + (kb & 3); }

__global__ void __launch_bounds__(384, 1) __cluster_dims__(2, 1, 1)
fused_kernel(const __nv_bfloat16* __restrict__ x, Scratch* const S, __nv_bfloat16* __restrict__ out, const __nv_bfloat16* __restrict__ cvec,
             const __nv_bfloat16* __restrict__ wd_re, const __nv_bfloat16* __restrict__ wd_im, const __grid_constant__ Params prm) {
  extern __shared__ __align__(1024) uint8_t smem_raw[];
  const uint32_t sb = smem_u32(smem_raw);
  const int tid = threadIdx.x, lane = tid & 31;
  const int warp = __shfl_sync(~0u, tid >> 5, 0);
  const int cl = blockIdx.x >> 1;
  const int rank = blockIdx.x & 1, c7 = ((cl - 36) * 37) >> 8;
  const int grp = cl < 4 ? 0 : cl < 36 ? (cl - 4) & 7 : cl - 35 - c7 * 7, gi = cl < 4 ? cl + 4 : cl < 36 ? (cl - 4) >> 3 : c7 + 4;
  const int j = gi >> 2, m4 = gi & 3, t = grp * 2 + rank;
  const int cgrp = m4 * 2 + j;
  const int b = t * 8 + cgrp;
  const bool moe = gi < 7;
  const int eb0 = j ? 64 + grp * 6 : grp * 8, eb = eb0 + m4 * 2 + rank;
  auto BAR = [&](int i) { return sb + BAR_OFF + i * 8; };

  uint4 xr[8];
  if ((warp & ~1) == 2) {
    const uint4* src = reinterpret_cast<const uint4*>(x + (size_t)(blockIdx.x * 2 + warp - 2) * D_) + lane;
#pragma unroll
    for (int i = 0; i < 4; i++) xr[i] = ldg_nc(src + 32 * i);
  }
  if (tid == 0) TRACE(0);
  if ((warp & ~1) != 2 && elect_one()) {
    const int w = warp < 2 ? warp : warp - 2;
#pragma unroll
    for (int k = 0; k < 5; k++) {
      const int i = w + 10 * k;
      if (i < B_NUM) mbar_init(BAR(i), (uint32_t)((i < 16 ? CNT0 : i < 32 ? CNT1 : CNT2) >> ((i & 15) * 4)) & 15u);
    }
    if (w < 4) mbar_expect_tx(BAR(B_FULL + w), STAGE);
    asm volatile("fence.mbarrier_init.release.cluster;" ::: "memory");
    if (w == 0) tma_2d(sb, &prm.ws[j], 0, t * 128, BAR(B_FULL), pol<0>());
    else prefetch_tmap(&prm.ws[1] + w);
  }
  if ((warp & ~1) != 2) { named_bar<4, 320>(); asm volatile("bar.arrive 3, 384;" ::: "memory"); }
  asm volatile("barrier.cluster.arrive.relaxed.aligned;" ::: "memory");

  if (warp < 4) {
    auto prefetch_piece = [&](int p) { pf_bulk(prm.we[p >> 3] + (size_t)((p & 7) * 128 + b) * 7168, 7168); };
    auto weight_box = [&](int n) {
      mbar_expect_tx(BAR(B_WF + (n & 3)), moe ? 8192 : 0);
      if (moe) tma_2d(sb + SP_OFF + (n & 3) * 8192, &prm.wg + (n >> 3), eb * 32, (n & 7) * 128, BAR(B_WF + (n & 3)), pol<3>());
    };
    uint32_t tag = 0;
    if (warp == 0) {
      const unsigned* flagAddr = &S->cntN[cnt_idx(lane)];
      const unsigned tgt = (ld_rlx(S->epoch) + 1) * 64u;
      asm volatile("barrier.cluster.wait.acquire.aligned;" ::: "memory");
      unsigned ready = 0;
      if (lane >= 4) sts32v(sb + POLL_OFF + lane * 4, tgt - 1);
#pragma unroll 1
      for (int g = 0; g < 32; g++) {
        const int s = g & 3;
        const uint32_t sa = sb + s * STAGE, fb = BAR(B_FULL + s);
        if (!((ready >> g) & 1)) {
          unsigned v;
          asm volatile("ld.volatile.shared.u32 %0, [%1];" : "=r"(v) : "r"(sb + POLL_OFF + lane * 4) : "memory");
          ready |= __ballot_sync(~0u, v == tgt) & ~15u;
          int it = 0;
          while (!((ready >> g) & 1)) {
            ready |= __ballot_sync(~0u, (lane >> 2) == (g >> 2) && ld_rlx(flagAddr) == tgt);
            SPIN_CHECK(it);
          }
          fence_async_global();
        }
        if (g >= 4) {
          mbar_wait(BAR(B_EMPTY + s), ((g >> 2) - 1) & 1);
          if (lane < 8 && ((~ready >> (lane * 4)) & 15))
            asm volatile("cp.async.cg.shared.global [%0], [%1], 16;" ::"r"(sb + POLL_OFF + lane * 16), "l"(&S->cntN[lane * 32]) : "memory");
          if (elect_one()) { TRACE2(128 + g); mbar_expect_tx(fb, STAGE); tma_2d(sa, &prm.ws[j], g * 64, t * 128, fb, pol<0>()); }
        }
        if (g >= 4) grid_wait();
        if (elect_one()) {
          if (g < FK_NOMC) { tma_3d(sa + SLOT, &prm.n, g * 64, m4 * 4, fb, pol<4>()); tma_3d(sa + 2 * SLOT, &prm.n, g * 64, m4 * 4 + 2, fb, pol<4>()); }
          else tma_3d_mc(sa + SLOT + rank * SLOT, &prm.n, g * 64, m4 * 4 + rank * 2, fb, pol<4>());
          if (g > 0 && g < 4) tma_2d(sa, &prm.ws[j], g * 64, t * 128, fb, pol<0>());
          TRACE2(64 + g);
        }
        if ((unsigned)(g - FK_WSPF) < 4u)
          asm volatile("prefetch.global.L2 [%0];" ::"l"(prm.wsp[j] + (size_t)(t * 128 + m4 * 32 + (g - FK_WSPF) * 8 + (lane >> 2)) * 4096 + 3584 + (lane & 3) * 128));
      }
      asm volatile("cp.async.wait_all;" ::: "memory");
    }
    asm volatile("" ::: "memory");
    if (warp == 1) {
      tag = ld_rlx(S->epoch) + 1;
      if (elect_one()) prefetch_tmap(&prm.ps);
      const uint32_t rb = sb + (m4 * 32 + lane) * 128 + ((lane & 7) << 4);
      float a0 = 0.f, a1 = 0.f, a2 = 0.f, a3 = 0.f;
#pragma unroll 1
      for (int g = 0; g < 32; g++) {
        const int s = g & 3;
        mbar_wait(BAR(B_FULL + s), (g >> 2) & 1);
        uint4 u[8];
#pragma unroll
        for (int c = 0; c < 8; c++) u[c] = lds128u((rb + s * STAGE) ^ (c << 4));
        u[7].x = __shfl_sync(~0u, u[7].x, lane);
        if (elect_one()) {
          mbar_arrive(BAR(B_EMPTY + s)); TRACE2(160 + g);
          if (g >= FK_G0 && ((g - FK_G0) & 3) == 0) prefetch_piece((g - FK_G0) >> 2);
        }
#pragma unroll
        for (int c = 0; c < 8; c++) {
          a0 += bf_lo(u[c].x) + bf_lo(u[c].y); a1 += bf_hi(u[c].x) + bf_hi(u[c].y);
          a2 += bf_lo(u[c].z) + bf_lo(u[c].w); a3 += bf_hi(u[c].z) + bf_hi(u[c].w);
        }
      }
      if (lane == 0) mbar_arrive(BAR(B_RSDONE));
      mbar_wait(BAR(B_RSDONE), 0);
      st_msg8(&S->rs[j * S_ + t * 128 + m4 * 32 + lane], __float_as_uint((a0 + a1) + (a2 + a3)), tag);
    }
    asm volatile("" ::: "memory");
    if (warp >= 2) {
      const uint32_t ring = sb + SP_OFF + (warp - 2) * 16384, mf = BAR(B_MF + (warp - 2) * 4);
      const int jw = b >> 6, e0 = (b & 63) * 16;
      const __nv_bfloat16* src = (jw ? wd_im : wd_re) + (size_t)e0 * D_;
      int nc = 0;
#pragma unroll 1
      for (int G = 0; G < 8; G += (G == 0 && warp == 2) + 1) {
        if (G) { mbar_wait(mf + (nc & 3) * 8, (nc >> 2) & 1); nc++; }
        const uint32_t stg = ring + (nc & 3) * 4096, sl = stg + (G ? (lane >> 4) * 2048 + (lane & 15) * 16 : lane * 16), st = G ? 256 : 512;
        if (G) {
#pragma unroll
          for (int k = 0; k < 8; k++) xr[k] = lds128u(sl + k * 256);
        }
        float s0 = 0.f, s1 = 0.f, q0 = 0.f, q1 = 0.f, s2 = 0.f, s3 = 0.f, q2 = 0.f, q3 = 0.f;
        float v[64];
#pragma unroll
        for (int h = 0; h < 2; h++)
          if (h == 0 || G) {
#pragma unroll
            for (int k = 4 * h; k < 4 * h + 4; k++) {
              float* u = v + 8 * k;
              u[0] = bf_lo(xr[k].x); u[1] = bf_hi(xr[k].x); u[2] = bf_lo(xr[k].y); u[3] = bf_hi(xr[k].y);
              u[4] = bf_lo(xr[k].z); u[5] = bf_hi(xr[k].z); u[6] = bf_lo(xr[k].w); u[7] = bf_hi(xr[k].w);
#pragma unroll
              for (int i = 0; i < 8; i += 4) {
                s0 += u[i]; s1 += u[i + 1]; s2 += u[i + 2]; s3 += u[i + 3];
                q0 = fmaf(u[i], u[i], q0); q1 = fmaf(u[i + 1], u[i + 1], q1); q2 = fmaf(u[i + 2], u[i + 2], q2); q3 = fmaf(u[i + 3], u[i + 3], q3);
              }
            }
          }
        float sum = (s0 + s1) + (s2 + s3), sq = (q0 + q1) + (q2 + q3);
#pragma unroll
        for (int o = 1; o < 32; o <<= 1)
          if (o < 16 || !G) { sum += __shfl_xor_sync(~0u, sum, o); sq += __shfl_xor_sync(~0u, sq, o); }
        const float mean = sum * (1.f / D_);
        const float rstd = rsqrt_f(fmaxf(fmaf(-mean, mean, sq * (1.f / D_)), 0.f) + 1e-5f), nmr = -mean * rstd;
#pragma unroll
        for (int h = 0; h < 2; h++)
          if (h == 0 || G) {
#pragma unroll
            for (int k = 4 * h; k < 4 * h + 4; k++) {
              const float* u = v + 8 * k;
              sts128u(sl + k * st, pack_bf16(fmaf(u[0], rstd, nmr), fmaf(u[1], rstd, nmr)), pack_bf16(fmaf(u[2], rstd, nmr), fmaf(u[3], rstd, nmr)),
                      pack_bf16(fmaf(u[4], rstd, nmr), fmaf(u[5], rstd, nmr)), pack_bf16(fmaf(u[6], rstd, nmr), fmaf(u[7], rstd, nmr)));
            }
          }
        fence_async_smem();
        const int kq = blockIdx.x >> 5;
        if (elect_one()) {
          bulk_store(S->n + (size_t)(G * 256 + blockIdx.x * 2 + (G ? 0 : warp - 2)) * D_, stg, G ? 4096 : 2048); bulk_commit();
          if (G == 0) { bulk_wait<0>(); rel_fence<0>(); red_add(&S->cntN[cnt_idx(kq)], 1); TRACE(42 + warp); }
        }
        if (G == 0) named_bar<3, 384>();
        if (elect_one()) {
          if (G == 0 && warp == 2) mbar_wait(BAR(B_FULL), 0);
          if (G >= 4) { bulk_wait<1>(); red_add(&S->cntN[(G - 1) * 32 + kq], 2); }
#pragma unroll 1
          for (int k = G ? nc + 1 : 0; k < (warp == 2 ? nc + 2 : 1); k++) {
            mbar_expect_tx(mf + (k & 3) * 8, 4096);
            bulk_load(ring + ((k + 1) & 3) * 4096, k < 6 ? x + (size_t)((k + 4 - warp) * 256 + blockIdx.x * 2) * D_ : src + (k - 6) * 2 * D_, 4096, mf + (k & 3) * 8, k < 6 ? pol<7>() : pol<2>());
          }
          if (G == 1 || G == 2 || G == 7) { bulk_wait<0>(); rel_fence<1>(); red_add(&S->cntN[G * 32 + kq], 2); if (G > 1) TRACE(44 + (G & 3)); }
        }
        __syncwarp();
        if (warp == 3 && G) break;
      }
      tag = ld_rlx(S->epoch) + 1;
      float* const mod = S->mod[tag & 1];
      if (warp == 3) {
        const uint32_t stab = sb + TAB_OFF, stg = stab + 512;
        {
          const uint32_t cw = __ldg(reinterpret_cast<const uint32_t*>(cvec + t * 64) + lane);
          const uint32_t sp = pack_bf16(silu_f(bf_lo(cw)), silu_f(bf_hi(cw)));
          sts64u(stab + lane * 8, sp << 16, sp & 0xFFFF0000u);
        }
        float acc[8];
#pragma unroll
        for (int i = 0; i < 8; i++) acc[i] = 0.f;
#pragma unroll 1
        for (int n = -3; n < 24; n++) {
          if (n < 21 && elect_one()) {
            mbar_expect_tx(mf + (n & 3) * 8, 4096);
            tma_2d(ring + (n & 3) * 4096, &prm.wm, ((n + 3) >> 3) * 2048 + cgrp * 256, t * 64 + ((n + 3) & 7) * 8, mf + (n & 3) * 8, pol<1>());
          }
          if (n < 0) continue;
          const uint32_t sl = ring + ((n + 1) & 3) * 4096 + lane * 16;
          const float4 sv0 = lds128(stab + (n & 7) * 32), sv1 = lds128(stab + (n & 7) * 32 + 16);
          const float sc[8] = {sv0.x, sv0.y, sv0.z, sv0.w, sv1.x, sv1.y, sv1.z, sv1.w};
          mbar_wait(mf + ((n + 1) & 3) * 8, ((n + 1) >> 2) & 1);
          uint4 v[8];
#pragma unroll
          for (int u = 0; u < 8; u++) v[u] = lds128u(sl + u * 512);
#pragma unroll
          for (int u = 0; u < 8; u++) {
            acc[0] = fmaf(sc[u], bf_lo(v[u].x), acc[0]); acc[1] = fmaf(sc[u], bf_hi(v[u].x), acc[1]);
            acc[2] = fmaf(sc[u], bf_lo(v[u].y), acc[2]); acc[3] = fmaf(sc[u], bf_hi(v[u].y), acc[3]);
            acc[4] = fmaf(sc[u], bf_lo(v[u].z), acc[4]); acc[5] = fmaf(sc[u], bf_hi(v[u].z), acc[5]);
            acc[6] = fmaf(sc[u], bf_lo(v[u].w), acc[6]); acc[7] = fmaf(sc[u], bf_hi(v[u].w), acc[7]);
          }
          asm volatile("" : "+f"(acc[0]) :: "memory");
          if ((n & 7) == 7) {
            sts128(stg + lane * 32, acc[0], acc[1], acc[2], acc[3]); sts128(stg + lane * 32 + 16, acc[4], acc[5], acc[6], acc[7]);
#pragma unroll
            for (int i = 0; i < 8; i++) acc[i] = 0.f;
            fence_async_smem();
            if (elect_one()) {
              asm volatile("cp.reduce.async.bulk.global.shared::cta.bulk_group.add.f32 [%0], [%1], 1024;" ::"l"(mod + (n >> 3) * 2048 + cgrp * 256), "r"(stg) : "memory");
              bulk_commit();
              if (n != 15) { bulk_wait<0>(); rel_fence<2>(); red_add(&S->cntMod[n > 7 ? 32 : 0], 1); } else bulk_wait_read<0>();
              TRACE(n > 7 ? 34 + (n >> 3) : 9);
            }
          }
        }
      } else {
        wait_cnt(S->cntMod, tag * 128u);
        if (lane == 0) TRACE(10);
        float4 sa[8];
        {
          const float4 c0 = ldg_cg(mod + D_ + m4 * 256 + lane * 8), c1 = ldg_cg(mod + D_ + m4 * 256 + lane * 8 + 4);
#pragma unroll
          for (int i = 0; i < 8; i++) {
            const float4 sv = ldg_cg(mod + (i >> 1) * 256 + lane * 8 + (i & 1) * 4);
            const uint32_t s0 = pack_bf16(sv.x, sv.y), s1 = pack_bf16(sv.z, sv.w);
            sa[i] = make_float4(bf_lo(s0), bf_hi(s0), bf_lo(s1), bf_hi(s1));
          }
          const uint32_t cw[4] = {pack_bf16(c0.x, c0.y), pack_bf16(c0.z, c0.w), pack_bf16(c1.x, c1.y), pack_bf16(c1.z, c1.w)};
#pragma unroll
          for (int q = 0; q < 4; q++) sts32v(sb + T1_OFF + (lane >> 2) * 64 + q * 16 + (lane & 3) * 4, add_bf16x2(cw[q], 0x3F803F80u) ^ (j ? 0x80008000u : 0u));
        }
        float ul = 0.f;
#pragma unroll 1
        for (int r = 0; r < 8; r++) {
          if (r < 6 && elect_one()) {
            mbar_expect_tx(mf + ((nc + 2) & 3) * 8, 4096);
            bulk_load(ring + ((nc + 3) & 3) * 4096, src + (r + 2) * 2 * D_, 4096, mf + ((nc + 2) & 3) * 8, pol<2>());
          }
          mbar_wait(mf + (nc & 3) * 8, (nc >> 2) & 1); nc++;
          uint4 v[8];
          float u[4] = {0.f, 0.f, 0.f, 0.f};
#pragma unroll
          for (int i = 0; i < 8; i++) v[i] = lds128u(ring + (nc & 3) * 4096 + lane * 16 + i * 512);
#pragma unroll
          for (int i = 0; i < 8; i++) {
            const float4 s0 = sa[2 * (i & 3)], s1 = sa[2 * (i & 3) + 1];
            float &u0 = u[(i >> 2) * 2], &u1 = u[(i >> 2) * 2 + 1];
            u0 = fmaf(bf_lo(v[i].x), s0.x, u0); u1 = fmaf(bf_hi(v[i].x), s0.y, u1); u0 = fmaf(bf_lo(v[i].y), s0.z, u0); u1 = fmaf(bf_hi(v[i].y), s0.w, u1);
            u0 = fmaf(bf_lo(v[i].z), s1.x, u0); u1 = fmaf(bf_hi(v[i].z), s1.y, u1); u0 = fmaf(bf_lo(v[i].w), s1.z, u0); u1 = fmaf(bf_hi(v[i].w), s1.w, u1);
          }
          const float ua = u[0] + u[1], ub = u[2] + u[3];
          float us = ((lane & 1) ? ub : ua) + __shfl_xor_sync(~0u, (lane & 1) ? ua : ub, 1);
#pragma unroll
          for (int o = 16; o > 1; o >>= 1) us += __shfl_xor_sync(~0u, us, o);
          if ((lane >> 1) == r) ul = jw ? -us : us;
        }
        if (lane < 16) st_msg8(&S->u[jw * D_ + e0 + lane], __float_as_uint(ul), tag);
        if (lane == 0) TRACE(11);
#pragma unroll
        for (int i = 0; i < 4; i++) sts128u(ring + lane * 16 + i * 512, SENT, SENT, SENT, SENT);
        fence_async_smem();
        if (elect_one()) {
#pragma unroll 1
          for (int i = 0; i < 9; i++)
            bulk_store(i < 4 ? &S->part[b * 512 + i * 128] : i == 4 ? &S->stats[b * 128] : &S->rowsH[((i - 5) >> 1) * 4096 + (t * 2 + (i & 1)) * 128 + cgrp * 16], ring, i < 5 ? 2048 : 256);
          bulk_store(&S->flagP[b * 32], ring, 128);
          bulk_commit(); bulk_wait<0>(); rel_fence<4>();
          mbar_arrive(BAR(B_RSDONE)); TRACE(30);
        }
        if (lane < 12) reinterpret_cast<float4*>(S->mod[~tag & 1] + b * 48)[lane] = make_float4(0.f, 0.f, 0.f, 0.f);
      }
      named_bar<1, 64>();
    }
    asm volatile("setmaxnreg.dec.sync.aligned.u32 40;" ::: "memory");
    if (warp == 2) {
      const int scl = blk_src(lane, cgrp);
      const unsigned* flagAddr = &S->flagP[(t * 8 + (scl >> 2)) * 32 + (scl & 3)];
      const unsigned* cellAddr = &S->flagP[(t * 8 + (lane & 7)) * 32];
      sts32v(sb + PFLAG_OFF + lane * 4, tag - 1);
      if (lane < 4) mbar_arrive(BAR(B_FULL2 + lane));
      mbar_wait(BAR(B_PREADY), 0);
      unsigned ready = 15;
      int u = 4, src = cgrp == 0, kk = 0; uint32_t ph = 1;
#pragma unroll 1
      for (int q = 4; q < 32; q++) {
        if (!((ready >> q) & 1)) {
          unsigned v;
          asm volatile("ld.volatile.shared.u32 %0, [%1];" : "=r"(v) : "r"(sb + PFLAG_OFF + scl * 4) : "memory");
          ready |= __ballot_sync(~0u, v == tag);
          int it = 0;
          while (!((ready >> q) & 1)) {
            ready |= __ballot_sync(~0u, (unsigned)(lane - q) < 7u && ld_rlx(flagAddr) == tag);
            SPIN_CHECK(it);
          }
          fence_async_global();
        }
        if (q == 8) mbar_wait(BAR(B_PS), 0);
        mbar_wait(BAR(q >= 8 ? B_EMPTY2 + u : q == 4 ? B_EMPTY + 2 : B_FULL2 + u), ph);
        if (elect_one()) {
          TRACE3(128 + q);
          mbar_expect_tx(BAR(B_FULL2 + u), SLOT);
          tma_2d(sb + buf_off(u), &prm.p, (src >> 1) * 256 + kk * 64, (src & 1) * S_ + t * 128, BAR(B_FULL2 + u), pol<5>());
        }
        if (((~ready >> q) & 15) && lane < 8)
          asm volatile("cp.async.cg.shared.global [%0], [%1], 16;" ::"r"(sb + PFLAG_OFF + lane * 16), "l"(cellAddr) : "memory");
        if (++u == 5) { u = 0; ph ^= 1; }
        src += 1 + (src + 1 == cgrp);
        if (src >= 8) { src = cgrp == 0; kk++; }
      }
      asm volatile("cp.async.wait_all;" ::: "memory");
    }
    asm volatile("" ::: "memory");
    if (warp == 0) {
      int u = 0; uint32_t ph = 1;
#pragma unroll 1
      for (int q = 0; q < 32; q++) {
        const int sc = blk_src(q, cgrp);
        mbar_wait(BAR(q >= 5 ? B_EMPTY2 + u : q < 2 ? B_ADONE : q == 4 ? B_EMPTY + 3 : B_EMPTY + 1), q >= 2 ? ph : 0);
        if (elect_one()) {
          TRACE3(160 + q);
          mbar_expect_tx(BAR(B_FULL2 + u), SLOT);
          tma_2d_mc(sb + buf_off(u) + SLOT + rank * 8192, &prm.wd[(sc >> 2) & 1], (sc >> 3) * 256 + (sc & 3) * 64, cgrp * 128 + rank * 64, BAR(B_FULL2 + u), pol<6>());
          if (q & 1) { const int p = 4 + FK_NA + ((q - FK_QP) >> 1); if (q >= FK_QP && p < 24) prefetch_piece(p); }
          else if (q >= 10) weight_box((q >> 1) - 1);
        }
        if (++u == 5) { u = 0; ph ^= 1; }
      }
      if (elect_one()) {
        mbar_expect_tx(BAR(B_DN), moe ? 65536 : 0);
#pragma unroll 1
        for (int i = 0; i < 9; i++) {
          if ((i & 3) == 0) mbar_wait(BAR(B_EMPTY2 + 2 + (i >> 2)), 1);
          if (i == 0) { mbar_arrive(BAR(B_B27)); weight_box(15); }
          else if (moe)
            asm volatile("cp.async.bulk.tensor.5d.shared::cluster.global.mbarrier::complete_tx::bytes.L2::cache_hint [%0], [%1, {0, 0, 0, %3, %4}], [%2], %5;"
                         ::"r"(sb + RKA_OFF + (i + (i >> 3) * 4) * 8192), "l"(&prm.wdn), "r"(BAR(B_DN)), "r"(eb * 2), "r"(i * 2 - 2), "l"(pol<3>()) : "memory");
        }
      }
    }
    asm volatile("" ::: "memory");
    if (warp == 1) {
      if (elect_one()) {
#pragma unroll 1
        for (int kk = 0; kk < 4; kk++) {
          mbar_wait(BAR(B_PREADY + kk), 0);
#pragma unroll 1
          for (int i = 0; i < 4; i++) {
            tma_store_2d(&prm.ps, sb + pstage(kk) + i * 4096, m4 * 256 + kk * 64, j * S_ + t * 128 + i * 32);
            if (kk && i < 3) { const unsigned next = clk32() + FK_PSPACE; while ((int)(clk32() - next) < 0) __nanosleep(20); }
          }
          bulk_commit(); bulk_wait<0>();
          if (kk < 2) mbar_arrive(BAR(B_PS + kk));
          rel_fence<3>();
          st_rlx(&S->flagP[b * 32 + kk], tag);
          TRACE(40 + kk); TRACE3(128 + kk);
        }
        prefetch_tmap(&prm.om);
        mbar_expect_tx(BAR(B_EFULL), 32768);
#pragma unroll 1
        for (int i = 0; i < 8; i++) {
          tma_3d(sb + E_OFF + i * 4096, &prm.xm, t * 128 + i * 16, cgrp * 2, BAR(B_EFULL), pol<8>());
          const unsigned next = clk32() + FK_SPACE;
          while ((int)(clk32() - next) < 0) __nanosleep(20);
        }
      }
      __syncwarp();
      mbar_wait(BAR(B_PREADY), 1);
      const float2 bk = lds64(sb + BK_OFF);
      const unsigned cmask = (1u << ((key_row(__float_as_uint(bk.x)) >> 4) & 7)) | (1u << ((key_row(__float_as_uint(bk.y)) >> 4) & 7));
      int r1 = -1, r2 = -1;
      unsigned next = clk32() + (m4 * 2 + rank) * (FK_OSPACE / 8);
#pragma unroll 1
      for (int i = 0; i < 16; i++) {
        if (i == 8) { mbar_wait(BAR(B_SEL), 0); const float2 sk = lds64(sb + SEL_OFF); r1 = key_row(__float_as_uint(sk.x)); r2 = key_row(__float_as_uint(sk.y)); }
        if (((cmask >> (i & 7)) & 1) != (i >> 3)) continue;
        while ((int)(clk32() - next) < 0) {}
        next += FK_OSPACE;
        const uint32_t slab = sb + E_OFF + (i & 7) * 4096;
        const int row = t * 128 + (i & 7) * 16;
        if ((r1 >> 4) != (row >> 4) && (r2 >> 4) != (row >> 4)) {
          if (elect_one()) asm volatile("cp.async.bulk.tensor.3d.global.shared::cta.bulk_group [%0, {0, %2, %3}], [%1];" ::"l"(&prm.om), "r"(slab), "r"(row), "r"(cgrp * 2) : "memory");
        } else {
#pragma unroll 1
          for (int r = lane >> 4; r < 16; r += 2) {
            const uint4 v = lds128u(slab + (lane & 8) * 256 + r * 128 + (((lane ^ r) & 7) << 4));
            if (row + r != r1 && row + r != r2) reinterpret_cast<uint4*>(out + (size_t)(row + r) * D_)[cgrp * 16 + (lane & 15)] = v;
          }
        }
      }
      if (elect_one()) { bulk_commit(); bulk_wait_read<0>(); TRACE(29); }
    }
    asm volatile("" ::: "memory");
    if (warp == 3) {
      if (elect_one()) {
        fence_async_smem();
        unsigned next = clk32();
#pragma unroll 1
        for (int n = 0; n < 4 + FK_NA; n++) {
          if (n < 4) weight_box(n); else prefetch_piece(n);
          next += FK_PACE;
          while ((int)(clk32() - next) < 0) __nanosleep(20);
        }
        TRACE(37);
      }
      __syncwarp();
      int it = 0;
      wait_cnt(&S->cntMod[32], tag * 128u);
      mbar_wait(BAR(B_PREADY + 1), 0);
      {
        const float* mp = S->mod[tag & 1] + cgrp * 128 + lane * 4;
        const float4 ga = ldg_cg(mp + 2 * D_), sv = ldg_cg(mp + 3 * D_), cb = ldg_cg(mp + 4 * D_), gb = ldg_cg(mp + 5 * D_);
        const uint2 wr = __ldg(reinterpret_cast<const uint2*>(prm.w_r + cgrp * 128 + lane * 4));
        const uint32_t Aa = add_bf16x2(pack_bf16(cb.x, cb.y), 0x3F803F80u), Ab = add_bf16x2(pack_bf16(cb.z, cb.w), 0x3F803F80u);
        const uint32_t Sa = pack_bf16(sv.x, sv.y), Sb = pack_bf16(sv.z, sv.w), Ga = pack_bf16(gb.x, gb.y), Gb = pack_bf16(gb.z, gb.w);
        const float w0 = bf_lo(Aa) * bf_lo(wr.x), w1 = bf_hi(Aa) * bf_hi(wr.x), w2 = bf_lo(Ab) * bf_lo(wr.y), w3 = bf_hi(Ab) * bf_hi(wr.y);
        const uint32_t tb = sb + TAB_OFF + (lane >> 3) * 64 + (lane & 1) * 32 + ((lane >> 1) & 3) * 4, Wa = pack_bf16(w0, w1), Wb = pack_bf16(w2, w3);
        auto put = [&](int off, uint32_t a, uint32_t c) { sts32v(tb + off, a); sts32v(tb + off + 16, c); };
        put(T_WH, Wa, Wb); put(T_ONE, 0x3F803F80u, 0x3F803F80u);
        put(T_WL, pack_bf16(w0 - bf_lo(Wa), w1 - bf_hi(Wa)), pack_bf16(w2 - bf_lo(Wb), w3 - bf_hi(Wb)));
        put(T_GA, pack_bf16(ga.x, ga.y), pack_bf16(ga.z, ga.w)); put(T_A, Aa, Ab); put(T_S, Sa, Sb); put(T_G, Ga, Gb);
        float c1 = (w0 + w1) + (w2 + w3), c2 = (bf_lo(Sa) * bf_lo(wr.x) + bf_hi(Sa) * bf_hi(wr.x)) + (bf_lo(Sb) * bf_lo(wr.y) + bf_hi(Sb) * bf_hi(wr.y));
#pragma unroll 1
        for (int h = 0; h < 2; h++) {
#pragma unroll
          for (int o = 16; o; o >>= 1) { c1 += __shfl_xor_sync(~0u, c1, o); c2 += __shfl_xor_sync(~0u, c2, o); }
          if (h) break;
          if (t == 0 && lane == 0) st_msg(&S->cst[cgrp], __float_as_uint(c1), __float_as_uint(c2), tag, 0);
          uint4 cm; it = 0;
          while (true) {
            cm = ld_msg(&S->cst[lane & 7]);
            if (__all_sync(~0u, cm.z == tag)) break;
            SPIN_CHECK(it); __nanosleep(200);
          }
          c1 = 0.25f * __uint_as_float(cm.x); c2 = 0.25f * __uint_as_float(cm.y);
        }
        if (lane == 0) { sts128u(sb + CST_OFF, __float_as_uint(c1), __float_as_uint(c2), tag, 0); TRACE(27); }
      }
      uint32_t rk[16];
#pragma unroll
      for (int h = 0; h < 2; h++) {
        const uint2* src = (h ? &S->u[cgrp * 128] : &S->rs[t * 128]) + lane;
        uint2 m[8]; it = 0;
        while (true) {
          bool ok = true;
#pragma unroll
          for (int i = 0; i < 8; i++) { m[i] = ld_msg8(src + (i >> 1) * 32 + (i & 1) * (h ? D_ : S_)); ok &= m[i].y == tag; }
          if (ok) break;
          SPIN_CHECK(it);
        }
#pragma unroll
        for (int i = 0; i < 4; i++) {
          const float r0 = __uint_as_float(m[2 * i].x) * (h ? 0.5f : 1.f), r1 = __uint_as_float(m[2 * i + 1].x) * (h ? 0.5f : 1.f);
          const uint32_t hi = pack_bf16(r0, r1);
          rk[h * 8 + 2 * i] = hi; rk[h * 8 + 2 * i + 1] = pack_bf16(r0 - bf_lo(hi), r1 - bf_hi(hi));
        }
      }
      mbar_wait(BAR(B_B27), 0);
#pragma unroll
      for (int i = 0; i < 4; i++) {
        sts128u(sb + RKA_OFF + (i * 32 + lane) * 16, rk[2 * i], rk[2 * i], rk[2 * i + 1], 0);
        sts128u(sb + RKB_OFF + (i * 32 + lane) * 16, rk[8 + 2 * i], rk[9 + 2 * i], rk[8 + 2 * i], 0);
      }
      fence_async_smem();
      __syncwarp();
      if (lane == 0) { mbar_arrive(BAR(B_TAB)); TRACE(26); }
    }
    asm volatile("" ::: "memory");
    if (warp == 2) {
      mbar_wait(BAR(B_B27), 0);
      mbar_wait(BAR(B_EMPTY2 + 4), 1);
      uint4 m; int it = 0;
      while (true) {
        m = ld_msg(&S->cand[(lane >> 1) * 8]);
        if (__all_sync(~0u, m.z == tag)) break;
        SPIN_CHECK(it);
      }
      uint32_t k1, k2;
      const uint32_t key = (lane & 1) ? m.y : m.x;
      warp_top2(key, k1, k2);
      if (lane == 0) { sts64u(sb + SEL_OFF, k1, k2); mbar_arrive(BAR(B_SEL)); TRACE(14); }
    }
  } else {
    const int cw = (warp - 4) >> 2;
    const int cwarp = warp - 4;
    const int gq = lane >> 2, q4 = lane & 3;
    const bool elect = (tid & 127) == 0;
    uint32_t rel;
    asm volatile("mapa.shared::cluster.u32 %0, %1, %2;" : "=r"(rel) : "r"(BAR(0)), "r"(tid & 1));
    if (tid & 126) rel = 0;
    asm volatile("" : "+r"(rel));
    auto release = [&](int bar) {
      asm volatile("{\n.reg .pred p;\nsetp.ne.u32 p, %1, 0;\n@p mbarrier.arrive.shared::cluster.b64 _, [%0];\n}" ::"r"(rel + bar * 8), "r"(rel) : "memory");
    };
    const uint32_t da0 = desc_lo(sb + cw * 8192, 16), db0 = desc_lo(sb + SLOT, 8192), db2 = desc_lo(sb + SLOT, 16);
    asm volatile("barrier.cluster.wait.acquire.aligned;" ::: "memory");

    uint32_t wf[64], uf[64], df[64];
    const int kr = (lane & 7) + (lane >> 4) * 8;
    const uint32_t wo = sb + SP_OFF + cwarp * 1024 + kr * 64 + ((((lane >> 3) & 1) ^ ((kr >> 1) & 3)) << 4);
    auto take_part = [&](uint32_t* dst, int part) {
#pragma unroll
      for (int i = 0; i < 4; i++)
        asm volatile("{\n.reg .pred p;\nsetp.eq.s32 p, %10, %11;\n"
                     "@p ldmatrix.sync.aligned.m8n8.x4.trans.shared.b16 {%0, %1, %2, %3}, [%8];\n"
                     "@p ldmatrix.sync.aligned.m8n8.x4.trans.shared.b16 {%4, %5, %6, %7}, [%9];\n}"
                     : "+r"(dst[8 * i]), "+r"(dst[8 * i + 1]), "+r"(dst[8 * i + 2]), "+r"(dst[8 * i + 3]), "+r"(dst[8 * i + 4]), "+r"(dst[8 * i + 5]), "+r"(dst[8 * i + 6]), "+r"(dst[8 * i + 7])
                     : "r"(wo + i * 8192), "r"((wo ^ 32) + i * 8192), "r"(part < 0 ? i : part), "r"(i) : "memory");
    };
    uint32_t pk[64];
    uint32_t* const xw = pk + 32;
    const uint32_t slab = sb + E_OFF + cwarp * 4096;
    uint32_t xo = slab + (lane & 15) * 128 + (((lane >> 4) ^ (lane & 7)) << 4);
    auto take_x = [&](int part) {
#pragma unroll
      for (int i = 0; i < 4; i++)
        asm volatile("{\n.reg .pred p;\nsetp.eq.s32 p, %9, %10;\n"
                     "@p ldmatrix.sync.aligned.m8n8.x4.shared.b16 {%0, %1, %2, %3}, [%8];\n"
                     "@p ldmatrix.sync.aligned.m8n8.x4.shared.b16 {%4, %5, %6, %7}, [%8 + 2048];\n}"
                     : "+r"(xw[4 * i]), "+r"(xw[4 * i + 1]), "+r"(xw[4 * i + 2]), "+r"(xw[4 * i + 3]), "+r"(xw[4 * i + 16]), "+r"(xw[4 * i + 17]), "+r"(xw[4 * i + 18]), "+r"(xw[4 * i + 19])
                     : "r"(xo ^ (part << 5)), "r"(part), "r"(i) : "memory");
    };
    const int row0 = cwarp * 16 + gq;
    float lo[64];
    const uint32_t so = sb + (uint32_t)(cwarp * 16 + (lane & 15)) * 128 + (((lane >> 4) ^ (lane & 7)) << 4);
    auto p_ready = [&](int kk) { fence_async_smem(); if (elect_one()) mbar_arrive(BAR(B_PREADY + kk)); };
    {
      float pa[64], pb[64];
      {
        float acc[128];
#pragma unroll 1
        for (int g = 0; g < 28; g++) {
          const int s = g & 3;
          mbar_wait(BAR(B_FULL + s), (g >> 2) & 1);
          const uint32_t da = da0 + s * (STAGE >> 4), db = db0 + s * (STAGE >> 4);
          wg_fence();
          wgmma_n256<1>(acc, da, db, g > 0);
#pragma unroll
          for (int k = 1; k < 4; k++) wgmma_n256<1>(acc, da + k * 2, db + k * 128, 1);
          wg_commit();
          wg_wait<1>();
          if (g > 0) { release(B_EMPTY + ((g - 1) & 3)); if (elect) TRACE2(191 + g + cw * 32); }
          STAMP2(g);
        }
        wg_wait<0>();
        release(B_EMPTY + 3);
#pragma unroll
        for (int i = 0; i < 64; i++) {
          asm volatile("mov.b32 %0, %1;" : "=f"(pa[i]) : "f"(acc[i]));
          asm volatile("mov.b32 %0, %1;" : "=f"(pb[i]) : "f"(acc[64 + i]));
        }
      }
      if (elect) TRACE(3 + tr);
      STAMP2(28);
#pragma unroll 1
      for (int s = 0; s < 4; s++) {
        mbar_wait(BAR(B_FULL + s), 1);
        wg_fence();
#pragma unroll
        for (int k = 0; k < 4; k++) wgmma_n128<1>(pa, da0 + s * (STAGE >> 4) + k * 2, db0 + s * (STAGE >> 4) + k * 128);
        wg_commit();
        if (s == 2) { wg_wait<1>(); if (elect) mbar_arrive(BAR(B_A29)); }
      }
      auto b_block = [&](int s) {
        wg_fence();
#pragma unroll
        for (int k = 0; k < 4; k++) wgmma_n128<1>(pb, da0 + s * (STAGE >> 4) + k * 2, db0 + s * (STAGE >> 4) + 1024 + k * 128);
        wg_commit();
      };
      uint4 t0, t1;
      auto load_t = [&](int kk) { t0 = lds128u(sb + T1_OFF + kk * 128 + q4 * 16); t1 = lds128u(sb + T1_OFF + kk * 128 + 64 + q4 * 16); };
      auto pack_p = [&](int kk, const float* a) {
        const uint32_t A[8] = {t0.x, t0.y, t0.z, t0.w, t1.x, t1.y, t1.z, t1.w};
#pragma unroll
        for (int i = 0; i < 16; i++) pk[kk * 16 + i] = mul_bf16x2(pack_bf16(a[2 * i], a[2 * i + 1]), A[i >> 1]);
      };
      auto stage_p = [&](int kk) {
#pragma unroll
        for (int k = 0; k < 4; k++) stsm_x4((so ^ (k << 5)) + pstage(kk), pk + kk * 16 + k * 4);
      };
      auto own_block = [&](int q) {
        const uint32_t db = db2 + (buf_off(q) >> 4);
        wg_fence();
        if (q == 0) wgmma_n128_rs<0>(lo, pk, db); else wgmma_n128_rs<1>(lo, pk + q * 16, db);
#pragma unroll
        for (int k = 1; k < 4; k++) wgmma_n128_rs<1>(lo, pk + q * 16 + k * 4, db + k * 2);
        wg_commit();
      };
      b_block(0);
      mbar_wait(BAR(B_RSDONE), 0);
      asm volatile("setmaxnreg.inc.sync.aligned.u32 232;" ::: "memory");
      mbar_wait(BAR(B_A29), 0);
      load_t(0);
      wg_wait<1>();
      reg_fence(pa);
      release(B_ADONE);
      if (elect) TRACE(4 + tr);
      STAMP2(29);
      pack_p(0, pa); stage_p(0);
      if (FK_TR0) { p_ready(0); b_block(1); } else { b_block(1); p_ready(0); }
      if (elect) TRACE(2 + tr);
      wg_wait<1>(); release(B_EMPTY);
      load_t(1);
      b_block(2);
      pack_p(1, pa + 32);
      wg_wait<1>(); release(B_EMPTY + 1);
      STAMP2(30);
      load_t(2);
      b_block(3);
      mbar_wait(BAR(B_FULL2), 0);
      wg_wait<1>(); release(B_EMPTY + 2);
      own_block(0);
      mbar_wait(BAR(B_FULL2 + 1), 0);
      wg_wait<1>(); release(B_EMPTY + 3);
      reg_fence(pb);
      if (elect) TRACE(1 + tr);
      STAMP2(31);
      own_block(1);
      pack_p(2, pb);
      mbar_wait(BAR(B_FULL2 + 2), 0);
      wg_wait<1>(); release(B_EMPTY2);
      STAMP2(32);
      load_t(3);
      own_block(2);
      pack_p(3, pb + 32);
      mbar_wait(BAR(B_EMPTY + 3), 1);
      mbar_wait(BAR(B_FULL2 + 3), 0);
      wg_wait<1>(); release(B_EMPTY2 + 1);
      STAMP2(33);
      stage_p(1);
      own_block(3);
      p_ready(1);
      wg_wait<1>(); release(B_EMPTY2 + 2);
      STAMP2(34);
    }
    {
      int u = 4, up = 3; uint32_t ph = 0;
      asm volatile("" : "+r"(xo));
      mbar_wait(BAR(B_FULL2 + 4), 0);
#pragma unroll 1
      for (int q = 4; q < 32; q++) {
        const uint32_t bo = (0x21098000u >> (u * 4)) & 0x3800, da = da0 + bo, db = db2 + bo;
        wg_fence();
#pragma unroll
        for (int k = 0; k < 4; k++) wgmma_n128<0>(lo, da + k * 2, db + k * 2);
        wg_commit();
        wg_wait<1>();
        STAMP2(31 + q);
        if (q == 31) break;
        if (q == 28 && rel) rel = BAR(0);
        release(B_EMPTY2 + up);
        up = u;
        if (++u == 5) { u = 0; ph ^= 1; }
        if (((0x100u | 0x1000u << (2 * FK_SG)) >> q) & 1) p_ready(q >> 2);
        if ((0x0D555750u >> q) & 1) mbar_wait(BAR((q & 1) ? (q == 9 ? B_PS + 1 : B_EFULL) : B_WF + (((q >> 1) + 2) & 3)), (q & 1) ? 0 : ((q - 4) >> 3) & 1);
        mbar_wait(BAR(B_FULL2 + u), ph);
        if (q >= 27) take_x(q - 27);
        else if (q & 1) {
          if (q < 15) {
#pragma unroll
            for (int i = 0; i < 4; i++)
              asm volatile("{\n.reg .pred p;\nsetp.eq.s32 p, %10, %11;\n"
                           "@p stmatrix.sync.aligned.m8n8.x4.shared.b16 [%8], {%0, %1, %2, %3};\n"
                           "@p stmatrix.sync.aligned.m8n8.x4.shared.b16 [%9], {%4, %5, %6, %7};\n}"
                           ::"r"(pk[32 + 8 * i]), "r"(pk[33 + 8 * i]), "r"(pk[34 + 8 * i]), "r"(pk[35 + 8 * i]), "r"(pk[36 + 8 * i]), "r"(pk[37 + 8 * i]), "r"(pk[38 + 8 * i]), "r"(pk[39 + 8 * i]),
                           "r"((so ^ ((i & 1) << 6)) + pstage(2 + (i >> 1))), "r"((so ^ ((i & 1) << 6) ^ 32) + pstage(2 + (i >> 1))), "r"(q), "r"(5 + 2 * i + (i & 2) * FK_SG) : "memory");
          }
        } else if (q < 12) take_part(wf, (q - 4) >> 1);
        else if (q < 20) take_part(wf + 32, (q - 12) >> 1);
        else take_part(uf, (q - 20) >> 1);
      }
    }
    mbar_wait(BAR(B_TAB), 0);
    wg_fence();
    wgmma_n128<0, 8>(lo, desc_lo(sb + RKA_OFF + cw * 1024, 0), desc_lo(sb + RKB_OFF, 0));
    wg_commit();
    uint32_t tq = sb + TAB_OFF + q4 * 16, tb = tq + (gq & 1) * T_ONE + (gq & 2) * (T_WL / 2);
    const bool odd = q4 & 1;
    const uint4* src = &S->stats[(t * 8 + (q4 >> 1) * 4) * 128 + row0 + 8 * (q4 & 1)];
    uint4* sdst = &S->stats[b * 128 + row0 + 8 * q4];
    asm volatile("" : "+r"(tq), "+r"(tb), "+l"(src), "+l"(sdst));
    {
      uint4 gw[4];
#pragma unroll
      for (int a = 0; a < 4; a++) gw[a] = lds128u(tq + T_GA + a * 64);
      wg_wait<0>();
      reg_fence(lo);
      STAMP(0);
      if (elect) { TRACE(7 + tr); if (cw == 0) TRACE_CLK(121); }
      float c[2][4], e0[2][4], e1[2][4];
#pragma unroll
      for (int i = 0; i < 4; i++) c[0][i] = c[1][i] = e0[0][i] = e0[1][i] = e1[0][i] = e1[1][i] = 0.f;
#pragma unroll
      for (int a = 0; a < 4; a++) {
        const uint4 bw = lds128u(tb + a * 64);
        const uint32_t g[4] = {gw[a].x, gw[a].y, gw[a].z, gw[a].w};
#pragma unroll
        for (int i = 0; i < 8; i++) xw[a * 8 + i] = fma_bf16x2(g[i >> 1], pack_bf16(lo[a * 16 + 2 * i], lo[a * 16 + 2 * i + 1]), xw[a * 8 + i]);
#pragma unroll
        for (int h = 0; h < 2; h++) {
          const uint32_t* w = xw + a * 8 + h * 4;
          mma_1688(e0[0], w[0], w[1], w[0]); mma_1688(e1[0], w[0], w[1], w[1]); mma_1688(e0[1], w[2], w[3], w[2]); mma_1688(e1[1], w[2], w[3], w[3]);
          mma_16816(c[h], w, h ? bw.z : bw.x, h ? bw.w : bw.y);
        }
      }
      const float c0 = c[0][0] + c[1][0], c2 = c[0][2] + c[1][2];
      const float q0 = (gq & 1) ? e0[0][1] + e0[1][1] : e0[0][0] + e0[1][0], q1 = (gq & 1) ? e1[0][3] + e1[1][3] : e1[0][2] + e1[1][2];
      const int dl = (lane & ~3) | (gq >> 1);
      const float da = (odd ? c2 : c0) + __shfl_xor_sync(~0u, odd ? c0 : c2, 1), s1 = __shfl_xor_sync(~0u, c[0][3] + c[1][3], 1);
      const float qa = __shfl_sync(~0u, q0, dl), qb = __shfl_sync(~0u, q1, dl);
      if (q4 < 2) st_msg(sdst, __float_as_uint(odd ? s1 : c[0][1] + c[1][1]), __float_as_uint(odd ? qb : qa), __float_as_uint(da), 0);
    }
    if (elect) TRACE(8 + tr);
    STAMP(1);
    uint32_t rh[2], rl[2], nm[2];
    uint32_t bk1, bk2;
    uint4 tA[4], tS[4];
    {
      uint4 m[4];
#pragma unroll 1
      for (int i = 0; i < 4; i++) mbar_wait(BAR(B_WF + i), 1);
#pragma unroll
      for (int i = 0; i < 4; i++) m[i] = ld_msg(src + 128 * i);
      const float4 cst = lds128(sb + CST_OFF);
      take_part(uf + 32, -1);
#pragma unroll
      for (int a = 0; a < 4; a++) { tA[a] = lds128u(tq + T_A + a * 64); tS[a] = lds128u(tq + T_S + a * 64); }
      STAMP(2);
      int it = 0;
      while (!__all_sync(~0u, (m[0].w | m[1].w | m[2].w | m[3].w) == 0)) {
#pragma unroll
        for (int i = 0; i < 4; i++) m[i] = ld_msg(src + 128 * i);
        SPIN_CHECK(it);
      }
      STAMP(3);
      float sa = (__uint_as_float(m[0].x) + __uint_as_float(m[1].x)) + (__uint_as_float(m[2].x) + __uint_as_float(m[3].x));
      float qa = (__uint_as_float(m[0].y) + __uint_as_float(m[1].y)) + (__uint_as_float(m[2].y) + __uint_as_float(m[3].y));
      float da = (__uint_as_float(m[0].z) + __uint_as_float(m[1].z)) + (__uint_as_float(m[2].z) + __uint_as_float(m[3].z));
      sa += __shfl_xor_sync(~0u, sa, 2); qa += __shfl_xor_sync(~0u, qa, 2); da += __shfl_xor_sync(~0u, da, 2);
      const float mean = sa * (1.f / D_);
      const float rs = rsqrt_f(fmaxf(fmaf(-mean, mean, qa * (1.f / D_)), 0.f) + 1e-5f);
      const float r = fmaf(rs, fmaf(-mean, cst.x, da), cst.y);
      if (q4 < 2) sts32v(sb + KEY_OFF + (row0 + 8 * q4) * 4, (fkey(r) & ~2047u) | (uint32_t)(2047 - (t * 128 + row0 + 8 * q4)));
      if (tid == 128) TRACE(12 + 16);
      STAMP(4);
      named_bar<2, 256>();
      const uint4 k4 = lds128u(sb + KEY_OFF + lane * 16);
      const uint32_t ka = max(k4.x, k4.y), kb = max(k4.z, k4.w), m1 = max(ka, kb), m2 = max(min(ka, kb), ka > kb ? min(k4.x, k4.y) : min(k4.z, k4.w));
      bk1 = redux_max(m1); bk2 = redux_max(m1 == bk1 ? m2 : m1);
      if (tid == 128) { st_msg(&S->cand[t * 8], bk1, bk2, __float_as_uint(cst.z), 0); sts64u(sb + BK_OFF, bk1, bk2); TRACE(13); }
      const uint32_t h = pack_bf16(rs, rs), ln = pack_bf16(rs - bf_lo(h), -mean * rs), hx = __shfl_xor_sync(~0u, h, 1), lx = __shfl_xor_sync(~0u, ln, 1);
      rh[0] = odd ? hx : h; rh[1] = odd ? h : hx;
      rl[0] = __byte_perm(odd ? lx : ln, 0, 0x1010); rl[1] = __byte_perm(odd ? ln : lx, 0, 0x1010);
      nm[0] = __byte_perm(odd ? lx : ln, 0, 0x3232); nm[1] = __byte_perm(odd ? ln : lx, 0, 0x3232);
      STAMP(5);
    }
    auto slab_row = [&](int r) { return lds128u(slab + (lane & 8) * 256 + r * 128 + (((lane ^ r) & 7) << 4)); };
    {
      const int lr1 = key_row(bk1) - t * 128, lr2 = key_row(bk2) - t * 128;
      uint4* cp[2]; bool cand[2];
#pragma unroll
      for (int r = 0; r < 2; r++) {
        const int lr = row0 + 8 * r;
        cand[r] = lr == lr1 || lr == lr2;
        cp[r] = &S->rowsH[(t * 2 + (lr == lr2)) * 128 + cgrp * 16 + q4];
      }
#pragma unroll
      for (int a = 0; a < 4; a++) {
        const uint4 tG = lds128u(tq + T_G + a * 64);
        const uint32_t A[4] = {tA[a].x, tA[a].y, tA[a].z, tA[a].w}, B[4] = {tS[a].x, tS[a].y, tS[a].z, tS[a].w}, G[4] = {tG.x, tG.y, tG.z, tG.w};
#pragma unroll
        for (int r = 0; r < 2; r++) {
          uint32_t h[4], *w = xw + a * 8 + r;
#pragma unroll
          for (int k = 0; k < 4; k++) h[k] = fma_bf16x2(fma_bf16x2(w[2 * k], rh[r], fma_bf16x2(w[2 * k], rl[r], nm[r])), A[k], B[k]);
          if (cand[r]) st_msg(cp[r] + a * 4, h[0], h[1], h[2], h[3]);
#pragma unroll
          for (int k = 0; k < 4; k++) w[2 * k] = fma_bf16x2(G[k], h[k], w[2 * k]);
        }
#pragma unroll
        for (int h = 0; h < 2; h++) stsm_x4((xo ^ ((((a & 1) * 2) + h) << 5)) + (a >> 1) * 2048, xw + a * 8 + h * 4);
      }
      const int lr = lane < 16 ? lr1 : lr2;
      __syncwarp();
      if ((lr >> 4) == cwarp) { const uint4 v = slab_row(lr & 15); st_msg(&S->rowsB[(t * 2 + (lane >> 4)) * 128 + cgrp * 16 + (lane & 15)], v.x, v.y, v.z, v.w); }
    }
    fence_async_smem();
    if (elect_one()) mbar_arrive(BAR(B_PREADY));
    STAMP(6);
    if (tid == 128) TRACE(15);
    STAMP(7);
    mbar_wait(BAR(B_SEL), 0);
    STAMP(8);
    const float2 selv = lds64(sb + SEL_OFF);
    const uint32_t key1 = __float_as_uint(selv.x), key2 = __float_as_uint(selv.y);
    const int t1 = key_row(key1) >> 7, t2 = key_row(key2) >> 7;
    const int slotA = t1 * 2, slotB = t2 * 2 + (t1 == t2 ? 1 : 0);
    const int fn = b & 1, fcol = (b >> 1) * 16 + q4 * 2 + ((lane >> 2) & 1) + (lane & 8);
    uint32_t fbase = SENT; float fgb = 0.f;
    const uint32_t* fbp = reinterpret_cast<const uint32_t*>(&S->rowsB[(fn ? slotB : slotA) * 128]) + (fcol >> 1);
    uint2 hb[8];
    const uint2* hp = reinterpret_cast<const uint2*>(&S->rowsH[((gq & 1) ? slotB : slotA) * 128 + (cwarp >> 1) * 4 + q4]) + (cwarp & 1);
    if (moe) {
#pragma unroll
      for (int i = 0; i < 8; i++) hb[i] = ld_msg8(hp + i * 32);
    }
    STAMP(9);
    mbar_wait(BAR(B_DN), 0);
    {
      const uint32_t db = sb + DN_OFF + (cwarp + (cwarp == 7) * 4) * 8192 + kr * 128 + ((((lane >> 3) & 1) ^ (lane & 7)) << 4);
#pragma unroll
      for (int i = 0; i < 16; i++) ldsm_x4_t((db ^ (((i >> 1) & 3) << 5)) + (i >> 3) * 4096 + (i & 1) * 2048, df + i * 4);
    }
    if (moe) {
      int it = 0;
      while (!__all_sync(~0u, max(max(max(hb[0].x, hb[1].x), max(hb[2].x, hb[3].x)), max(max(hb[4].x, hb[5].x), max(hb[6].x, hb[7].x))) != SENT)) {
#pragma unroll
        for (int i = 0; i < 8; i++) hb[i] = ld_msg8(hp + i * 32);
        SPIN_CHECK(it);
      }
      if (tid == 128) TRACE(16);
      STAMP(10);
      float c[4][4];
#pragma unroll
      for (int i = 0; i < 4; i++) c[i][0] = c[i][1] = c[i][2] = c[i][3] = 0.f;
#pragma unroll
      for (int ks = 0; ks < 8; ks++) {
        const uint32_t b0 = hb[ks].x, b1 = hb[ks].y;
        mma_16816(c[0], wf + ks * 8, b0, b1); mma_16816(c[1], wf + ks * 8 + 4, b0, b1);
        mma_16816(c[2], uf + ks * 8, b0, b1); mma_16816(c[3], uf + ks * 8 + 4, b0, b1);
      }
      {
        float v[4];
#pragma unroll
        for (int i = 0; i < 4; i++) v[i] = (q4 & 2) ? (odd ? c[3][i] : c[2][i]) : (odd ? c[1][i] : c[0][i]);
        sts128(sb + RED_OFF + cwarp * 512 + (q4 * 8 + (gq ^ (q4 * 2))) * 16, v[0], v[2], v[1], v[3]);
      }
    }
    STAMP(11);
    if (cwarp == 0) { fbase = ld_rlx(fbp); fgb = __uint_as_float(ld_rlx(S->mod[lds32u(sb + CST_OFF + 8) & 1] + 5 * D_ + fcol)); }
    if (moe) {
      named_bar<2, 256>();
      STAMP(12);
      float g0 = 0.f, g1 = 0.f, u0 = 0.f, u1 = 0.f;
#pragma unroll
      for (int w = 0; w < 8; w++) {
        const float2 gv = lds64(sb + RED_OFF + w * 512 + ((lane * 8) ^ ((lane & 16) * 2))), uv = lds64(sb + RED_OFF + w * 512 + 256 + ((lane * 8) ^ ((lane & 16) * 2) ^ 64));
        g0 += gv.x; g1 += gv.y; u0 += uv.x; u1 += uv.y;
      }
      const uint32_t gp = pack_bf16(g0, g1), up = pack_bf16(u0, u1), sp = pack_bf16(silu_f(bf_lo(gp)), silu_f(bf_hi(gp)));
      const uint32_t act = pack_bf16(bf_lo(sp) * bf_lo(up), bf_hi(sp) * bf_hi(up));
      uint32_t ab[4];
#pragma unroll
      for (int i = 0; i < 4; i++) ab[i] = __shfl_sync(~0u, act, i * 8 + q4 * 2 + (gq & 1));
      if (tid == 128) TRACE(31);
      STAMP(13);
#pragma unroll
      for (int T = 0; T < 2; T++) {
        float c[4][4];
#pragma unroll
        for (int i = 0; i < 4; i++) {
          c[i][0] = c[i][1] = c[i][2] = c[i][3] = 0.f;
          mma_16816(c[i], df + (T * 4 + i) * 8, ab[0], ab[1]); mma_16816(c[i], df + (T * 4 + i) * 8 + 4, ab[2], ab[3]);
        }
        float v[4];
#pragma unroll
        for (int i = 0; i < 4; i++) v[i] = (q4 & 2) ? (odd ? c[3][i] : c[2][i]) : (odd ? c[1][i] : c[0][i]);
        uint2* pp = reinterpret_cast<uint2*>(&S->part[((cwarp * 16 + T * 8 + q4 * 2) * 128 + eb) * 4]) + gq;
        st_msg8(pp, __float_as_uint(v[0]), __float_as_uint(v[2])); st_msg8(pp + 1024, __float_as_uint(v[1]), __float_as_uint(v[3]));
      }
      if (tid == 128) TRACE(32);
      STAMP(14);
    }
    if (cwarp == 0) {
      const uint32_t fk = fn ? key2 : key1;
      const float sg = round_bf16(sigmoid_f(round_bf16(fkey_inv((fk & ~2047u) | 1024u))));
      int it = 0;
      while (fbase == SENT) { fbase = ld_rlx(fbp); SPIN_CHECK(it); }
      spin(moe ? FK_PDELAY : FK_PDELAY + 1200);
      uint4 m[14];
      while (true) {
        bool ok = true;
#pragma unroll
        for (int i = 0; i < 14; i++) { m[i] = ld_msg(&S->part[b * 512 + i * 32 + lane]); ok &= m[i].x != SENT && m[i].z != SENT; }
        if (__all_sync(~0u, ok)) break;
        SPIN_CHECK(it);
      }
      if (lane == 0) TRACE(33);
      STAMP(15);
      float y[4] = {0.f, 0.f, 0.f, 0.f};
#pragma unroll
      for (int i = 0; i < 14; i++) { y[0] += __uint_as_float(m[i].x); y[1] += __uint_as_float(m[i].y); y[2] += __uint_as_float(m[i].z); y[3] += __uint_as_float(m[i].w); }
      const bool b2 = lane & 4;
      float y0 = (b2 ? y[2] : y[0]) + __shfl_xor_sync(~0u, b2 ? y[0] : y[2], 4), y1 = (b2 ? y[3] : y[1]) + __shfl_xor_sync(~0u, b2 ? y[1] : y[3], 4);
      y0 = ((lane & 8) ? y1 : y0) + __shfl_xor_sync(~0u, (lane & 8) ? y0 : y1, 8);
      y0 += __shfl_xor_sync(~0u, y0, 16);
      const float upd = round_bf16(round_bf16(y0) * sg);
      if (lane < 16) out[(size_t)key_row(fk) * D_ + fcol] = __float2bfloat16_rn(fmaf(round_bf16(fgb), upd, (fcol & 1) ? bf_hi(fbase) : bf_lo(fbase)));
      if (lane == 0) {
        TRACE(34); TRACE_CLK(122);
        if (b == 0) S->epoch[0] = lds32u(sb + CST_OFF + 8);
      }
    }
  }
}

typedef CUresult (*PFN_encodeTiled)(CUtensorMap*, CUtensorMapDataType, cuuint32_t, void*, const cuuint64_t*, const cuuint64_t*,
                                    const cuuint32_t*, const cuuint32_t*, CUtensorMapInterleave, CUtensorMapSwizzle,
                                    CUtensorMapL2promotion, CUtensorMapFloatOOBfill);

static void mapnd(PFN_encodeTiled enc, CUtensorMap* m, const void* p, int nd, const cuuint64_t* dims, const cuuint64_t* str, const cuuint32_t* box,
                  CUtensorMapSwizzle sw, CUtensorMapL2promotion pr) {
  const cuuint32_t es[5] = {1, 1, 1, 1, 1};
  enc(m, CU_TENSOR_MAP_DATA_TYPE_BFLOAT16, nd, (void*)p, dims, str, box, es, CU_TENSOR_MAP_INTERLEAVE_NONE, sw, pr, CU_TENSOR_MAP_FLOAT_OOB_FILL_NONE);
}
static void map2d(PFN_encodeTiled enc, CUtensorMap* m, const void* p, uint64_t rows, uint64_t cols, uint32_t brows, uint32_t bcols,
                  CUtensorMapSwizzle sw = CU_TENSOR_MAP_SWIZZLE_128B, CUtensorMapL2promotion pr = CU_TENSOR_MAP_L2_PROMOTION_L2_128B) {
  const cuuint64_t dims[2] = {cols, rows}, str[1] = {cols * 2}; const cuuint32_t box[2] = {bcols, brows};
  mapnd(enc, m, p, 2, dims, str, box, sw, pr);
}
static void map3d(PFN_encodeTiled enc, CUtensorMap* m, const void* p, uint64_t rows, uint64_t cols, uint32_t brows, uint32_t bgroups) {
  const cuuint64_t dims[3] = {64, rows, cols / 64}, str[2] = {cols * 2, 128}; const cuuint32_t box[3] = {64, brows, bgroups};
  mapnd(enc, m, p, 3, dims, str, box, CU_TENSOR_MAP_SWIZZLE_128B, CU_TENSOR_MAP_L2_PROMOTION_L2_128B);
}

}

extern "C" void kernel_launch(void* const* d_in, const int* in_sizes, int n_in, void* d_out, int out_size) {
  using namespace fk;
  (void)in_sizes; (void)n_in; (void)out_size;
  static PFN_encodeTiled enc = nullptr;
  static Scratch* scr = nullptr;
  if (!enc) {
    void* fn = nullptr; cudaDriverEntryPointQueryResult qr;
    cudaGetDriverEntryPoint("cuTensorMapEncodeTiled", &fn, cudaEnableDefault, &qr);
    enc = (PFN_encodeTiled)fn;
    cudaGetSymbolAddress((void**)&scr, g_scr);
    cudaFuncSetAttribute(fused_kernel, cudaFuncAttributeMaxDynamicSharedMemorySize, SMEM_BYTES);
  }
  typedef const __nv_bfloat16* bp;
  Params prm;
  prm.w_r = (bp)d_in[6];
  prm.wsp[0] = (const char*)d_in[1]; prm.wsp[1] = (const char*)d_in[2];
  map2d(enc, &prm.ws[0], d_in[1], S_, S_, 128, 64);
  map2d(enc, &prm.ws[1], d_in[2], S_, S_, 128, 64);
  map3d(enc, &prm.n, scr->n, S_, D_, 64, 2);
  map2d(enc, &prm.wm, d_in[11], D_, 6 * D_, 8, 256, CU_TENSOR_MAP_SWIZZLE_NONE, CU_TENSOR_MAP_L2_PROMOTION_L2_256B);
  map2d(enc, &prm.p, scr->P, 2 * S_, D_, 128, 64);
  map2d(enc, &prm.wd[0], d_in[3], D_, D_, 64, 64);
  map2d(enc, &prm.wd[1], d_in[4], D_, D_, 64, 64);
  map2d(enc, &prm.wg, d_in[7], D_, F_, 128, 32, CU_TENSOR_MAP_SWIZZLE_64B);
  map2d(enc, &prm.wu, d_in[8], D_, F_, 128, 32, CU_TENSOR_MAP_SWIZZLE_64B);
  for (int i = 0; i < 3; i++) prm.we[i] = (const char*)d_in[7 + i];
  map2d(enc, &prm.ps, scr->P, 2 * S_, D_, 32, 64);
  map3d(enc, &prm.xm, d_in[0], S_, D_, 16, 2);
  map3d(enc, &prm.om, d_out, S_, D_, 16, 2);
  {
    const cuuint64_t dims[5] = {64, 2, 8, 224, 16}, str[4] = {8 * 2048, 2048, 16 * 2048, 128}; const cuuint32_t box[5] = {64, 2, 8, 2, 2};
    mapnd(enc, &prm.wdn, d_in[9], 5, dims, str, box, CU_TENSOR_MAP_SWIZZLE_128B, CU_TENSOR_MAP_L2_PROMOTION_L2_128B);
  }

  fused_kernel<<<NCTA, 384, SMEM_BYTES, cudaStreamPerThread>>>((bp)d_in[0], scr, (__nv_bfloat16*)d_out, (bp)d_in[10], (bp)d_in[3], (bp)d_in[4], prm);
}
```

```cpp
#include <cuda_runtime.h>
#include <cuda_bf16.h>
#include <cuda.h>
#include <stdint.h>

#define DEVINL __device__ __forceinline__

namespace fk {

constexpr int S_ = 2048, D_ = 1024, F_ = 3584;
constexpr int NCTA = 128;
constexpr int SLOT = 16384;
constexpr int STAGE = 3 * SLOT;
constexpr int BUF = 2 * SLOT;
constexpr int E_OFF = 5 * BUF;
constexpr int SP_OFF = 4 * STAGE;
constexpr int MISC_OFF = SP_OFF + 32768;
constexpr int SMEM_BYTES = MISC_OFF + 3072;
constexpr int BAR_OFF = MISC_OFF;
constexpr int SEL_OFF = MISC_OFF + 344;
constexpr int BK_OFF = MISC_OFF + 360;
constexpr int CST_OFF = MISC_OFF + 368;
constexpr int PFLAG_OFF = MISC_OFF + 384;
constexpr int TAB_OFF = MISC_OFF + 512;
enum { T_WH = 0, T_ONE = 320, T_WL = 576, T_GA = 896, T_A = 1152, T_S = 1408, T_G = 1664 };
constexpr int KEY_OFF = TAB_OFF + 2048;
constexpr int POLL_OFF = TAB_OFF + 256;
constexpr int T1_OFF = TAB_OFF + 1536;
constexpr int RKA_OFF = BUF;
constexpr int RKB_OFF = RKA_OFF + 2048;
constexpr int RED_OFF = RKB_OFF + 2048;
constexpr int DN_OFF = RED_OFF + 4096;

enum { B_FULL = 0, B_EMPTY = 4, B_PREADY = 8, B_MF = 12  , B_FULL2 = 20  , B_EMPTY2 = 25  , B_A29 = 30, B_ADONE = 31,
       B_RSDONE = 32, B_TAB = 33, B_B27 = 34, B_SEL = 35, B_DN = 36, B_EFULL = 37, B_PS = 38  , B_WF = 40, B_BK = 41, B_FIN = 42, B_NUM = 43 };
constexpr unsigned long long CNT0 = 0x1111888855551111ull, CNT1 = 0x4244444222221111ull, CNT2 = 0x1111111111111112ull;

#define FK_SKIP 0
#define FK_X 0
#define FK_PS0 1
#define FK_XN 0
#define FK_S1 0
#define FK_NL 15
#define FK_XD 0
#define FK_GS 1
#define FK_TD 1
#define FK_TX 1
#define FK_REL 0x14
#define FK_WSPF 22
#define FK_SPACE 300
#define FK_OSPACE 100
#define FK_NOMC 4
#define FK_TR0 0
#define FK_G0 5
#define FK_NA 2
#define FK_PACE 800
#define FK_QP 3
#define FK_PSPACE 400
#define FK_ORD 0
#define FK_PDELAY 700
constexpr int SPIN_LIMIT = 1 << 20;
constexpr uint32_t SENT = 0xFFFFFFFFu;

struct Scratch {
  uint4 part[128 * 128 * 4];
  uint4 stats[128 * 128];
  uint4 rowsH[32 * 128];
  uint4 rowsB[32 * 128];
  uint4 cand[16 * 8];
  uint2 rs[2 * S_];
  uint4 cst[8];
  float mod[2][6 * D_];
  uint2 u[2 * D_];
  unsigned flagP[128 * 4 * 8];
  unsigned cntN[12 * 32];
  unsigned cntMod[2 * 32];
  unsigned epoch[32];
  alignas(1024) __nv_bfloat16 n[S_ * D_];
  __nv_bfloat16 P[2 * S_ * D_];
};
__device__ __align__(1024) Scratch g_scr;

struct Params {
  CUtensorMap ws[2];
  CUtensorMap n;
  CUtensorMap wm;
  CUtensorMap p;
  CUtensorMap wg, wu;
  CUtensorMap xm;
  CUtensorMap wdn;
  CUtensorMap wd[2];
  CUtensorMap om;
  CUtensorMap ps;
  CUtensorMap tch[2];
  const __nv_bfloat16* w_r;
  const char* wsp[2];
  const char* we[3];
};

DEVINL uint32_t smem_u32(const void* p) { return (uint32_t)__cvta_generic_to_shared(p); }
DEVINL void mbar_init(uint32_t bar, uint32_t cnt) { asm volatile("mbarrier.init.shared::cta.b64 [%0], %1;" ::"r"(bar), "r"(cnt) : "memory"); }
DEVINL void mbar_expect_tx(uint32_t bar, uint32_t bytes) { asm volatile("mbarrier.arrive.expect_tx.shared::cta.b64 _, [%0], %1;" ::"r"(bar), "r"(bytes) : "memory"); }
DEVINL void mbar_arrive(uint32_t bar) { asm volatile("mbarrier.arrive.shared::cta.b64 _, [%0];" ::"r"(bar) : "memory"); }
DEVINL void mbar_wait(uint32_t bar, uint32_t parity) {
  asm volatile("{\n.reg .pred p;\n.reg .u32 c;\nmov.u32 c, 0;\n"
               "LW:\nmbarrier.try_wait.parity.shared::cta.b64 p, [%0], %1;\n@p bra LD;\n"
               "add.u32 c, c, 1;\nsetp.lt.u32 p, c, 1048576;\n@p bra LW;\ntrap;\nLD:\n}" ::"r"(bar), "r"(parity) : "memory");
}
DEVINL void mbar_wait_cluster(uint32_t bar, uint32_t parity) {
  asm volatile("{\n.reg .pred p;\n.reg .u32 c;\nmov.u32 c, 0;\n"
               "LW:\nmbarrier.try_wait.parity.acquire.cluster.shared::cta.b64 p, [%0], %1;\n@p bra LD;\n"
               "add.u32 c, c, 1;\nsetp.lt.u32 p, c, 1048576;\n@p bra LW;\ntrap;\nLD:\n}" ::"r"(bar), "r"(parity) : "memory");
}
#define SPIN_CHECK(it) if (++(it) > SPIN_LIMIT) __trap()
DEVINL void fence_async_smem() { asm volatile("fence.proxy.async.shared::cta;" ::: "memory"); }
DEVINL void fence_async_global() { asm volatile("fence.proxy.async.global;" ::: "memory"); }
template <int BIT> DEVINL void rel_fence() { if ((FK_REL >> BIT) & 1) asm volatile("fence.acq_rel.gpu;" ::: "memory"); }
DEVINL void fence_gpu() { asm volatile("fence.acq_rel.gpu;" ::: "memory"); }
template <int ID, int N> DEVINL void named_bar() { asm volatile("bar.sync %0, %1;" ::"n"(ID), "n"(N) : "memory"); }
DEVINL bool elect_one() { uint32_t p; asm volatile("{\n.reg .pred e;\nelect.sync _|e, 0xffffffff;\nselp.u32 %0, 1, 0, e;\n}" : "=r"(p)); return p; }
DEVINL unsigned clk32() { unsigned c; asm volatile("mov.u32 %0, %%clock;" : "=r"(c)); return c; }
#define FK_GRIDW 32
#define FK_GRID 0
DEVINL void grid_wait() {
  if (FK_GRID) {
    unsigned t0, t1;
    asm volatile("mov.u32 %0, %%globaltimer_lo;" : "=r"(t0));
    do { asm volatile("mov.u32 %0, %%globaltimer_lo;" : "=r"(t1)); } while (((t0 - FK_GRIDW) ^ t1) < FK_GRID + 0u + !FK_GRID);
  }
}
DEVINL void spin(unsigned n) { const unsigned c = clk32(); while (clk32() - c < n) {} }

constexpr uint64_t POL_NORMAL = 0x1000000000000000ull, POL_FIRST = 0x12F0000000000000ull;
#define FK_HINTS 0x11B
template <int BIT> DEVINL constexpr uint64_t pol() { return ((FK_HINTS >> BIT) & 1) ? POL_FIRST : POL_NORMAL; }
DEVINL void tma_2d(uint32_t dst, const CUtensorMap* m, int x, int y, uint32_t bar, uint64_t pol) {
  asm volatile("cp.async.bulk.tensor.2d.shared::cluster.global.mbarrier::complete_tx::bytes.L2::cache_hint [%0], [%1, {%3, %4}], [%2], %5;"
               ::"r"(dst), "l"(m), "r"(bar), "r"(x), "r"(y), "l"(pol) : "memory");
}
DEVINL void tma_3d(uint32_t dst, const CUtensorMap* m, int y, int z, uint32_t bar, uint64_t pol) {
  asm volatile("cp.async.bulk.tensor.3d.shared::cluster.global.mbarrier::complete_tx::bytes.L2::cache_hint [%0], [%1, {0, %3, %4}], [%2], %5;"
               ::"r"(dst), "l"(m), "r"(bar), "r"(y), "r"(z), "l"(pol) : "memory");
}
DEVINL void tma_3d_mc(uint32_t dst, const CUtensorMap* m, int y, int z, uint32_t bar, uint64_t pol) {
  asm volatile("cp.async.bulk.tensor.3d.shared::cluster.global.mbarrier::complete_tx::bytes.multicast::cluster.L2::cache_hint [%0], [%1, {0, %3, %4}], [%2], %5, %6;"
               ::"r"(dst), "l"(m), "r"(bar), "r"(y), "r"(z), "h"((unsigned short)3), "l"(pol) : "memory");
}
DEVINL void tma_2d_mc(uint32_t dst, const CUtensorMap* m, int x, int y, uint32_t bar, uint64_t pol) {
  asm volatile("cp.async.bulk.tensor.2d.shared::cluster.global.mbarrier::complete_tx::bytes.multicast::cluster.L2::cache_hint [%0], [%1, {%3, %4}], [%2], %5, %6;"
               ::"r"(dst), "l"(m), "r"(bar), "r"(x), "r"(y), "h"((unsigned short)3), "l"(pol) : "memory");
}
DEVINL void tma_store_2d(const CUtensorMap* m, uint32_t src, int x, int y) {
  asm volatile("cp.async.bulk.tensor.2d.global.shared::cta.bulk_group [%0, {%2, %3}], [%1];" ::"l"(m), "r"(src), "r"(x), "r"(y) : "memory");
}
DEVINL void bulk_store(void* dst, uint32_t src, uint32_t bytes) {
  asm volatile("cp.async.bulk.global.shared::cta.bulk_group [%0], [%1], %2;" ::"l"(dst), "r"(src), "r"(bytes) : "memory");
}
DEVINL void bulk_load(uint32_t dst, const void* src, uint32_t bytes, uint32_t bar, uint64_t pol) {
  asm volatile("cp.async.bulk.shared::cluster.global.mbarrier::complete_tx::bytes.L2::cache_hint [%0], [%1], %2, [%3], %4;" ::"r"(dst), "l"(src), "r"(bytes), "r"(bar), "l"(pol) : "memory");
}
template <int N> DEVINL void bulk_wait_read() { asm volatile("cp.async.bulk.wait_group.read %0;" ::"n"(N) : "memory"); }
DEVINL void pf_bulk(const void* p, uint32_t bytes) { asm volatile("cp.async.bulk.prefetch.L2.global [%0], %1;" ::"l"(p), "r"(bytes) : "memory"); }
DEVINL void bulk_commit() { asm volatile("cp.async.bulk.commit_group;" ::: "memory"); }
template <int N> DEVINL void bulk_wait() { asm volatile("cp.async.bulk.wait_group %0;" ::"n"(N) : "memory"); }
DEVINL void prefetch_tmap(const CUtensorMap* m) { asm volatile("prefetch.tensormap [%0];" ::"l"(m) : "memory"); }

DEVINL void wg_fence() { asm volatile("wgmma.fence.sync.aligned;" ::: "memory"); }
DEVINL void wg_commit() { asm volatile("wgmma.commit_group.sync.aligned;" ::: "memory"); }
template <int N> DEVINL void wg_wait() { asm volatile("wgmma.wait_group.sync.aligned %0;" ::"n"(N) : "memory"); }
DEVINL uint32_t desc_lo(uint32_t addr, uint32_t lbo) { return ((addr & 0x3FFFF) >> 4) | ((lbo >> 4) << 16); }

#define R8(a, o) "+f"(a[o]), "+f"(a[o + 1]), "+f"(a[o + 2]), "+f"(a[o + 3]), "+f"(a[o + 4]), "+f"(a[o + 5]), "+f"(a[o + 6]), "+f"(a[o + 7])
#define R64(a, o) R8(a, o), R8(a, o + 8), R8(a, o + 16), R8(a, o + 24), R8(a, o + 32), R8(a, o + 40), R8(a, o + 48), R8(a, o + 56)
#define ACC64 "{%0, %1, %2, %3, %4, %5, %6, %7, %8, %9, %10, %11, %12, %13, %14, %15, "              \
              "%16, %17, %18, %19, %20, %21, %22, %23, %24, %25, %26, %27, %28, %29, %30, %31, "    \
              "%32, %33, %34, %35, %36, %37, %38, %39, %40, %41, %42, %43, %44, %45, %46, %47, "    \
              "%48, %49, %50, %51, %52, %53, %54, %55, %56, %57, %58, %59, %60, %61, %62, %63"
#define ACC128 ACC64 ", %64, %65, %66, %67, %68, %69, %70, %71, %72, %73, %74, %75, %76, %77, %78, %79, "      \
              "%80, %81, %82, %83, %84, %85, %86, %87, %88, %89, %90, %91, %92, %93, %94, %95, "               \
              "%96, %97, %98, %99, %100, %101, %102, %103, %104, %105, %106, %107, %108, %109, %110, %111, "   \
              "%112, %113, %114, %115, %116, %117, %118, %119, %120, %121, %122, %123, %124, %125, %126, %127"
template <int TB> DEVINL void wgmma_n256(float (&d)[128], uint32_t da, uint32_t db, int scale_d) {
  asm volatile("{\n.reg .pred p;\n.reg .b64 a, b;\nsetp.ne.b32 p, %130, 0;\nmov.b64 a, {%128, 0x40000040};\nmov.b64 b, {%129, 0x40000040};\n"
               "wgmma.mma_async.sync.aligned.m64n256k16.f32.bf16.bf16 " ACC128 "}, a, b, p, 1, 1, 0, %131;\n}\n"
               : R64(d, 0), R64(d, 64) : "r"(da), "r"(db), "r"(scale_d), "n"(TB));
}
template <int TB, int HI = 0x40000040> DEVINL void wgmma_n128(float (&d)[64], uint32_t da, uint32_t db) {
  asm volatile("{\n.reg .b64 a, b;\nmov.b64 a, {%64, %67};\nmov.b64 b, {%65, %67};\n"
               "wgmma.mma_async.sync.aligned.m64n128k16.f32.bf16.bf16 " ACC64 "}, a, b, 1, 1, 1, 0, %66;\n}\n" : R64(d, 0) : "r"(da), "r"(db), "n"(TB), "n"(HI));
}
template <int SC> DEVINL void wgmma_n128_rs(float (&d)[64], const uint32_t* a, uint32_t db) {
  asm volatile("{\n.reg .pred p;\n.reg .b64 b;\nsetp.ne.b32 p, %69, 0;\nmov.b64 b, {%68, 0x40000040};\n"
               "wgmma.mma_async.sync.aligned.m64n128k16.f32.bf16.bf16 " ACC64 "}, {%64, %65, %66, %67}, b, p, 1, 1, 0;\n}\n"
               : R64(d, 0) : "r"(a[0]), "r"(a[1]), "r"(a[2]), "r"(a[3]), "r"(db), "n"(SC));
}
template <int N> DEVINL void reg_fence(float (&a)[N]) {
#pragma unroll
  for (int i = 0; i < N; i++) asm volatile("" : "+f"(a[i])::"memory");
}

DEVINL uint32_t pack_bf16(float lo, float hi) { uint32_t r; asm("cvt.rn.bf16x2.f32 %0, %1, %2;" : "=r"(r) : "f"(hi), "f"(lo)); return r; }
DEVINL uint32_t add_bf16x2(uint32_t a, uint32_t b) { uint32_t r; asm("add.rn.bf16x2 %0, %1, %2;" : "=r"(r) : "r"(a), "r"(b)); return r; }
DEVINL uint32_t mul_bf16x2(uint32_t a, uint32_t b) { uint32_t r; asm("mul.rn.bf16x2 %0, %1, %2;" : "=r"(r) : "r"(a), "r"(b)); return r; }
DEVINL uint32_t fma_bf16x2(uint32_t a, uint32_t b, uint32_t c) { uint32_t r; asm("fma.rn.bf16x2 %0, %1, %2, %3;" : "=r"(r) : "r"(a), "r"(b), "r"(c)); return r; }
DEVINL float bf_lo(uint32_t w) { return __uint_as_float(w << 16); }
DEVINL float bf_hi(uint32_t w) { return __uint_as_float(w & 0xFFFF0000u); }
DEVINL float round_bf16(float v) { return bf_lo(pack_bf16(v, 0.f)); }
DEVINL float sigmoid_f(float v) { float r; asm("rcp.approx.ftz.f32 %0, %1;" : "=f"(r) : "f"(1.f + __expf(-v))); return r; }
DEVINL float rsqrt_f(float v) { float r; asm("rsqrt.approx.ftz.f32 %0, %1;" : "=f"(r) : "f"(v)); return r; }
DEVINL float silu_f(float v) { return v * sigmoid_f(v); }
DEVINL void stsm_x4(uint32_t addr, const uint32_t* r) {
  asm volatile("stmatrix.sync.aligned.m8n8.x4.shared.b16 [%0], {%1, %2, %3, %4};" ::"r"(addr), "r"(r[0]), "r"(r[1]), "r"(r[2]), "r"(r[3]) : "memory");
}
DEVINL void ldsm_x4(uint32_t addr, uint32_t* r) {
  asm volatile("ldmatrix.sync.aligned.m8n8.x4.shared.b16 {%0, %1, %2, %3}, [%4];" : "=r"(r[0]), "=r"(r[1]), "=r"(r[2]), "=r"(r[3]) : "r"(addr) : "memory");
}
DEVINL void ldsm_x4_t(uint32_t addr, uint32_t* r) {
  asm volatile("ldmatrix.sync.aligned.m8n8.x4.trans.shared.b16 {%0, %1, %2, %3}, [%4];" : "=r"(r[0]), "=r"(r[1]), "=r"(r[2]), "=r"(r[3]) : "r"(addr) : "memory");
}
DEVINL void mma_16816(float (&c)[4], const uint32_t* a, uint32_t b0, uint32_t b1) {
  asm("mma.sync.aligned.m16n8k16.row.col.f32.bf16.bf16.f32 {%0, %1, %2, %3}, {%4, %5, %6, %7}, {%8, %9}, {%0, %1, %2, %3};"
      : "+f"(c[0]), "+f"(c[1]), "+f"(c[2]), "+f"(c[3]) : "r"(a[0]), "r"(a[1]), "r"(a[2]), "r"(a[3]), "r"(b0), "r"(b1));
}
DEVINL void mma_1688(float (&c)[4], uint32_t a0, uint32_t a1, uint32_t b0) {
  asm("mma.sync.aligned.m16n8k8.row.col.f32.bf16.bf16.f32 {%0, %1, %2, %3}, {%4, %5}, {%6}, {%0, %1, %2, %3};"
      : "+f"(c[0]), "+f"(c[1]), "+f"(c[2]), "+f"(c[3]) : "r"(a0), "r"(a1), "r"(b0));
}
DEVINL float4 lds128(uint32_t a) { float4 v; asm volatile("ld.shared.v4.f32 {%0, %1, %2, %3}, [%4];" : "=f"(v.x), "=f"(v.y), "=f"(v.z), "=f"(v.w) : "r"(a)); return v; }
DEVINL uint4 lds128u(uint32_t a) { uint4 v; asm volatile("ld.shared.v4.u32 {%0, %1, %2, %3}, [%4];" : "=r"(v.x), "=r"(v.y), "=r"(v.z), "=r"(v.w) : "r"(a)); return v; }
DEVINL float2 lds64(uint32_t a) { float2 v; asm volatile("ld.shared.v2.f32 {%0, %1}, [%2];" : "=f"(v.x), "=f"(v.y) : "r"(a)); return v; }
DEVINL uint32_t lds32u(uint32_t a) { uint32_t v; asm volatile("ld.shared.u32 %0, [%1];" : "=r"(v) : "r"(a)); return v; }
DEVINL void sts128(uint32_t a, float x, float y, float z, float w) { asm volatile("st.shared.v4.f32 [%0], {%1, %2, %3, %4};" ::"r"(a), "f"(x), "f"(y), "f"(z), "f"(w) : "memory"); }
DEVINL void sts128u(uint32_t a, uint32_t x, uint32_t y, uint32_t z, uint32_t w) { asm volatile("st.shared.v4.u32 [%0], {%1, %2, %3, %4};" ::"r"(a), "r"(x), "r"(y), "r"(z), "r"(w) : "memory"); }
DEVINL void sts64u(uint32_t a, uint32_t x, uint32_t y) { asm volatile("st.shared.v2.u32 [%0], {%1, %2};" ::"r"(a), "r"(x), "r"(y) : "memory"); }
DEVINL void sts32v(uint32_t a, uint32_t v) { asm volatile("st.volatile.shared.u32 [%0], %1;" ::"r"(a), "r"(v) : "memory"); }
DEVINL void sts32(uint32_t a, float v) { asm volatile("st.shared.f32 [%0], %1;" ::"r"(a), "f"(v) : "memory"); }

DEVINL uint4 ld_msg(const void* p) {
  unsigned long long a, b;
  asm volatile("{\n.reg .b128 r;\nld.relaxed.gpu.global.b128 r, [%2];\nmov.b128 {%0, %1}, r;\n}" : "=l"(a), "=l"(b) : "l"(p) : "memory");
  return make_uint4((uint32_t)a, (uint32_t)(a >> 32), (uint32_t)b, (uint32_t)(b >> 32));
}
DEVINL void st_msg(void* p, uint32_t x, uint32_t y, uint32_t z, uint32_t w) {
  unsigned long long a = (unsigned long long)x | ((unsigned long long)y << 32), b = (unsigned long long)z | ((unsigned long long)w << 32);
  asm volatile("{\n.reg .b128 r;\nmov.b128 r, {%1, %2};\nst.relaxed.gpu.global.b128 [%0], r;\n}" ::"l"(p), "l"(a), "l"(b) : "memory");
}
DEVINL uint2 ld_msg8(const void* p) {
  unsigned long long a;
  asm volatile("ld.relaxed.gpu.global.b64 %0, [%1];" : "=l"(a) : "l"(p) : "memory");
  return make_uint2((uint32_t)a, (uint32_t)(a >> 32));
}
DEVINL void st_msg8(void* p, uint32_t x, uint32_t y) {
  asm volatile("st.relaxed.gpu.global.b64 [%0], %1;" ::"l"(p), "l"((unsigned long long)x | ((unsigned long long)y << 32)) : "memory");
}
DEVINL unsigned ld_rlx(const void* p) { unsigned v; asm volatile("ld.relaxed.gpu.global.u32 %0, [%1];" : "=r"(v) : "l"(p) : "memory"); return v; }
DEVINL void st_rlx(unsigned* p, unsigned v) { asm volatile("st.relaxed.gpu.global.u32 [%0], %1;" ::"l"(p), "r"(v) : "memory"); }
DEVINL void red_add(unsigned* p, unsigned v) { asm volatile("red.relaxed.gpu.global.add.u32 [%0], %1;" ::"l"(p), "r"(v) : "memory"); }
DEVINL uint4 ldg_nc(const void* p) {
  uint4 v;
  asm volatile("ld.global.nc.L1::no_allocate.v4.u32 {%0, %1, %2, %3}, [%4];" : "=r"(v.x), "=r"(v.y), "=r"(v.z), "=r"(v.w) : "l"(p));
  return v;
}
DEVINL float4 ldg_cg(const float* p) { float4 v; asm volatile("ld.global.cg.v4.f32 {%0, %1, %2, %3}, [%4];" : "=f"(v.x), "=f"(v.y), "=f"(v.z), "=f"(v.w) : "l"(p) : "memory"); return v; }
DEVINL void wait_cnt(const unsigned* p, unsigned target) {
  int it = 0;
  while ((int)(ld_rlx(p) - target) < 0) { SPIN_CHECK(it); __nanosleep(100); }
}

#define TRACE2(id)
#define TRACE3(id)
#define TRACE(id)
#define TRACE_CLK(id)

#define STAMP2(i)
#define STAMP(i)
DEVINL uint32_t fkey(float v) { const uint32_t u = __float_as_uint(v); return (u & 0x80000000u) ? ~u : (u | 0x80000000u); }
DEVINL float fkey_inv(uint32_t k) { return __uint_as_float((k & 0x80000000u) ? (k & 0x7FFFFFFFu) : ~k); }
DEVINL uint32_t redux_max(uint32_t v) { uint32_t r; asm volatile("redux.sync.max.u32 %0, %1, 0xffffffff;" : "=r"(r) : "r"(v)); return r; }
DEVINL void warp_top2(uint32_t key, uint32_t& k1, uint32_t& k2) { k1 = redux_max(key); k2 = redux_max(key == k1 ? 0u : key); }
DEVINL int key_row(uint32_t k) { return 2047 - (int)(k & 2047u); }
DEVINL int blk_src(int q, int cgrp) { const int f = q - 4, kk = (f * 37) >> 8, i = f - kk * 7; return f < 0 ? cgrp * 4 + q : (FK_SKIP ? i + (i >= cgrp) : i == cgrp ? 7 : i) * 4 + kk; }
DEVINL uint32_t pstage(int kk) { return ((0xABA4 >> (kk * 4)) & 15) * SLOT; }
DEVINL uint32_t buf_off(int u) { return ((0x42130 >> (u * 4)) & 15) * BUF; }
DEVINL int cnt_idx(int kb) { return kb < 4 ? (8 + kb) * 32 : (kb >> 2) * 32 + (kb & 3); }

__global__ void __launch_bounds__(384, 1) __cluster_dims__(2, 1, 1)
fused_kernel(const __nv_bfloat16* __restrict__ x, Scratch* const S, __nv_bfloat16* __restrict__ out, const __nv_bfloat16* __restrict__ cvec,
             const __nv_bfloat16* __restrict__ wd_re, const __nv_bfloat16* __restrict__ wd_im, const __grid_constant__ Params prm) {
  extern __shared__ __align__(1024) uint8_t smem_raw[];
  const uint32_t sb = smem_u32(smem_raw);
  const int tid = threadIdx.x, lane = tid & 31;
  const int warp = __shfl_sync(~0u, tid >> 5, 0);
  const int cl = blockIdx.x >> 1;
  const int rank = blockIdx.x & 1, c7 = ((cl - 36) * 37) >> 8;
  const int grp = cl < 4 ? 0 : cl < 36 ? (cl - 4) & 7 : cl - 35 - c7 * 7, gi = cl < 4 ? cl + 4 : cl < 36 ? (cl - 4) >> 3 : c7 + 4;
  const int j = gi >> 2, m4 = gi & 3, t = grp * 2 + rank;
  const int cgrp = m4 * 2 + j;
  const int b = t * 8 + cgrp;
  const bool moe = gi < 7;
  const int eb0 = j ? 64 + grp * 6 : grp * 8, eb = eb0 + m4 * 2 + rank;
  auto BAR = [&](int i) { return sb + BAR_OFF + i * 8; };

  uint4 xr[8];
  if ((warp & ~1) == 2) {
    const uint4* src = reinterpret_cast<const uint4*>(x + (size_t)(blockIdx.x * 2 + warp - 2) * D_) + lane;
#pragma unroll
    for (int i = 0; i < 4; i++) xr[i] = ldg_nc(src + 32 * i);
  }
  if (tid == 0) TRACE(0);
  if ((warp & ~1) != 2 && elect_one()) {
    const int w = warp < 2 ? warp : warp - 2;
#pragma unroll
    for (int k = 0; k < 5; k++) {
      const int i = w + 10 * k;
      if (i < B_NUM) mbar_init(BAR(i), (uint32_t)((i < 16 ? CNT0 : i < 32 ? CNT1 : CNT2) >> ((i & 15) * 4)) & 15u);
    }
    if (w < 4) mbar_expect_tx(BAR(B_FULL + w), STAGE);
    asm volatile("fence.mbarrier_init.release.cluster;" ::: "memory");
    if (w == 0) tma_2d(sb, &prm.ws[j], 0, t * 128, BAR(B_FULL), pol<0>());
    else prefetch_tmap(&prm.ws[1] + w);
  }
  if ((warp & ~1) != 2) { named_bar<4, 320>(); asm volatile("bar.arrive 3, 384;" ::: "memory"); }
  asm volatile("barrier.cluster.arrive.relaxed.aligned;" ::: "memory");

  if (warp < 4) {
    auto prefetch_piece = [&](int p) { if (!(FK_X & 1)) pf_bulk(prm.we[p >> 3] + (size_t)((p & 7) * 128 + b) * 7168, 7168); };
    auto weight_box = [&](int n, uint32_t bar) {
      if (moe && !(FK_X & 2)) {
        asm volatile("mbarrier.expect_tx.relaxed.cta.shared::cta.b64 [%0], 8192;" ::"r"(bar) : "memory");
        tma_2d(sb + SP_OFF + (n & 3) * 8192, &prm.wg + (n >> 3), eb * 32, (n & 7) * 128, bar, pol<3>());
      }
    };
    uint32_t tag = 0;
    if (warp == 0) {
      const unsigned* flagAddr = &S->cntN[cnt_idx(lane)];
      const unsigned tgt = (ld_rlx(S->epoch) + 1) * 64u;
      asm volatile("barrier.cluster.wait.acquire.aligned;" ::: "memory");
      unsigned ready = 0;
      if (lane >= 4) sts32v(sb + POLL_OFF + lane * 4, tgt - 1);
#pragma unroll 1
      for (int g = 0; g < 32; g++) {
        const int s = g & 3;
        const uint32_t sa = sb + s * STAGE, fb = BAR(B_FULL + s);
        if (!((ready >> g) & 1)) {
          unsigned v;
          asm volatile("ld.volatile.shared.u32 %0, [%1];" : "=r"(v) : "r"(sb + POLL_OFF + lane * 4) : "memory");
          ready |= __ballot_sync(~0u, v == tgt) & ~15u;
          int it = 0;
          while (!((ready >> g) & 1)) {
            ready |= __ballot_sync(~0u, (lane >> 2) == (g >> 2) && ld_rlx(flagAddr) == tgt);
            SPIN_CHECK(it);
          }
          fence_async_global();
        }
        if (g >= 4) {
          mbar_wait(BAR(B_EMPTY + s), ((g >> 2) - 1) & 1);
          if (lane < 8 && ((~ready >> (lane * 4)) & 15))
            asm volatile("cp.async.cg.shared.global [%0], [%1], 16;" ::"r"(sb + POLL_OFF + lane * 16), "l"(&S->cntN[lane * 32]) : "memory");
          if (elect_one()) { TRACE2(128 + g); mbar_expect_tx(fb, STAGE); tma_2d(sa, &prm.ws[j], g * 64, t * 128, fb, pol<0>()); }
        }
        if (elect_one()) {
          if (g < FK_NOMC) { tma_3d(sa + SLOT, &prm.n, g * 64, m4 * 4, fb, pol<4>()); tma_3d(sa + 2 * SLOT, &prm.n, g * 64, m4 * 4 + 2, fb, pol<4>()); }
          else tma_3d_mc(sa + SLOT + rank * SLOT, &prm.n, g * 64, m4 * 4 + rank * 2, fb, pol<4>());
          if (g > 0 && g < 4) tma_2d(sa, &prm.ws[j], g * 64, t * 128, fb, pol<0>());
          TRACE2(64 + g);
        }
        if ((unsigned)(g - FK_WSPF) < 4u)
          asm volatile("prefetch.global.L2 [%0];" ::"l"(prm.wsp[j] + (size_t)(t * 128 + m4 * 32 + (g - FK_WSPF) * 8 + (lane >> 2)) * 4096 + 3584 + (lane & 3) * 128));
      }
      asm volatile("cp.async.wait_all;" ::: "memory");
    }
    asm volatile("" ::: "memory");
    if (warp == 1) {
      tag = ld_rlx(S->epoch) + 1;
      if (elect_one()) prefetch_tmap(&prm.ps);
      const uint32_t rb = sb + (m4 * 32 + lane) * 128 + ((lane & 7) << 4);
      float a0 = 0.f, a1 = 0.f, a2 = 0.f, a3 = 0.f;
#pragma unroll 1
      for (int g = 0; g < 32; g++) {
        const int s = g & 3;
        mbar_wait(BAR(B_FULL + s), (g >> 2) & 1);
        uint4 u[8];
#pragma unroll
        for (int c = 0; c < 8; c++) u[c] = lds128u((rb + s * STAGE) ^ (c << 4));
        u[7].x = __shfl_sync(~0u, u[7].x, lane);
        if (elect_one()) {
          mbar_arrive(BAR(B_EMPTY + s)); TRACE2(160 + g);
          const int p = (g - FK_G0) >> FK_GS;
          if (g >= FK_G0 && !((g - FK_G0) & FK_GS) && (p < 8 ? moe && FK_TD : p < 12 && FK_TX)) {
            asm volatile("mbarrier.expect_tx.relaxed.cta.shared::cta.b64 [%0], 512;" ::"r"(BAR(B_RSDONE)) : "memory");
            tma_3d(sb + KEY_OFF, &prm.tch[p >> 3], p < 8 ? p : cgrp, p < 8 ? eb * 32 : t * 128 + (p - 8) * 32, BAR(B_RSDONE), POL_NORMAL);
          }
        }
#pragma unroll
        for (int c = 0; c < 8; c++) {
          a0 += bf_lo(u[c].x) + bf_lo(u[c].y); a1 += bf_hi(u[c].x) + bf_hi(u[c].y);
          a2 += bf_lo(u[c].z) + bf_lo(u[c].w); a3 += bf_hi(u[c].z) + bf_hi(u[c].w);
        }
      }
      if (lane == 0) mbar_arrive(BAR(B_RSDONE));
      mbar_wait(BAR(B_RSDONE), 0);
      st_msg8(&S->rs[j * S_ + t * 128 + m4 * 32 + lane], __float_as_uint((a0 + a1) + (a2 + a3)), tag);
    }
    asm volatile("" ::: "memory");
    if (warp >= 2) {
      const uint32_t ring = sb + SP_OFF + (warp - 2) * 16384, mf = BAR(B_MF + (warp - 2) * 4);
      const int jw = b >> 6, e0 = (b & 63) * 16;
      const __nv_bfloat16* src = (jw ? wd_im : wd_re) + (size_t)e0 * D_;
      int nc = 0;
#pragma unroll 1
      for (int G = 0; G < 8; G += (G == 0 && warp == 2) + 1) {
        if (G) { mbar_wait(mf + (nc & 3) * 8, (nc >> 2) & 1); nc++; }
        const uint32_t stg = ring + (nc & 3) * 4096, sl = stg + (G ? (lane >> 4) * 2048 + (lane & 15) * 16 : lane * 16), st = G ? 256 : 512;
        if (G) {
#pragma unroll
          for (int k = 0; k < 8; k++) xr[k] = lds128u(sl + k * 256);
        }
        float s0 = 0.f, s1 = 0.f, q0 = 0.f, q1 = 0.f, s2 = 0.f, s3 = 0.f, q2 = 0.f, q3 = 0.f;
        float v[64];
#pragma unroll
        for (int h = 0; h < 2; h++)
          if (h == 0 || G) {
#pragma unroll
            for (int k = 4 * h; k < 4 * h + 4; k++) {
              float* u = v + 8 * k;
              u[0] = bf_lo(xr[k].x); u[1] = bf_hi(xr[k].x); u[2] = bf_lo(xr[k].y); u[3] = bf_hi(xr[k].y);
              u[4] = bf_lo(xr[k].z); u[5] = bf_hi(xr[k].z); u[6] = bf_lo(xr[k].w); u[7] = bf_hi(xr[k].w);
#pragma unroll
              for (int i = 0; i < 8; i += 4) {
                s0 += u[i]; s1 += u[i + 1]; s2 += u[i + 2]; s3 += u[i + 3];
                q0 = fmaf(u[i], u[i], q0); q1 = fmaf(u[i + 1], u[i + 1], q1); q2 = fmaf(u[i + 2], u[i + 2], q2); q3 = fmaf(u[i + 3], u[i + 3], q3);
              }
            }
          }
        float sum = (s0 + s1) + (s2 + s3), sq = (q0 + q1) + (q2 + q3);
#pragma unroll
        for (int o = 1; o < 32; o <<= 1)
          if (o < 16 || !G) { sum += __shfl_xor_sync(~0u, sum, o); sq += __shfl_xor_sync(~0u, sq, o); }
        const float mean = sum * (1.f / D_);
        const float rstd = rsqrt_f(fmaxf(fmaf(-mean, mean, sq * (1.f / D_)), 0.f) + 1e-5f), nmr = -mean * rstd;
#pragma unroll
        for (int h = 0; h < 2; h++)
          if (h == 0 || G) {
#pragma unroll
            for (int k = 4 * h; k < 4 * h + 4; k++) {
              const float* u = v + 8 * k;
              sts128u(sl + k * st, pack_bf16(fmaf(u[0], rstd, nmr), fmaf(u[1], rstd, nmr)), pack_bf16(fmaf(u[2], rstd, nmr), fmaf(u[3], rstd, nmr)),
                      pack_bf16(fmaf(u[4], rstd, nmr), fmaf(u[5], rstd, nmr)), pack_bf16(fmaf(u[6], rstd, nmr), fmaf(u[7], rstd, nmr)));
            }
          }
        fence_async_smem();
        const int kq = blockIdx.x >> 5;
        if (elect_one()) {
          bulk_store(S->n + (size_t)(G * 256 + blockIdx.x * 2 + (G ? 0 : warp - 2)) * D_, stg, G ? 4096 : 2048); bulk_commit();
          if (G == 0) { bulk_wait<0>(); rel_fence<0>(); red_add(&S->cntN[cnt_idx(kq)], 1); TRACE(42 + warp); }
        }
        if (G == 0) named_bar<3, 384>();
        if (elect_one()) {
          if (G == 0 && warp == 2) mbar_wait(BAR(B_FULL), 0);
          if (G >= 4) { bulk_wait<1>(); red_add(&S->cntN[(G - 1) * 32 + kq], 2); }
#pragma unroll 1
          for (int k = G ? nc + 1 : 0; k < (warp == 2 ? nc + 2 : 1); k++) {
            mbar_expect_tx(mf + (k & 3) * 8, 4096);
            bulk_load(ring + ((k + 1) & 3) * 4096, k < 6 ? x + (size_t)((k + 4 - warp) * 256 + blockIdx.x * 2) * D_ : src + (k - 6) * 2 * D_, 4096, mf + (k & 3) * 8, k < 6 ? pol<7>() : pol<2>());
          }
          if (G == 1 || G == 2 || G == 7) { bulk_wait<0>(); rel_fence<1>(); red_add(&S->cntN[G * 32 + kq], 2); if (G > 1) TRACE(44 + (G & 3)); }
        }
        __syncwarp();
        if (warp == 3 && G) break;
      }
      tag = ld_rlx(S->epoch) + 1;
      float* const mod = S->mod[tag & 1];
      if (warp == 3) {
        const uint32_t stab = sb + TAB_OFF, stg = stab + 512;
        {
          const uint32_t cw = __ldg(reinterpret_cast<const uint32_t*>(cvec + t * 64) + lane);
          const uint32_t sp = pack_bf16(silu_f(bf_lo(cw)), silu_f(bf_hi(cw)));
          sts64u(stab + lane * 8, sp << 16, sp & 0xFFFF0000u);
        }
        float acc[8];
#pragma unroll
        for (int i = 0; i < 8; i++) acc[i] = 0.f;
#pragma unroll 1
        for (int n = -3; n < 24; n++) {
          if (n < 21 && elect_one()) {
            mbar_expect_tx(mf + (n & 3) * 8, 4096);
            tma_2d(ring + (n & 3) * 4096, &prm.wm, ((n + 3) >> 3) * 2048 + cgrp * 256, t * 64 + ((n + 3) & 7) * 8, mf + (n & 3) * 8, pol<1>());
          }
          if (n < 0) continue;
          const uint32_t sl = ring + ((n + 1) & 3) * 4096 + lane * 16;
          const float4 sv0 = lds128(stab + (n & 7) * 32), sv1 = lds128(stab + (n & 7) * 32 + 16);
          const float sc[8] = {sv0.x, sv0.y, sv0.z, sv0.w, sv1.x, sv1.y, sv1.z, sv1.w};
          mbar_wait(mf + ((n + 1) & 3) * 8, ((n + 1) >> 2) & 1);
          uint4 v[8];
#pragma unroll
          for (int u = 0; u < 8; u++) v[u] = lds128u(sl + u * 512);
#pragma unroll
          for (int u = 0; u < 8; u++) {
            acc[0] = fmaf(sc[u], bf_lo(v[u].x), acc[0]); acc[1] = fmaf(sc[u], bf_hi(v[u].x), acc[1]);
            acc[2] = fmaf(sc[u], bf_lo(v[u].y), acc[2]); acc[3] = fmaf(sc[u], bf_hi(v[u].y), acc[3]);
            acc[4] = fmaf(sc[u], bf_lo(v[u].z), acc[4]); acc[5] = fmaf(sc[u], bf_hi(v[u].z), acc[5]);
            acc[6] = fmaf(sc[u], bf_lo(v[u].w), acc[6]); acc[7] = fmaf(sc[u], bf_hi(v[u].w), acc[7]);
          }
          asm volatile("" : "+f"(acc[0]) :: "memory");
          if ((n & 7) == 7) {
            sts128(stg + lane * 32, acc[0], acc[1], acc[2], acc[3]); sts128(stg + lane * 32 + 16, acc[4], acc[5], acc[6], acc[7]);
#pragma unroll
            for (int i = 0; i < 8; i++) acc[i] = 0.f;
            fence_async_smem();
            if (elect_one()) {
              asm volatile("cp.reduce.async.bulk.global.shared::cta.bulk_group.add.f32 [%0], [%1], 1024;" ::"l"(mod + (n >> 3) * 2048 + cgrp * 256), "r"(stg) : "memory");
              bulk_commit();
              if (n != 15) { bulk_wait<0>(); rel_fence<2>(); red_add(&S->cntMod[n > 7 ? 32 : 0], 1); } else bulk_wait_read<0>();
              TRACE(n > 7 ? 34 + (n >> 3) : 9);
            }
          }
        }
      } else {
        wait_cnt(S->cntMod, tag * 128u);
        if (lane == 0) TRACE(10);
        float4 sa[8];
        {
          const float4 c0 = ldg_cg(mod + D_ + m4 * 256 + lane * 8), c1 = ldg_cg(mod + D_ + m4 * 256 + lane * 8 + 4);
#pragma unroll
          for (int i = 0; i < 8; i++) {
            const float4 sv = ldg_cg(mod + (i >> 1) * 256 + lane * 8 + (i & 1) * 4);
            const uint32_t s0 = pack_bf16(sv.x, sv.y), s1 = pack_bf16(sv.z, sv.w);
            sa[i] = make_float4(bf_lo(s0), bf_hi(s0), bf_lo(s1), bf_hi(s1));
          }
          const uint32_t cw[4] = {pack_bf16(c0.x, c0.y), pack_bf16(c0.z, c0.w), pack_bf16(c1.x, c1.y), pack_bf16(c1.z, c1.w)};
#pragma unroll
          for (int q = 0; q < 4; q++) sts32v(sb + T1_OFF + (lane >> 2) * 64 + q * 16 + (lane & 3) * 4, add_bf16x2(cw[q], 0x3F803F80u) ^ (j ? 0x80008000u : 0u));
        }
        float ul = 0.f;
#pragma unroll 1
        for (int r = 0; r < 8; r++) {
          if (r < 6 && elect_one()) {
            mbar_expect_tx(mf + ((nc + 2) & 3) * 8, 4096);
            bulk_load(ring + ((nc + 3) & 3) * 4096, src + (r + 2) * 2 * D_, 4096, mf + ((nc + 2) & 3) * 8, pol<2>());
          }
          mbar_wait(mf + (nc & 3) * 8, (nc >> 2) & 1); nc++;
          uint4 v[8];
          float u[4] = {0.f, 0.f, 0.f, 0.f};
#pragma unroll
          for (int i = 0; i < 8; i++) v[i] = lds128u(ring + (nc & 3) * 4096 + lane * 16 + i * 512);
#pragma unroll
          for (int i = 0; i < 8; i++) {
            const float4 s0 = sa[2 * (i & 3)], s1 = sa[2 * (i & 3) + 1];
            float &u0 = u[(i >> 2) * 2], &u1 = u[(i >> 2) * 2 + 1];
            u0 = fmaf(bf_lo(v[i].x), s0.x, u0); u1 = fmaf(bf_hi(v[i].x), s0.y, u1); u0 = fmaf(bf_lo(v[i].y), s0.z, u0); u1 = fmaf(bf_hi(v[i].y), s0.w, u1);
            u0 = fmaf(bf_lo(v[i].z), s1.x, u0); u1 = fmaf(bf_hi(v[i].z), s1.y, u1); u0 = fmaf(bf_lo(v[i].w), s1.z, u0); u1 = fmaf(bf_hi(v[i].w), s1.w, u1);
          }
          const float ua = u[0] + u[1], ub = u[2] + u[3];
          float us = ((lane & 1) ? ub : ua) + __shfl_xor_sync(~0u, (lane & 1) ? ua : ub, 1);
#pragma unroll
          for (int o = 16; o > 1; o >>= 1) us += __shfl_xor_sync(~0u, us, o);
          if ((lane >> 1) == r) ul = jw ? -us : us;
        }
        if (lane < 16) st_msg8(&S->u[jw * D_ + e0 + lane], __float_as_uint(ul), tag);
        if (lane == 0) TRACE(11);
#pragma unroll
        for (int i = 0; i < 4; i++) sts128u(ring + lane * 16 + i * 512, SENT, SENT, SENT, SENT);
        fence_async_smem();
        if (elect_one()) {
#pragma unroll 1
          for (int i = 0; i < 9; i++)
            bulk_store(i < 4 ? &S->part[b * 512 + i * 128] : i == 4 ? &S->stats[b * 128] : &S->rowsH[((i - 5) >> 1) * 4096 + (t * 2 + (i & 1)) * 128 + cgrp * 16], ring, i < 5 ? 2048 : 256);
          bulk_store(&S->flagP[b * 32], ring, 128);
          bulk_commit(); bulk_wait<0>(); rel_fence<4>();
          mbar_arrive(BAR(B_RSDONE)); TRACE(30);
        }
        if (lane < 12) reinterpret_cast<float4*>(S->mod[~tag & 1] + b * 48)[lane] = make_float4(0.f, 0.f, 0.f, 0.f);
      }
      named_bar<1, 64>();
    }
    asm volatile("setmaxnreg.dec.sync.aligned.u32 40;" ::: "memory");
    if (warp == 2) {
      const int scl = blk_src(lane, cgrp);
      const unsigned* flagAddr = &S->flagP[(t * 8 + (scl >> 2)) * 32 + (scl & 3)];
      const unsigned* cellAddr = &S->flagP[(t * 8 + (lane & 7)) * 32];
      sts32v(sb + PFLAG_OFF + lane * 4, tag - 1);
      if (lane < 4) mbar_arrive(BAR(B_FULL2 + lane));
      mbar_wait(BAR(B_PREADY), 0);
      unsigned ready = 15;
      int u = 4, i7 = 0, kk = 0; uint32_t ph = 1;
#pragma unroll 1
      for (int q = 4; q < 32; q++) {
        const int src = FK_SKIP ? i7 + (i7 >= cgrp) : i7 == cgrp ? 7 : i7;
        if (!((ready >> q) & 1)) {
          unsigned v;
          asm volatile("ld.volatile.shared.u32 %0, [%1];" : "=r"(v) : "r"(sb + PFLAG_OFF + scl * 4) : "memory");
          ready |= __ballot_sync(~0u, v == tag);
          int it = 0;
          while (!((ready >> q) & 1)) {
            ready |= __ballot_sync(~0u, (unsigned)(lane - q) < 7u && ld_rlx(flagAddr) == tag);
            SPIN_CHECK(it);
          }
          fence_async_global();
        }
        if ((q & ~4) == 8) mbar_wait(BAR(B_PS - 2 + (q >> 2)), 0);
        mbar_wait(BAR(q >= 8 ? B_EMPTY2 + u : q == 4 ? B_EMPTY + 2 : B_FULL2 + u), ph);
        if (q >= 8) grid_wait();
        if (elect_one()) {
          TRACE3(128 + q);
          mbar_expect_tx(BAR(B_FULL2 + u), SLOT);
          tma_2d(sb + buf_off(u), &prm.p, (src >> 1) * 256 + kk * 64, (src & 1) * S_ + t * 128, BAR(B_FULL2 + u), pol<5>());
        }
        if (((~ready >> q) & 15) && lane < 8)
          asm volatile("cp.async.cg.shared.global [%0], [%1], 16;" ::"r"(sb + PFLAG_OFF + lane * 16), "l"(cellAddr) : "memory");
        if (++u == 5) { u = 0; ph ^= 1; }
        if (++i7 == 7) { i7 = 0; kk++; }
      }
      asm volatile("cp.async.wait_all;" ::: "memory");
    }
    asm volatile("" ::: "memory");
    if (warp == 0) {
      int u = 0; uint32_t ph = 1;
#pragma unroll 1
      for (int q = 0; q < 32; q++) {
        const int sc = blk_src(q, cgrp);
        mbar_wait(BAR(q >= 5 ? B_EMPTY2 + u : q < 2 ? B_ADONE : q == 4 ? B_EMPTY + 3 : B_EMPTY + 1), q >= 2 ? ph : 0);
        if (elect_one()) {
          TRACE3(160 + q);
          mbar_expect_tx(BAR(B_FULL2 + u), SLOT);
          tma_2d_mc(sb + buf_off(u) + SLOT + rank * 8192, &prm.wd[(sc >> 2) & 1], (sc >> 3) * 256 + (sc & 3) * 64, cgrp * 128 + rank * 64, BAR(B_FULL2 + u), pol<6>());
          if (q & 1) { const int p = 4 + FK_NA + ((q - FK_QP) >> 1); if (q >= FK_QP && p < (FK_TD ? 16 : 24)) prefetch_piece(p); }
          else if (q >= 10 && q < 2 * FK_NL + 2) weight_box((q >> 1) - 1, BAR(B_FULL2 + (u == 4 ? 0 : u + 1)));
        }
        if (++u == 5) { u = 0; ph ^= 1; }
      }
      if (elect_one()) {
#pragma unroll 1
        for (int n = FK_NL; n < 15; n++) weight_box(n, BAR(B_WF));
        mbar_expect_tx(BAR(B_DN), moe ? 65536 : 0);
#pragma unroll 1
        for (int i = 0; i < 9; i++) {
          if ((i & 3) == 0) mbar_wait(BAR(B_EMPTY2 + 2 + (i >> 2)), 1);
          if (i == 0) { mbar_arrive(BAR(B_B27)); weight_box(15, BAR(B_WF)); mbar_arrive(BAR(B_WF)); }
          else if (moe)
            asm volatile("cp.async.bulk.tensor.5d.shared::cluster.global.mbarrier::complete_tx::bytes.L2::cache_hint [%0], [%1, {0, 0, 0, %3, %4}], [%2], %5;"
                         ::"r"(sb + RKA_OFF + (i + (i >> 3) * 4) * 8192), "l"(&prm.wdn), "r"(BAR(B_DN)), "r"(eb * 2), "r"(i * 2 - 2), "l"(pol<3>()) : "memory");
        }
      }
    }
    asm volatile("" ::: "memory");
    if (warp == 1) {
      if (elect_one()) {
#pragma unroll 1
        for (int kk = 0; kk < 4; kk++) {
          mbar_wait(BAR(B_PREADY + kk), 0);
#pragma unroll 1
          for (int i = 0; i < 4; i++) {
            tma_store_2d(&prm.ps, sb + pstage(kk) + i * 4096, m4 * 256 + kk * 64, j * S_ + t * 128 + i * 32);
            if (kk >= FK_PS0 && i < 3) { const unsigned next = clk32() + FK_PSPACE; while ((int)(clk32() - next) < 0) __nanosleep(20); }
          }
          bulk_commit(); bulk_wait<0>();
          if (kk < 2) mbar_arrive(BAR(B_PS + kk));
          rel_fence<3>();
          st_rlx(&S->flagP[b * 32 + kk], tag);
          TRACE(40 + kk); TRACE3(128 + kk);
        }
        prefetch_tmap(&prm.om);
        if (FK_XD) { const unsigned next = clk32() + FK_XD; while ((int)(clk32() - next) < 0) __nanosleep(20); }
        mbar_expect_tx(BAR(B_EFULL), (FK_X & 4) ? 0 : 32768);
#pragma unroll 1
        for (int i = 0; i < 8; i++) {
          if (!(FK_X & 4)) tma_3d(sb + E_OFF + i * 4096, &prm.xm, t * 128 + i * 16, cgrp * 2, BAR(B_EFULL), pol<8>());
          const unsigned next = clk32() + FK_SPACE;
          while ((int)(clk32() - next) < 0) __nanosleep(20);
        }
      }
      __syncwarp();
      mbar_wait(BAR(B_PREADY), 1);
      const int lr = lds32u(sb + BK_OFF + (lane >> 4) * 4);
      {
        const uint4 v = lds128u(sb + E_OFF + (lr >> 4) * 4096 + (lane & 8) * 256 + (lr & 15) * 128 + (((lane ^ lr) & 7) << 4));
        st_msg(&S->rowsB[(t * 2 + (lane >> 4)) * 128 + cgrp * 16 + (lane & 15)], v.x, v.y, v.z, v.w);
      }
      const unsigned cmask = __reduce_or_sync(~0u, 1u << (lr >> 4));
      int r1 = -1, r2 = -1;
      unsigned next = clk32() + (m4 * 2 + rank) * (FK_OSPACE / 8);
#pragma unroll 1
      for (int i = 0; i < 16; i++) {
        if (i == 8) { mbar_wait(BAR(B_SEL), 0); r1 = lds32u(sb + SEL_OFF); r2 = lds32u(sb + SEL_OFF + 4); }
        if (((cmask >> (i & 7)) & 1) != (i >> 3)) continue;
        while ((int)(clk32() - next) < 0) {}
        next += FK_OSPACE;
        const uint32_t slab = sb + E_OFF + (i & 7) * 4096;
        const int row = t * 128 + (i & 7) * 16;
        if ((r1 >> 4) != (row >> 4) && (r2 >> 4) != (row >> 4)) {
          if (elect_one()) asm volatile("cp.async.bulk.tensor.3d.global.shared::cta.bulk_group [%0, {0, %2, %3}], [%1];" ::"l"(&prm.om), "r"(slab), "r"(row), "r"(cgrp * 2) : "memory");
        } else {
#pragma unroll 1
          for (int r = lane >> 4; r < 16; r += 2) {
            const uint4 v = lds128u(slab + (lane & 8) * 256 + r * 128 + (((lane ^ r) & 7) << 4));
            if (row + r != r1 && row + r != r2) reinterpret_cast<uint4*>(out + (size_t)(row + r) * D_)[cgrp * 16 + (lane & 15)] = v;
          }
        }
      }
      if (elect_one()) { bulk_commit(); bulk_wait_read<0>(); TRACE(29); }
    }
    asm volatile("" ::: "memory");
    if (warp == 3) {
      if (elect_one()) {
        fence_async_smem();
        unsigned next = clk32();
#pragma unroll 1
        for (int n = 0; n < 4 + FK_NA; n++) {
          if (n < 4) weight_box(n, BAR(B_WF)); else prefetch_piece(n);
          if (n == 3) mbar_arrive(BAR(B_WF));
          if (!FK_TX && (unsigned)(n - FK_XN) < 4u) pf_bulk(x + (size_t)(b * 16 + (n - FK_XN) * 4) * D_, 8192);
          next += FK_PACE;
          while ((int)(clk32() - next) < 0) __nanosleep(20);
        }
        TRACE(37);
      }
      __syncwarp();
      int it = 0;
      wait_cnt(&S->cntMod[32], tag * 128u);
      mbar_wait(BAR(B_PREADY + 2), 0);
      {
        const float* mp = S->mod[tag & 1] + cgrp * 128 + lane * 4;
        const float4 ga = ldg_cg(mp + 2 * D_), sv = ldg_cg(mp + 3 * D_), cb = ldg_cg(mp + 4 * D_), gb = ldg_cg(mp + 5 * D_);
        const uint2 wr = __ldg(reinterpret_cast<const uint2*>(prm.w_r + cgrp * 128 + lane * 4));
        const uint32_t Aa = add_bf16x2(pack_bf16(cb.x, cb.y), 0x3F803F80u), Ab = add_bf16x2(pack_bf16(cb.z, cb.w), 0x3F803F80u);
        const uint32_t Sa = pack_bf16(sv.x, sv.y), Sb = pack_bf16(sv.z, sv.w), Ga = pack_bf16(gb.x, gb.y), Gb = pack_bf16(gb.z, gb.w);
        const float w0 = bf_lo(Aa) * bf_lo(wr.x), w1 = bf_hi(Aa) * bf_hi(wr.x), w2 = bf_lo(Ab) * bf_lo(wr.y), w3 = bf_hi(Ab) * bf_hi(wr.y);
        const uint32_t tb = sb + TAB_OFF + (lane >> 3) * 64 + (lane & 1) * 32 + ((lane >> 1) & 3) * 4, Wa = pack_bf16(w0, w1), Wb = pack_bf16(w2, w3);
        auto put = [&](int off, uint32_t a, uint32_t c) { sts32v(tb + off, a); sts32v(tb + off + 16, c); };
        put(T_WH, Wa, Wb); put(T_ONE, 0x3F803F80u, 0x3F803F80u);
        put(T_WL, pack_bf16(w0 - bf_lo(Wa), w1 - bf_hi(Wa)), pack_bf16(w2 - bf_lo(Wb), w3 - bf_hi(Wb)));
        put(T_GA, pack_bf16(ga.x, ga.y), pack_bf16(ga.z, ga.w)); put(T_A, Aa, Ab); put(T_S, Sa, Sb); put(T_G, Ga, Gb);
        float c1 = (w0 + w1) + (w2 + w3), c2 = (bf_lo(Sa) * bf_lo(wr.x) + bf_hi(Sa) * bf_hi(wr.x)) + (bf_lo(Sb) * bf_lo(wr.y) + bf_hi(Sb) * bf_hi(wr.y));
#pragma unroll 1
        for (int h = 0; h < 2; h++) {
#pragma unroll
          for (int o = 16; o; o >>= 1) { c1 += __shfl_xor_sync(~0u, c1, o); c2 += __shfl_xor_sync(~0u, c2, o); }
          if (h) break;
          if (t == 0 && lane == 0) st_msg(&S->cst[cgrp], __float_as_uint(c1), __float_as_uint(c2), tag, 0);
          uint4 cm; it = 0;
          while (true) {
            cm = ld_msg(&S->cst[lane & 7]);
            if (__all_sync(~0u, cm.z == tag)) break;
            SPIN_CHECK(it); __nanosleep(200);
          }
          c1 = 0.25f * __uint_as_float(cm.x); c2 = 0.25f * __uint_as_float(cm.y);
        }
        if (lane == 0) { sts128u(sb + CST_OFF, __float_as_uint(c1), __float_as_uint(c2), tag, b | eb << 8 | (int)moe << 16); TRACE(27); }
      }
      uint32_t rk[16];
#pragma unroll
      for (int h = 0; h < 2; h++) {
        const uint2* src = (h ? &S->u[cgrp * 128] : &S->rs[t * 128]) + lane;
        uint2 m[8]; it = 0;
        while (true) {
          bool ok = true;
#pragma unroll
          for (int i = 0; i < 8; i++) { m[i] = ld_msg8(src + (i >> 1) * 32 + (i & 1) * (h ? D_ : S_)); ok &= m[i].y == tag; }
          if (ok) break;
          SPIN_CHECK(it);
        }
#pragma unroll
        for (int i = 0; i < 4; i++) {
          const float r0 = __uint_as_float(m[2 * i].x) * (h ? 0.5f : 1.f), r1 = __uint_as_float(m[2 * i + 1].x) * (h ? 0.5f : 1.f);
          const uint32_t hi = pack_bf16(r0, r1);
          rk[h * 8 + 2 * i] = hi; rk[h * 8 + 2 * i + 1] = pack_bf16(r0 - bf_lo(hi), r1 - bf_hi(hi));
        }
      }
      mbar_wait(BAR(B_B27), 0);
#pragma unroll
      for (int i = 0; i < 4; i++) {
        sts128u(sb + RKA_OFF + (i * 32 + lane) * 16, rk[2 * i], rk[2 * i], rk[2 * i + 1], 0);
        sts128u(sb + RKB_OFF + (i * 32 + lane) * 16, rk[8 + 2 * i], rk[9 + 2 * i], rk[8 + 2 * i], 0);
      }
      fence_async_smem();
      __syncwarp();
      if (lane == 0) { mbar_arrive(BAR(B_TAB)); TRACE(26); }
    }
    asm volatile("" ::: "memory");
    if (warp == 2) {
      const uint4* cp = &S->cand[(lane >> 1) * 8];
      mbar_wait(BAR(B_B27), 0);
      uint4 m = ld_msg(cp);
      bool ok = __all_sync(~0u, m.z == tag);
      named_bar<5, 288>();
      uint32_t k1, k2;
      {
        const uint4 k4 = lds128u(sb + KEY_OFF + lane * 16);
        const uint32_t ka = max(k4.x, k4.y), kb = max(k4.z, k4.w), m1 = max(ka, kb), m2 = max(min(ka, kb), ka > kb ? min(k4.x, k4.y) : min(k4.z, k4.w));
        k1 = redux_max(m1); k2 = redux_max(m1 == k1 ? m2 : m1);
        if (lane == 0) { st_msg(&S->cand[t * 8], k1, k2, tag, 0); sts64u(sb + BK_OFF, key_row(k1) & 127, key_row(k2) & 127); mbar_arrive(BAR(B_BK)); TRACE(13); }
      }
      int it = 0;
      while (!ok) {
        m = ld_msg(cp);
        ok = __all_sync(~0u, m.z == tag);
        SPIN_CHECK(it);
      }
      warp_top2((lane & 1) ? m.y : m.x, k1, k2);
      const int r1 = key_row(k1), r2 = key_row(k2), slot1 = (r1 >> 7) * 2, slot2 = (r2 >> 7) * 2 + ((r1 >> 7) == (r2 >> 7));
      if (lane == 0) { sts64u(sb + SEL_OFF, r1, r2); sts64u(sb + SEL_OFF + 8, slot1 * 2048, slot2 * 2048); mbar_arrive(BAR(B_SEL)); TRACE(14); }
      const int fcol = (b >> 1) * 16 + (lane & 15);
      const float gb = round_bf16(__uint_as_float(ld_rlx(S->mod[tag & 1] + 5 * D_ + fcol)));
      const uint32_t* fbp = reinterpret_cast<const uint32_t*>(&S->rowsB[((b & 1) ? slot2 : slot1) * 128]) + (fcol >> 1);
      uint32_t fb;
      do { fb = ld_rlx(fbp); SPIN_CHECK(it); } while (fb == SENT);
      sts64u(sb + PFLAG_OFF + (lane & 15) * 8, (lane & 1) ? fb & 0xFFFF0000u : fb << 16, __float_as_uint(gb));
      __syncwarp();
      if (lane == 0) {
        sts32(sb + CST_OFF, round_bf16(sigmoid_f(round_bf16(fkey_inv((((b & 1) ? k2 : k1) & ~2047u) | 1024u)))));
        mbar_arrive(BAR(B_FIN));
        if (b == 0) S->epoch[0] = tag;
      }
    }
  } else {
    const int cw = (warp - 4) >> 2;
    const int cwarp = warp - 4;
    const bool elect = (tid & 127) == 0;
    uint32_t rel;
    asm volatile("mapa.shared::cluster.u32 %0, %1, %2;" : "=r"(rel) : "r"(BAR(0)), "r"(tid & 1));
    if (tid & 126) rel = 0;
    asm volatile("" : "+r"(rel));
    auto release = [&](int bar) {
      asm volatile("{\n.reg .pred p;\nsetp.ne.u32 p, %1, 0;\n@p mbarrier.arrive.shared::cluster.b64 _, [%0];\n}" ::"r"(rel + bar * 8), "r"(rel) : "memory");
    };
    const uint32_t da0 = desc_lo(sb + cw * 8192, 16), db0 = desc_lo(sb + SLOT, 8192), db2 = desc_lo(sb + SLOT, 16);
    asm volatile("barrier.cluster.wait.acquire.aligned;" ::: "memory");

    uint32_t wf[64], uf[64], df[64];
    uint32_t pk[64];
    uint32_t xw[32];
    float lo[64];
    int ln;
    uint32_t so, wo;
    auto p_ready = [&](int kk) { fence_async_smem(); if (elect_one()) mbar_arrive(BAR(B_PREADY + kk)); };
    {
      float pa[64], pb[64];
      {
        float acc[128];
#pragma unroll 1
        for (int g = 0; g < 28; g++) {
          const int s = g & 3;
          mbar_wait(BAR(B_FULL + s), (g >> 2) & 1);
          const uint32_t da = da0 + s * (STAGE >> 4), db = db0 + s * (STAGE >> 4);
          wg_fence();
          wgmma_n256<1>(acc, da, db, g > 0);
#pragma unroll
          for (int k = 1; k < 4; k++) wgmma_n256<1>(acc, da + k * 2, db + k * 128, 1);
          wg_commit();
          wg_wait<1>();
          if (g > 0) { release(B_EMPTY + ((g - 1) & 3)); if (elect) TRACE2(191 + g + cw * 32); }
          STAMP2(g);
        }
        wg_wait<0>();
        release(B_EMPTY + 3);
#pragma unroll
        for (int i = 0; i < 64; i++) {
          asm volatile("mov.b32 %0, %1;" : "=f"(pa[i]) : "f"(acc[i]));
          asm volatile("mov.b32 %0, %1;" : "=f"(pb[i]) : "f"(acc[64 + i]));
        }
      }
      if (elect) TRACE(3 + tr);
      STAMP2(28);
#pragma unroll 1
      for (int s = 0; s < 4; s++) {
        mbar_wait(BAR(B_FULL + s), 1);
        wg_fence();
#pragma unroll
        for (int k = 0; k < 4; k++) wgmma_n128<1>(pa, da0 + s * (STAGE >> 4) + k * 2, db0 + s * (STAGE >> 4) + k * 128);
        wg_commit();
        if (s == 2) { wg_wait<1>(); if (elect) mbar_arrive(BAR(B_A29)); }
      }
      auto b_block = [&](int s) {
        wg_fence();
#pragma unroll
        for (int k = 0; k < 4; k++) wgmma_n128<1>(pb, da0 + s * (STAGE >> 4) + k * 2, db0 + s * (STAGE >> 4) + 1024 + k * 128);
        wg_commit();
      };
      uint4 t0, t1;
      auto load_t = [&](int kk) { t0 = lds128u(sb + T1_OFF + kk * 128 + (ln & 3) * 16); t1 = lds128u(sb + T1_OFF + kk * 128 + 64 + (ln & 3) * 16); };
      auto pack_p = [&](int kk, const float* a) {
        const uint32_t A[8] = {t0.x, t0.y, t0.z, t0.w, t1.x, t1.y, t1.z, t1.w};
#pragma unroll
        for (int i = 0; i < 16; i++) pk[kk * 16 + i] = mul_bf16x2(pack_bf16(a[2 * i], a[2 * i + 1]), A[i >> 1]);
      };
      auto stage_p = [&](int kk) {
#pragma unroll
        for (int k = 0; k < 4; k++) stsm_x4((so ^ (k << 5)) + pstage(kk), pk + kk * 16 + k * 4);
      };
      auto own_block = [&](int q) {
        const uint32_t db = db2 + (buf_off(q) >> 4);
        wg_fence();
        if (q == 0) wgmma_n128_rs<0>(lo, pk, db); else wgmma_n128_rs<1>(lo, pk + q * 16, db);
#pragma unroll
        for (int k = 1; k < 4; k++) wgmma_n128_rs<1>(lo, pk + q * 16 + k * 4, db + k * 2);
        wg_commit();
      };
      b_block(0);
      mbar_wait(BAR(B_RSDONE), 0);
      asm volatile("setmaxnreg.inc.sync.aligned.u32 232;" ::: "memory");
      asm volatile("mov.u32 %0, %%laneid;" : "=r"(ln));
      so = sb + (uint32_t)(cwarp * 16 + (ln & 15)) * 128 + (((ln >> 4) ^ (ln & 7)) << 4);
      wo = sb + SP_OFF + cwarp * 1024 + ((ln & 7) + (ln >> 4) * 8) * 64 + ((((ln >> 3) & 1) ^ ((ln >> 1) & 3)) << 4);
      mbar_wait(BAR(B_A29), 0);
      load_t(0);
      wg_wait<1>();
      reg_fence(pa);
      release(B_ADONE);
      if (elect) TRACE(4 + tr);
      STAMP2(29);
      pack_p(0, pa); stage_p(0);
      if (FK_TR0) { p_ready(0); b_block(1); } else { b_block(1); p_ready(0); }
      if (elect) TRACE(2 + tr);
      wg_wait<1>(); release(B_EMPTY);
      load_t(1);
      b_block(2);
      pack_p(1, pa + 32);
      wg_wait<1>(); release(B_EMPTY + 1);
      STAMP2(30);
      load_t(2);
      b_block(3);
      mbar_wait(BAR(B_FULL2), 0);
      wg_wait<1>(); release(B_EMPTY + 2);
      if (FK_S1 == 0) { mbar_wait(BAR(B_ADONE), 0); stage_p(1); }
      own_block(0);
      if (FK_S1 == 0) p_ready(1);
      mbar_wait(BAR(B_FULL2 + 1), 0);
      if (FK_S1 == 1) mbar_wait(BAR(B_ADONE), 0);
      wg_wait<1>(); release(B_EMPTY + 3);
      reg_fence(pb);
      if (elect) TRACE(1 + tr);
      STAMP2(31);
      if (FK_S1 == 1) stage_p(1);
      own_block(1);
      if (FK_S1 == 1) p_ready(1);
      pack_p(2, pb);
      mbar_wait(BAR(B_FULL2 + 2), 0);
      wg_wait<1>(); release(B_EMPTY2);
      STAMP2(32);
      load_t(3);
      own_block(2);
      pack_p(3, pb + 32);
      mbar_wait(BAR(B_EMPTY + 3), 1);
      mbar_wait(BAR(B_FULL2 + 3), 0);
      wg_wait<1>(); release(B_EMPTY2 + 1);
      STAMP2(33);
      if (FK_S1 == 3) stage_p(1);
      own_block(3);
      if (FK_S1 == 3) p_ready(1);
      mbar_wait(BAR(B_WF), 0);
      wg_wait<1>(); release(B_EMPTY2 + 2);
      STAMP2(34);
    }
    {
      mbar_wait(BAR(B_FULL2 + 4), 0);
#pragma unroll
      for (int q = 4; q < 32; q++) {
        const uint32_t da = da0 + (buf_off(q % 5) >> 4) + (q << 16), db = db2 + (buf_off(q % 5) >> 4) + (q << 16);
        wg_fence();
#pragma unroll
        for (int k = 0; k < 4; k++) wgmma_n128<0>(lo, da + k * 2, db + k * 2);
        wg_commit();
        if (q == 31) break;
        if (FK_ORD == 1) { wg_wait<1>(); if (q == 28 && rel) rel = BAR(0); release(B_EMPTY2 + (q - 1) % 5); STAMP2(31 + q); }
        if (q == 8 || q == 14) p_ready(q >> 2);
        if (q == 27) mbar_wait(BAR(B_EFULL), 0);
        mbar_wait(BAR(B_FULL2 + (q + 1) % 5), ((q + 1) / 5) & 1);
        if (q >= 27) {
#pragma unroll
          for (int h = 0; h < 2; h++) ldsm_x4((so ^ ((q - 27) << 5)) + E_OFF + cwarp * 2048 + h * 2048, xw + (q - 27) * 4 + h * 16);
        } else if (!(q & 1)) {
          const int n = (q - 4) >> 1;
#pragma unroll
          for (int h = 0; h < 2; h++) ldsm_x4_t((wo ^ (h << 5)) + (n & 3) * 8192, (n < 8 ? wf + n * 8 : uf + (n - 8) * 8) + h * 4);
        } else if (q < 15 && q != 9) {
          const int i = (q - 5 - (q > 9) * 2) >> 1;
#pragma unroll
          for (int h = 0; h < 2; h++) stsm_x4((so ^ (((i & 1) * 2 + h) << 5)) + pstage(2 + (i >> 1)), pk + 32 + i * 8 + h * 4);
        }
        if (FK_ORD == 0) { wg_wait<1>(); if (q == 28 && rel) rel = BAR(0); release(B_EMPTY2 + (q - 1) % 5); STAMP2(31 + q); }
      }
    }
    mbar_wait(BAR(B_TAB), 0);
    wg_fence();
    wgmma_n128<0, 8>(lo, desc_lo(sb + RKA_OFF, 0) + (cwarp & 4) * 16, desc_lo(sb + RKB_OFF, 0));
    wg_commit();
    const int gq = ln >> 2, q4 = ln & 3, row0 = cwarp * 16 + gq;
    const bool odd = ln & 1;
    const uint32_t role = lds32u(sb + CST_OFF + 12), bq = role & 255;
    uint32_t tq = sb + TAB_OFF + q4 * 16, tb = tq + (gq & 1) * T_ONE + (gq & 2) * (T_WL / 2);
    const uint4* src = &S->stats[((bq & ~7) + (q4 >> 1) * 4) * 128 + row0 + 8 * (q4 & 1)];
    uint4* sdst = &S->stats[bq * 128 + row0 + 8 * q4];
    asm volatile("" : "+r"(tq), "+r"(tb), "+l"(src), "+l"(sdst));
    {
      uint4 gw[4];
#pragma unroll
      for (int a = 0; a < 4; a++) gw[a] = lds128u(tq + T_GA + a * 64);
      wg_wait<0>();
      reg_fence(lo);
      STAMP(0);
      if (elect) { TRACE(7 + tr); if (cw == 0) TRACE_CLK(121); }
      float c[2][4], e0[2][4], e1[2][4];
#pragma unroll
      for (int i = 0; i < 4; i++) c[0][i] = c[1][i] = e0[0][i] = e0[1][i] = e1[0][i] = e1[1][i] = 0.f;
#pragma unroll
      for (int a = 0; a < 4; a++) {
        const uint4 bw = lds128u(tb + a * 64);
        const uint32_t g[4] = {gw[a].x, gw[a].y, gw[a].z, gw[a].w};
#pragma unroll
        for (int i = 0; i < 8; i++) xw[a * 8 + i] = fma_bf16x2(g[i >> 1], pack_bf16(lo[a * 16 + 2 * i], lo[a * 16 + 2 * i + 1]), xw[a * 8 + i]);
#pragma unroll
        for (int h = 0; h < 2; h++) {
          const uint32_t* w = xw + a * 8 + h * 4;
          mma_1688(e0[0], w[0], w[1], w[0]); mma_1688(e1[0], w[0], w[1], w[1]); mma_1688(e0[1], w[2], w[3], w[2]); mma_1688(e1[1], w[2], w[3], w[3]);
          mma_16816(c[h], w, h ? bw.z : bw.x, h ? bw.w : bw.y);
        }
      }
      const float c0 = c[0][0] + c[1][0], c2 = c[0][2] + c[1][2];
      const float q0 = (gq & 1) ? e0[0][1] + e0[1][1] : e0[0][0] + e0[1][0], q1 = (gq & 1) ? e1[0][3] + e1[1][3] : e1[0][2] + e1[1][2];
      const int dl = (ln & ~3) | (gq >> 1);
      const float da = (odd ? c2 : c0) + __shfl_xor_sync(~0u, odd ? c0 : c2, 1), s1 = __shfl_xor_sync(~0u, c[0][3] + c[1][3], 1);
      const float qa = __shfl_sync(~0u, q0, dl), qb = __shfl_sync(~0u, q1, dl);
      if (q4 < 2) st_msg(sdst, __float_as_uint(odd ? s1 : c[0][1] + c[1][1]), __float_as_uint(odd ? qb : qa), __float_as_uint(da), 0);
    }
    if (elect) TRACE(8 + tr);
    STAMP(1);
    {
      uint4 m[4], tA[4], tS[4];
      mbar_wait(BAR(B_WF), 1);
#pragma unroll
      for (int i = 0; i < 4; i++) m[i] = ld_msg(src + 128 * i);
      const float2 cst = lds64(sb + CST_OFF);
#pragma unroll
      for (int i = 0; i < 8; i++) ldsm_x4_t((wo ^ ((i & 1) << 5)) + (i >> 1) * 8192, uf + 32 + i * 4);
#pragma unroll
      for (int a = 0; a < 4; a++) { tA[a] = lds128u(tq + T_A + a * 64); tS[a] = lds128u(tq + T_S + a * 64); }
      uint32_t kaddr = sb + KEY_OFF + (row0 + 8 * (q4 & 1)) * 4, kidx = 2047 - ((bq >> 3) * 128 + row0 + 8 * (q4 & 1));
      asm volatile("" : "+r"(kaddr), "+r"(kidx));
      STAMP(2);
      int it = 0;
      while (!__all_sync(~0u, (m[0].w | m[1].w | m[2].w | m[3].w) == 0)) {
#pragma unroll
        for (int i = 0; i < 4; i++) m[i] = ld_msg(src + 128 * i);
        SPIN_CHECK(it);
      }
      STAMP(3);
      float sa = (__uint_as_float(m[0].x) + __uint_as_float(m[1].x)) + (__uint_as_float(m[2].x) + __uint_as_float(m[3].x));
      float qa = (__uint_as_float(m[0].y) + __uint_as_float(m[1].y)) + (__uint_as_float(m[2].y) + __uint_as_float(m[3].y));
      float da = (__uint_as_float(m[0].z) + __uint_as_float(m[1].z)) + (__uint_as_float(m[2].z) + __uint_as_float(m[3].z));
      sa += __shfl_xor_sync(~0u, sa, 2); qa += __shfl_xor_sync(~0u, qa, 2); da += __shfl_xor_sync(~0u, da, 2);
      const float mean = sa * (1.f / D_);
      const float rs = rsqrt_f(fmaxf(fmaf(-mean, mean, qa * (1.f / D_)), 0.f) + 1e-5f);
      sts32v(kaddr, (fkey(fmaf(rs, fmaf(-mean, cst.x, da), cst.y)) & ~2047u) | kidx);
      uint32_t one;
      asm volatile("bar.arrive 5, 288;\nld.volatile.shared.u32 %0, [%1];" : "=r"(one) : "r"(sb + TAB_OFF + T_ONE) : "memory");
      if (tid == 128) TRACE(12 + 16);
      STAMP(4);
      const uint32_t h0 = pack_bf16(rs, rs), l0 = mul_bf16x2(pack_bf16(rs - bf_lo(h0), -mean * rs), one), hx = __shfl_xor_sync(~0u, h0, 1), lx = __shfl_xor_sync(~0u, l0, 1);
      const uint32_t rh[2] = {odd ? hx : h0, odd ? h0 : hx};
      const uint32_t rl[2] = {__byte_perm(odd ? lx : l0, 0, 0x1010), __byte_perm(odd ? l0 : lx, 0, 0x1010)};
      const uint32_t nm[2] = {__byte_perm(odd ? lx : l0, 0, 0x3232), __byte_perm(odd ? l0 : lx, 0, 0x3232)};
      uint32_t h[32];
#pragma unroll
      for (int a = 0; a < 4; a++) {
        const uint32_t A[4] = {tA[a].x, tA[a].y, tA[a].z, tA[a].w}, B[4] = {tS[a].x, tS[a].y, tS[a].z, tS[a].w};
#pragma unroll
        for (int i = 0; i < 8; i++) {
          const uint32_t w = xw[a * 8 + (i & 3) * 2 + (i >> 2)];
          h[a * 8 + i] = fma_bf16x2(fma_bf16x2(w, rh[i >> 2], fma_bf16x2(w, rl[i >> 2], nm[i >> 2])), A[i & 3], B[i & 3]);
        }
      }
      uint4* cp = &S->rowsH[(bq >> 3) * 256 + (bq & 7) * 16 + q4];
#pragma unroll
      for (int i = 0; i < 32; i++) asm volatile("" : "+r"(h[i]));
      asm volatile("" : "+l"(cp));
      mbar_wait(BAR(B_BK), 0);
      STAMP(5);
      const float2 bk = lds64(sb + BK_OFF);
#pragma unroll
      for (int r = 0; r < 2; r++) {
        const bool second = row0 + 8 * r == __float_as_int(bk.y);
        if (second || row0 + 8 * r == __float_as_int(bk.x)) {
#pragma unroll
          for (int a = 0; a < 4; a++) st_msg(cp + (second ? 128 : 0) + a * 4, h[a * 8 + r * 4], h[a * 8 + r * 4 + 1], h[a * 8 + r * 4 + 2], h[a * 8 + r * 4 + 3]);
        }
      }
      mbar_wait(BAR(B_DN), 0);
#pragma unroll
      for (int a = 0; a < 4; a++) {
        const uint4 tG = lds128u(tq + T_G + a * 64);
        const uint32_t G[4] = {tG.x, tG.y, tG.z, tG.w};
#pragma unroll
        for (int i = 0; i < 8; i++) xw[a * 8 + i] = fma_bf16x2(G[i >> 1], h[a * 8 + (i & 1) * 4 + (i >> 1)], xw[a * 8 + i]);
#pragma unroll
        for (int k = 0; k < 2; k++) stsm_x4((so ^ ((((a & 1) * 2) + k) << 5)) + E_OFF + cwarp * 2048 + (a >> 1) * 2048, xw + a * 8 + k * 4);
      }
    }
    fence_async_smem();
    if (elect_one()) mbar_arrive(BAR(B_PREADY));
    STAMP(6);
    if (tid == 128) TRACE(15);
    if (role >> 16) {
      const char* hp = reinterpret_cast<const char*>(&S->rowsH[(cwarp >> 1) * 4 + q4]) + (cwarp & 1) * 8;
      uint32_t db = sb + DN_OFF + (cwarp + (cwarp == 7) * 4) * 8192 + ((ln & 7) + (ln >> 4) * 8) * 128 + ((((ln >> 3) & 1) ^ (ln & 7)) << 4), sa = sb + SEL_OFF + 8 + (gq & 1) * 4;
      asm volatile("" : "+l"(hp), "+r"(db), "+r"(sa));
      STAMP(7);
      mbar_wait(BAR(B_SEL), 0);
      STAMP(8);
      { const uint32_t off = lds32u(sa); hp += off; db += off >> 31; }
      uint2 hb[8];
#pragma unroll
      for (int i = 0; i < 8; i++) hb[i] = ld_msg8(hp + i * 256);
      STAMP(9);
#pragma unroll
      for (int i = 0; i < 16; i++) ldsm_x4_t((db ^ (((i >> 1) & 3) << 5)) + (i >> 3) * 4096 + (i & 1) * 2048, df + i * 4);
      int it = 0;
      while (!__all_sync(~0u, max(max(max(hb[0].x, hb[1].x), max(hb[2].x, hb[3].x)), max(max(hb[4].x, hb[5].x), max(hb[6].x, hb[7].x))) != SENT)) {
#pragma unroll
        for (int i = 0; i < 8; i++) hb[i] = ld_msg8(hp + i * 256);
        SPIN_CHECK(it);
      }
      if (tid == 128) TRACE(16);
      STAMP(10);
      float c[4][4];
#pragma unroll
      for (int i = 0; i < 4; i++) c[i][0] = c[i][1] = c[i][2] = c[i][3] = 0.f;
#pragma unroll
      for (int ks = 0; ks < 8; ks++) {
        const uint32_t b0 = hb[ks].x, b1 = hb[ks].y;
        mma_16816(c[0], wf + ks * 8, b0, b1); mma_16816(c[1], wf + ks * 8 + 4, b0, b1);
        mma_16816(c[2], uf + ks * 8, b0, b1); mma_16816(c[3], uf + ks * 8 + 4, b0, b1);
      }
      {
        float v[4];
#pragma unroll
        for (int i = 0; i < 4; i++) v[i] = (q4 & 2) ? (odd ? c[3][i] : c[2][i]) : (odd ? c[1][i] : c[0][i]);
        sts128(sb + RED_OFF + cwarp * 512 + (q4 * 8 + (gq ^ (q4 * 2))) * 16, v[0], v[2], v[1], v[3]);
      }
      uint2* pp = reinterpret_cast<uint2*>(&S->part[((cwarp * 16 + q4 * 2) * 128 + ((role >> 8) & 255)) * 4]) + gq;
      uint32_t ra = sb + RED_OFF + ((ln * 8) ^ ((ln & 16) * 2));
      asm volatile("" : "+l"(pp), "+r"(ra));
      STAMP(11);
      named_bar<2, 256>();
      STAMP(12);
      float g0 = 0.f, g1 = 0.f, u0 = 0.f, u1 = 0.f;
#pragma unroll
      for (int w = 0; w < 8; w++) {
        const float2 gv = lds64(ra + w * 512), uv = lds64((ra ^ 64) + w * 512 + 256);
        g0 += gv.x; g1 += gv.y; u0 += uv.x; u1 += uv.y;
      }
      const uint32_t gp = pack_bf16(g0, g1), up = pack_bf16(u0, u1), sp = pack_bf16(silu_f(bf_lo(gp)), silu_f(bf_hi(gp)));
      const uint32_t act = pack_bf16(bf_lo(sp) * bf_lo(up), bf_hi(sp) * bf_hi(up));
      uint32_t ab[4];
#pragma unroll
      for (int i = 0; i < 4; i++) ab[i] = __shfl_sync(~0u, act, i * 8 + q4 * 2 + (gq & 1));
      if (tid == 128) TRACE(31);
      STAMP(13);
#pragma unroll
      for (int T = 0; T < 2; T++) {
#pragma unroll
        for (int i = 0; i < 4; i++) {
          c[i][0] = c[i][1] = c[i][2] = c[i][3] = 0.f;
          mma_16816(c[i], df + (T * 4 + i) * 8, ab[0], ab[1]); mma_16816(c[i], df + (T * 4 + i) * 8 + 4, ab[2], ab[3]);
        }
        float v[4];
#pragma unroll
        for (int i = 0; i < 4; i++) v[i] = (q4 & 2) ? (odd ? c[3][i] : c[2][i]) : (odd ? c[1][i] : c[0][i]);
        st_msg8(pp + T * 8192, __float_as_uint(v[0]), __float_as_uint(v[2])); st_msg8(pp + T * 8192 + 1024, __float_as_uint(v[1]), __float_as_uint(v[3]));
      }
      if (tid == 128) TRACE(32);
      STAMP(14);
    }
    if (cwarp == 0) {
      const unsigned t0 = clk32();
      mbar_wait(BAR(B_FIN), 0);
      const int fc = q4 * 2 + ((ln >> 2) & 1) + (ln & 8);
      const float2 fo = lds64(sb + PFLAG_OFF + fc * 8);
      const float sg = __uint_as_float(lds32u(sb + CST_OFF));
      __nv_bfloat16* op = out + (size_t)lds32u(sb + SEL_OFF + (bq & 1) * 4) * D_ + (bq >> 1) * 16 + fc;
      const uint4* ip = &S->part[bq * 512 + ln];
      asm volatile("" : "+l"(op), "+l"(ip));
      if (role >> 16) { while (clk32() - t0 < FK_PDELAY) {} } else spin(FK_PDELAY + 600);
      int it = 0;
      uint4 m[14];
      while (true) {
        bool ok = true;
#pragma unroll
        for (int i = 0; i < 14; i++) { m[i] = ld_msg(ip + i * 32); ok &= m[i].x != SENT && m[i].z != SENT; }
        if (__all_sync(~0u, ok)) break;
        SPIN_CHECK(it);
      }
      if (lane == 0) TRACE(33);
      STAMP(15);
      float y[4] = {0.f, 0.f, 0.f, 0.f};
#pragma unroll
      for (int i = 0; i < 14; i++) { y[0] += __uint_as_float(m[i].x); y[1] += __uint_as_float(m[i].y); y[2] += __uint_as_float(m[i].z); y[3] += __uint_as_float(m[i].w); }
      const bool b2 = ln & 4;
      float y0 = (b2 ? y[2] : y[0]) + __shfl_xor_sync(~0u, b2 ? y[0] : y[2], 4), y1 = (b2 ? y[3] : y[1]) + __shfl_xor_sync(~0u, b2 ? y[1] : y[3], 4);
      y0 = ((ln & 8) ? y1 : y0) + __shfl_xor_sync(~0u, (ln & 8) ? y0 : y1, 8);
      y0 += __shfl_xor_sync(~0u, y0, 16);
      const float upd = round_bf16(round_bf16(y0) * sg);
      if (ln < 16) *op = __float2bfloat16_rn(fmaf(fo.y, upd, fo.x));
      if (lane == 0) {
        TRACE(34); TRACE_CLK(122);
      }
    }
  }
}

typedef CUresult (*PFN_encodeTiled)(CUtensorMap*, CUtensorMapDataType, cuuint32_t, void*, const cuuint64_t*, const cuuint64_t*,
                                    const cuuint32_t*, const cuuint32_t*, CUtensorMapInterleave, CUtensorMapSwizzle,
                                    CUtensorMapL2promotion, CUtensorMapFloatOOBfill);

static void mapnd(PFN_encodeTiled enc, CUtensorMap* m, const void* p, int nd, const cuuint64_t* dims, const cuuint64_t* str, const cuuint32_t* box,
                  CUtensorMapSwizzle sw, CUtensorMapL2promotion pr) {
  const cuuint32_t es[5] = {1, 1, 1, 1, 1};
  enc(m, CU_TENSOR_MAP_DATA_TYPE_BFLOAT16, nd, (void*)p, dims, str, box, es, CU_TENSOR_MAP_INTERLEAVE_NONE, sw, pr, CU_TENSOR_MAP_FLOAT_OOB_FILL_NONE);
}
static void map2d(PFN_encodeTiled enc, CUtensorMap* m, const void* p, uint64_t rows, uint64_t cols, uint32_t brows, uint32_t bcols,
                  CUtensorMapSwizzle sw = CU_TENSOR_MAP_SWIZZLE_128B, CUtensorMapL2promotion pr = CU_TENSOR_MAP_L2_PROMOTION_L2_128B) {
  const cuuint64_t dims[2] = {cols, rows}, str[1] = {cols * 2}; const cuuint32_t box[2] = {bcols, brows};
  mapnd(enc, m, p, 2, dims, str, box, sw, pr);
}
static void map3d(PFN_encodeTiled enc, CUtensorMap* m, const void* p, uint64_t rows, uint64_t cols, uint32_t brows, uint32_t bgroups) {
  const cuuint64_t dims[3] = {64, rows, cols / 64}, str[2] = {cols * 2, 128}; const cuuint32_t box[3] = {64, brows, bgroups};
  mapnd(enc, m, p, 3, dims, str, box, CU_TENSOR_MAP_SWIZZLE_128B, CU_TENSOR_MAP_L2_PROMOTION_L2_128B);
}

}

extern "C" void kernel_launch(void* const* d_in, const int* in_sizes, int n_in, void* d_out, int out_size) {
  using namespace fk;
  (void)in_sizes; (void)n_in; (void)out_size;
  static PFN_encodeTiled enc = nullptr;
  static Scratch* scr = nullptr;
  if (!enc) {
    void* fn = nullptr; cudaDriverEntryPointQueryResult qr;
    cudaGetDriverEntryPoint("cuTensorMapEncodeTiled", &fn, cudaEnableDefault, &qr);
    enc = (PFN_encodeTiled)fn;
    cudaGetSymbolAddress((void**)&scr, g_scr);
    cudaFuncSetAttribute(fused_kernel, cudaFuncAttributeMaxDynamicSharedMemorySize, SMEM_BYTES);
  }
  typedef const __nv_bfloat16* bp;
  Params prm;
  prm.w_r = (bp)d_in[6];
  prm.wsp[0] = (const char*)d_in[1]; prm.wsp[1] = (const char*)d_in[2];
  map2d(enc, &prm.ws[0], d_in[1], S_, S_, 128, 64);
  map2d(enc, &prm.ws[1], d_in[2], S_, S_, 128, 64);
  map3d(enc, &prm.n, scr->n, S_, D_, 64, 2);
  map2d(enc, &prm.wm, d_in[11], D_, 6 * D_, 8, 256, CU_TENSOR_MAP_SWIZZLE_NONE, CU_TENSOR_MAP_L2_PROMOTION_L2_256B);
  map2d(enc, &prm.p, scr->P, 2 * S_, D_, 128, 64);
  map2d(enc, &prm.wd[0], d_in[3], D_, D_, 64, 64);
  map2d(enc, &prm.wd[1], d_in[4], D_, D_, 64, 64);
  map2d(enc, &prm.wg, d_in[7], D_, F_, 128, 32, CU_TENSOR_MAP_SWIZZLE_64B);
  map2d(enc, &prm.wu, d_in[8], D_, F_, 128, 32, CU_TENSOR_MAP_SWIZZLE_64B);
  for (int i = 0; i < 3; i++) prm.we[i] = (const char*)d_in[7 + i];
  map2d(enc, &prm.ps, scr->P, 2 * S_, D_, 32, 64);
  for (int i = 0; i < 2; i++) {
    const cuuint64_t dims[3] = {128, 8, i ? 2048u : 3584u}, str[2] = {256, 2048}; const cuuint32_t box[3] = {8, 1, 32};
    mapnd(enc, &prm.tch[i], d_in[i ? 0 : 9], 3, dims, str, box, CU_TENSOR_MAP_SWIZZLE_NONE, CU_TENSOR_MAP_L2_PROMOTION_L2_256B);
  }
  map3d(enc, &prm.xm, d_in[0], S_, D_, 16, 2);
  map3d(enc, &prm.om, d_out, S_, D_, 16, 2);
  {
    const cuuint64_t dims[5] = {64, 2, 8, 224, 16}, str[4] = {8 * 2048, 2048, 16 * 2048, 128}; const cuuint32_t box[5] = {64, 2, 8, 2, 2};
    mapnd(enc, &prm.wdn, d_in[9], 5, dims, str, box, CU_TENSOR_MAP_SWIZZLE_128B, CU_TENSOR_MAP_L2_PROMOTION_L2_128B);
  }

  fused_kernel<<<NCTA, 384, SMEM_BYTES, cudaStreamPerThread>>>((bp)d_in[0], scr, (__nv_bfloat16*)d_out, (bp)d_in[10], (bp)d_in[3], (bp)d_in[4], prm);
}
```

```cpp
#include <cuda_runtime.h>
#include <cuda_bf16.h>
#include <cuda.h>
#include <stdint.h>

#define DEVINL __device__ __forceinline__

namespace fk {

constexpr int S_ = 2048, D_ = 1024, F_ = 3584;
constexpr int NCTA = 128;
constexpr int SLOT = 16384;
constexpr int STAGE = 3 * SLOT;
constexpr int BUF = 2 * SLOT;
constexpr int E_OFF = 5 * BUF;
constexpr int SP_OFF = 4 * STAGE;
constexpr int MISC_OFF = SP_OFF + 32768;
constexpr int SMEM_BYTES = MISC_OFF + 3072;
constexpr int BAR_OFF = MISC_OFF;
constexpr int SEL_OFF = MISC_OFF + 344;
constexpr int BK_OFF = MISC_OFF + 360;
constexpr int CST_OFF = MISC_OFF + 368;
constexpr int PFLAG_OFF = MISC_OFF + 384;
constexpr int TAB_OFF = MISC_OFF + 512;
enum { T_WH = 0, T_ONE = 320, T_WL = 576, T_GA = 896, T_A = 1152, T_S = 1408, T_G = 1664 };
constexpr int KEY_OFF = TAB_OFF + 2048;
constexpr int POLL_OFF = TAB_OFF + 256;
constexpr int T1_OFF = TAB_OFF + 1536;
constexpr int RKA_OFF = BUF;
constexpr int RKB_OFF = RKA_OFF + 2048;
constexpr int RED_OFF = RKB_OFF + 2048;
constexpr int DN_OFF = RED_OFF + 4096;

enum { B_FULL = 0, B_EMPTY = 4, B_PREADY = 8, B_MF = 12  , B_FULL2 = 20  , B_EMPTY2 = 25  , B_A29 = 30, B_ADONE = 31,
       B_RSDONE = 32, B_TAB = 33, B_B27 = 34, B_SEL = 35, B_DN = 36, B_EFULL = 37, B_PS = 38  , B_WF = 40, B_BK = 41, B_FIN = 42, B_NUM = 43 };
constexpr unsigned long long CNT0 = 0x1111888855551111ull, CNT1 = 0x4244444222221111ull, CNT2 = 0x1111111111111112ull;

#define FK_SKIP 0
#define FK_X 0
#define FK_PS0 1
#define FK_XN 0
#define FK_S1 0
#define FK_NL 15
#define FK_XD 0
#define FK_GS 1
#define FK_TD 0
#define FK_TX 1
#define FK_ODELAY 100
#define FK_OMASK 0
#define FK_OSPACE2 0
#define FK_REL 0x14
#define FK_WSPF 22
#define FK_SPACE 300
#define FK_OSPACE 200
#define FK_NOMC 4
#define FK_TR0 0
#define FK_G0 5
#define FK_NA 6
#define FK_PACE 800
#define FK_QP 3
#define FK_PSPACE 400
#define FK_ORD 0
#define FK_PDELAY 700
constexpr int SPIN_LIMIT = 1 << 20;
constexpr uint32_t SENT = 0xFFFFFFFFu;

struct Scratch {
  uint4 part[128 * 128 * 4];
  uint4 stats[128 * 128];
  uint4 rowsH[32 * 128];
  uint4 rowsB[32 * 128];
  uint4 cand[16 * 8];
  uint2 rs[2 * S_];
  uint4 cst[8];
  float mod[2][6 * D_];
  uint2 u[2 * D_];
  unsigned flagP[128 * 4 * 8];
  unsigned cntN[12 * 32];
  unsigned cntMod[2 * 32];
  unsigned epoch[32];
  alignas(1024) __nv_bfloat16 n[S_ * D_];
  __nv_bfloat16 P[2 * S_ * D_];
};
__device__ __align__(1024) Scratch g_scr;

struct Params {
  CUtensorMap ws[2];
  CUtensorMap n;
  CUtensorMap wm;
  CUtensorMap p;
  CUtensorMap wg, wu;
  CUtensorMap xm;
  CUtensorMap wdn;
  CUtensorMap wd[2];
  CUtensorMap om;
  CUtensorMap ps;
  CUtensorMap tch[2];
  const __nv_bfloat16* w_r;
  const char* wsp[2];
  const char* we[3];
};

DEVINL uint32_t smem_u32(const void* p) { return (uint32_t)__cvta_generic_to_shared(p); }
DEVINL void mbar_init(uint32_t bar, uint32_t cnt) { asm volatile("mbarrier.init.shared::cta.b64 [%0], %1;" ::"r"(bar), "r"(cnt) : "memory"); }
DEVINL void mbar_expect_tx(uint32_t bar, uint32_t bytes) { asm volatile("mbarrier.arrive.expect_tx.shared::cta.b64 _, [%0], %1;" ::"r"(bar), "r"(bytes) : "memory"); }
DEVINL void mbar_arrive(uint32_t bar) { asm volatile("mbarrier.arrive.shared::cta.b64 _, [%0];" ::"r"(bar) : "memory"); }
DEVINL void mbar_wait(uint32_t bar, uint32_t parity) {
  asm volatile("{\n.reg .pred p;\n.reg .u32 c;\nmov.u32 c, 0;\n"
               "LW:\nmbarrier.try_wait.parity.shared::cta.b64 p, [%0], %1;\n@p bra LD;\n"
               "add.u32 c, c, 1;\nsetp.lt.u32 p, c, 1048576;\n@p bra LW;\ntrap;\nLD:\n}" ::"r"(bar), "r"(parity) : "memory");
}
DEVINL void mbar_wait_cluster(uint32_t bar, uint32_t parity) {
  asm volatile("{\n.reg .pred p;\n.reg .u32 c;\nmov.u32 c, 0;\n"
               "LW:\nmbarrier.try_wait.parity.acquire.cluster.shared::cta.b64 p, [%0], %1;\n@p bra LD;\n"
               "add.u32 c, c, 1;\nsetp.lt.u32 p, c, 1048576;\n@p bra LW;\ntrap;\nLD:\n}" ::"r"(bar), "r"(parity) : "memory");
}
#define SPIN_CHECK(it) if (++(it) > SPIN_LIMIT) __trap()
DEVINL void fence_async_smem() { asm volatile("fence.proxy.async.shared::cta;" ::: "memory"); }
DEVINL void fence_async_global() { asm volatile("fence.proxy.async.global;" ::: "memory"); }
template <int BIT> DEVINL void rel_fence() { if ((FK_REL >> BIT) & 1) asm volatile("fence.acq_rel.gpu;" ::: "memory"); }
DEVINL void fence_gpu() { asm volatile("fence.acq_rel.gpu;" ::: "memory"); }
template <int ID, int N> DEVINL void named_bar() { asm volatile("bar.sync %0, %1;" ::"n"(ID), "n"(N) : "memory"); }
DEVINL bool elect_one() { uint32_t p; asm volatile("{\n.reg .pred e;\nelect.sync _|e, 0xffffffff;\nselp.u32 %0, 1, 0, e;\n}" : "=r"(p)); return p; }
DEVINL unsigned clk32() { unsigned c; asm volatile("mov.u32 %0, %%clock;" : "=r"(c)); return c; }
#define FK_GRIDW 32
#define FK_GRID 0
DEVINL void grid_wait() {
  if (FK_GRID) {
    unsigned t0, t1;
    asm volatile("mov.u32 %0, %%globaltimer_lo;" : "=r"(t0));
    do { asm volatile("mov.u32 %0, %%globaltimer_lo;" : "=r"(t1)); } while (((t0 - FK_GRIDW) ^ t1) < FK_GRID + 0u + !FK_GRID);
  }
}
DEVINL void spin(unsigned n) { const unsigned c = clk32(); while (clk32() - c < n) {} }

constexpr uint64_t POL_NORMAL = 0x1000000000000000ull, POL_FIRST = 0x12F0000000000000ull;
#define FK_HINTS 0x30B
template <int BIT> DEVINL constexpr uint64_t pol() { return ((FK_HINTS >> BIT) & 1) ? POL_FIRST : POL_NORMAL; }
DEVINL void tma_2d(uint32_t dst, const CUtensorMap* m, int x, int y, uint32_t bar, uint64_t pol) {
  asm volatile("cp.async.bulk.tensor.2d.shared::cluster.global.mbarrier::complete_tx::bytes.L2::cache_hint [%0], [%1, {%3, %4}], [%2], %5;"
               ::"r"(dst), "l"(m), "r"(bar), "r"(x), "r"(y), "l"(pol) : "memory");
}
DEVINL void tma_3d(uint32_t dst, const CUtensorMap* m, int y, int z, uint32_t bar, uint64_t pol) {
  asm volatile("cp.async.bulk.tensor.3d.shared::cluster.global.mbarrier::complete_tx::bytes.L2::cache_hint [%0], [%1, {0, %3, %4}], [%2], %5;"
               ::"r"(dst), "l"(m), "r"(bar), "r"(y), "r"(z), "l"(pol) : "memory");
}
DEVINL void tma_3d_mc(uint32_t dst, const CUtensorMap* m, int y, int z, uint32_t bar, uint64_t pol) {
  asm volatile("cp.async.bulk.tensor.3d.shared::cluster.global.mbarrier::complete_tx::bytes.multicast::cluster.L2::cache_hint [%0], [%1, {0, %3, %4}], [%2], %5, %6;"
               ::"r"(dst), "l"(m), "r"(bar), "r"(y), "r"(z), "h"((unsigned short)3), "l"(pol) : "memory");
}
DEVINL void tma_2d_mc(uint32_t dst, const CUtensorMap* m, int x, int y, uint32_t bar, uint64_t pol) {
  asm volatile("cp.async.bulk.tensor.2d.shared::cluster.global.mbarrier::complete_tx::bytes.multicast::cluster.L2::cache_hint [%0], [%1, {%3, %4}], [%2], %5, %6;"
               ::"r"(dst), "l"(m), "r"(bar), "r"(x), "r"(y), "h"((unsigned short)3), "l"(pol) : "memory");
}
DEVINL void tma_store_2d(const CUtensorMap* m, uint32_t src, int x, int y) {
  asm volatile("cp.async.bulk.tensor.2d.global.shared::cta.bulk_group [%0, {%2, %3}], [%1];" ::"l"(m), "r"(src), "r"(x), "r"(y) : "memory");
}
DEVINL void bulk_store(void* dst, uint32_t src, uint32_t bytes) {
  asm volatile("cp.async.bulk.global.shared::cta.bulk_group [%0], [%1], %2;" ::"l"(dst), "r"(src), "r"(bytes) : "memory");
}
DEVINL void bulk_load(uint32_t dst, const void* src, uint32_t bytes, uint32_t bar, uint64_t pol) {
  asm volatile("cp.async.bulk.shared::cluster.global.mbarrier::complete_tx::bytes.L2::cache_hint [%0], [%1], %2, [%3], %4;" ::"r"(dst), "l"(src), "r"(bytes), "r"(bar), "l"(pol) : "memory");
}
template <int N> DEVINL void bulk_wait_read() { asm volatile("cp.async.bulk.wait_group.read %0;" ::"n"(N) : "memory"); }
DEVINL void pf_bulk(const void* p, uint32_t bytes) { asm volatile("cp.async.bulk.prefetch.L2.global [%0], %1;" ::"l"(p), "r"(bytes) : "memory"); }
DEVINL void bulk_commit() { asm volatile("cp.async.bulk.commit_group;" ::: "memory"); }
template <int N> DEVINL void bulk_wait() { asm volatile("cp.async.bulk.wait_group %0;" ::"n"(N) : "memory"); }
DEVINL void prefetch_tmap(const CUtensorMap* m) { asm volatile("prefetch.tensormap [%0];" ::"l"(m) : "memory"); }

DEVINL void wg_fence() { asm volatile("wgmma.fence.sync.aligned;" ::: "memory"); }
DEVINL void wg_commit() { asm volatile("wgmma.commit_group.sync.aligned;" ::: "memory"); }
template <int N> DEVINL void wg_wait() { asm volatile("wgmma.wait_group.sync.aligned %0;" ::"n"(N) : "memory"); }
DEVINL uint32_t desc_lo(uint32_t addr, uint32_t lbo) { return ((addr & 0x3FFFF) >> 4) | ((lbo >> 4) << 16); }

#define R8(a, o) "+f"(a[o]), "+f"(a[o + 1]), "+f"(a[o + 2]), "+f"(a[o + 3]), "+f"(a[o + 4]), "+f"(a[o + 5]), "+f"(a[o + 6]), "+f"(a[o + 7])
#define R64(a, o) R8(a, o), R8(a, o + 8), R8(a, o + 16), R8(a, o + 24), R8(a, o + 32), R8(a, o + 40), R8(a, o + 48), R8(a, o + 56)
#define ACC64 "{%0, %1, %2, %3, %4, %5, %6, %7, %8, %9, %10, %11, %12, %13, %14, %15, "              \
              "%16, %17, %18, %19, %20, %21, %22, %23, %24, %25, %26, %27, %28, %29, %30, %31, "    \
              "%32, %33, %34, %35, %36, %37, %38, %39, %40, %41, %42, %43, %44, %45, %46, %47, "    \
              "%48, %49, %50, %51, %52, %53, %54, %55, %56, %57, %58, %59, %60, %61, %62, %63"
#define ACC128 ACC64 ", %64, %65, %66, %67, %68, %69, %70, %71, %72, %73, %74, %75, %76, %77, %78, %79, "      \
              "%80, %81, %82, %83, %84, %85, %86, %87, %88, %89, %90, %91, %92, %93, %94, %95, "               \
              "%96, %97, %98, %99, %100, %101, %102, %103, %104, %105, %106, %107, %108, %109, %110, %111, "   \
              "%112, %113, %114, %115, %116, %117, %118, %119, %120, %121, %122, %123, %124, %125, %126, %127"
template <int TB> DEVINL void wgmma_n256(float (&d)[128], uint32_t da, uint32_t db, int scale_d) {
  asm volatile("{\n.reg .pred p;\n.reg .b64 a, b;\nsetp.ne.b32 p, %130, 0;\nmov.b64 a, {%128, 0x40000040};\nmov.b64 b, {%129, 0x40000040};\n"
               "wgmma.mma_async.sync.aligned.m64n256k16.f32.bf16.bf16 " ACC128 "}, a, b, p, 1, 1, 0, %131;\n}\n"
               : R64(d, 0), R64(d, 64) : "r"(da), "r"(db), "r"(scale_d), "n"(TB));
}
template <int TB, int HI = 0x40000040> DEVINL void wgmma_n128(float (&d)[64], uint32_t da, uint32_t db) {
  asm volatile("{\n.reg .b64 a, b;\nmov.b64 a, {%64, %67};\nmov.b64 b, {%65, %67};\n"
               "wgmma.mma_async.sync.aligned.m64n128k16.f32.bf16.bf16 " ACC64 "}, a, b, 1, 1, 1, 0, %66;\n}\n" : R64(d, 0) : "r"(da), "r"(db), "n"(TB), "n"(HI));
}
template <int SC> DEVINL void wgmma_n128_rs(float (&d)[64], const uint32_t* a, uint32_t db) {
  asm volatile("{\n.reg .pred p;\n.reg .b64 b;\nsetp.ne.b32 p, %69, 0;\nmov.b64 b, {%68, 0x40000040};\n"
               "wgmma.mma_async.sync.aligned.m64n128k16.f32.bf16.bf16 " ACC64 "}, {%64, %65, %66, %67}, b, p, 1, 1, 0;\n}\n"
               : R64(d, 0) : "r"(a[0]), "r"(a[1]), "r"(a[2]), "r"(a[3]), "r"(db), "n"(SC));
}
template <int N> DEVINL void reg_fence(float (&a)[N]) {
#pragma unroll
  for (int i = 0; i < N; i++) asm volatile("" : "+f"(a[i])::"memory");
}

DEVINL uint32_t pack_bf16(float lo, float hi) { uint32_t r; asm("cvt.rn.bf16x2.f32 %0, %1, %2;" : "=r"(r) : "f"(hi), "f"(lo)); return r; }
DEVINL uint32_t add_bf16x2(uint32_t a, uint32_t b) { uint32_t r; asm("add.rn.bf16x2 %0, %1, %2;" : "=r"(r) : "r"(a), "r"(b)); return r; }
DEVINL uint32_t mul_bf16x2(uint32_t a, uint32_t b) { uint32_t r; asm("mul.rn.bf16x2 %0, %1, %2;" : "=r"(r) : "r"(a), "r"(b)); return r; }
DEVINL uint32_t fma_bf16x2(uint32_t a, uint32_t b, uint32_t c) { uint32_t r; asm("fma.rn.bf16x2 %0, %1, %2, %3;" : "=r"(r) : "r"(a), "r"(b), "r"(c)); return r; }
DEVINL float bf_lo(uint32_t w) { return __uint_as_float(w << 16); }
DEVINL float bf_hi(uint32_t w) { return __uint_as_float(w & 0xFFFF0000u); }
DEVINL float round_bf16(float v) { return bf_lo(pack_bf16(v, 0.f)); }
DEVINL float sigmoid_f(float v) { float r; asm("rcp.approx.ftz.f32 %0, %1;" : "=f"(r) : "f"(1.f + __expf(-v))); return r; }
DEVINL float rsqrt_f(float v) { float r; asm("rsqrt.approx.ftz.f32 %0, %1;" : "=f"(r) : "f"(v)); return r; }
DEVINL float silu_f(float v) { return v * sigmoid_f(v); }
DEVINL void stsm_x4(uint32_t addr, const uint32_t* r) {
  asm volatile("stmatrix.sync.aligned.m8n8.x4.shared.b16 [%0], {%1, %2, %3, %4};" ::"r"(addr), "r"(r[0]), "r"(r[1]), "r"(r[2]), "r"(r[3]) : "memory");
}
DEVINL void ldsm_x4(uint32_t addr, uint32_t* r) {
  asm volatile("ldmatrix.sync.aligned.m8n8.x4.shared.b16 {%0, %1, %2, %3}, [%4];" : "=r"(r[0]), "=r"(r[1]), "=r"(r[2]), "=r"(r[3]) : "r"(addr) : "memory");
}
DEVINL void ldsm_x4_t(uint32_t addr, uint32_t* r) {
  asm volatile("ldmatrix.sync.aligned.m8n8.x4.trans.shared.b16 {%0, %1, %2, %3}, [%4];" : "=r"(r[0]), "=r"(r[1]), "=r"(r[2]), "=r"(r[3]) : "r"(addr) : "memory");
}
DEVINL void mma_16816(float (&c)[4], const uint32_t* a, uint32_t b0, uint32_t b1) {
  asm("mma.sync.aligned.m16n8k16.row.col.f32.bf16.bf16.f32 {%0, %1, %2, %3}, {%4, %5, %6, %7}, {%8, %9}, {%0, %1, %2, %3};"
      : "+f"(c[0]), "+f"(c[1]), "+f"(c[2]), "+f"(c[3]) : "r"(a[0]), "r"(a[1]), "r"(a[2]), "r"(a[3]), "r"(b0), "r"(b1));
}
DEVINL void mma_1688(float (&c)[4], uint32_t a0, uint32_t a1, uint32_t b0) {
  asm("mma.sync.aligned.m16n8k8.row.col.f32.bf16.bf16.f32 {%0, %1, %2, %3}, {%4, %5}, {%6}, {%0, %1, %2, %3};"
      : "+f"(c[0]), "+f"(c[1]), "+f"(c[2]), "+f"(c[3]) : "r"(a0), "r"(a1), "r"(b0));
}
DEVINL float4 lds128(uint32_t a) { float4 v; asm volatile("ld.shared.v4.f32 {%0, %1, %2, %3}, [%4];" : "=f"(v.x), "=f"(v.y), "=f"(v.z), "=f"(v.w) : "r"(a)); return v; }
DEVINL uint4 lds128u(uint32_t a) { uint4 v; asm volatile("ld.shared.v4.u32 {%0, %1, %2, %3}, [%4];" : "=r"(v.x), "=r"(v.y), "=r"(v.z), "=r"(v.w) : "r"(a)); return v; }
DEVINL float2 lds64(uint32_t a) { float2 v; asm volatile("ld.shared.v2.f32 {%0, %1}, [%2];" : "=f"(v.x), "=f"(v.y) : "r"(a)); return v; }
DEVINL uint32_t lds32u(uint32_t a) { uint32_t v; asm volatile("ld.shared.u32 %0, [%1];" : "=r"(v) : "r"(a)); return v; }
DEVINL void sts128(uint32_t a, float x, float y, float z, float w) { asm volatile("st.shared.v4.f32 [%0], {%1, %2, %3, %4};" ::"r"(a), "f"(x), "f"(y), "f"(z), "f"(w) : "memory"); }
DEVINL void sts128u(uint32_t a, uint32_t x, uint32_t y, uint32_t z, uint32_t w) { asm volatile("st.shared.v4.u32 [%0], {%1, %2, %3, %4};" ::"r"(a), "r"(x), "r"(y), "r"(z), "r"(w) : "memory"); }
DEVINL void sts64u(uint32_t a, uint32_t x, uint32_t y) { asm volatile("st.shared.v2.u32 [%0], {%1, %2};" ::"r"(a), "r"(x), "r"(y) : "memory"); }
DEVINL void sts32v(uint32_t a, uint32_t v) { asm volatile("st.volatile.shared.u32 [%0], %1;" ::"r"(a), "r"(v) : "memory"); }
DEVINL void sts32(uint32_t a, float v) { asm volatile("st.shared.f32 [%0], %1;" ::"r"(a), "f"(v) : "memory"); }

DEVINL uint4 ld_msg(const void* p) {
  unsigned long long a, b;
  asm volatile("{\n.reg .b128 r;\nld.relaxed.gpu.global.b128 r, [%2];\nmov.b128 {%0, %1}, r;\n}" : "=l"(a), "=l"(b) : "l"(p) : "memory");
  return make_uint4((uint32_t)a, (uint32_t)(a >> 32), (uint32_t)b, (uint32_t)(b >> 32));
}
DEVINL void st_msg(void* p, uint32_t x, uint32_t y, uint32_t z, uint32_t w) {
  unsigned long long a = (unsigned long long)x | ((unsigned long long)y << 32), b = (unsigned long long)z | ((unsigned long long)w << 32);
  asm volatile("{\n.reg .b128 r;\nmov.b128 r, {%1, %2};\nst.relaxed.gpu.global.b128 [%0], r;\n}" ::"l"(p), "l"(a), "l"(b) : "memory");
}
DEVINL uint2 ld_msg8(const void* p) {
  unsigned long long a;
  asm volatile("ld.relaxed.gpu.global.b64 %0, [%1];" : "=l"(a) : "l"(p) : "memory");
  return make_uint2((uint32_t)a, (uint32_t)(a >> 32));
}
DEVINL void st_msg8(void* p, uint32_t x, uint32_t y) {
  asm volatile("st.relaxed.gpu.global.b64 [%0], %1;" ::"l"(p), "l"((unsigned long long)x | ((unsigned long long)y << 32)) : "memory");
}
DEVINL unsigned ld_rlx(const void* p) { unsigned v; asm volatile("ld.relaxed.gpu.global.u32 %0, [%1];" : "=r"(v) : "l"(p) : "memory"); return v; }
DEVINL void st_rlx(unsigned* p, unsigned v) { asm volatile("st.relaxed.gpu.global.u32 [%0], %1;" ::"l"(p), "r"(v) : "memory"); }
DEVINL void red_add(unsigned* p, unsigned v) { asm volatile("red.relaxed.gpu.global.add.u32 [%0], %1;" ::"l"(p), "r"(v) : "memory"); }
DEVINL uint4 ldg_nc(const void* p) {
  uint4 v;
  asm volatile("ld.global.nc.L1::no_allocate.v4.u32 {%0, %1, %2, %3}, [%4];" : "=r"(v.x), "=r"(v.y), "=r"(v.z), "=r"(v.w) : "l"(p));
  return v;
}
DEVINL float4 ldg_cg(const float* p) { float4 v; asm volatile("ld.global.cg.v4.f32 {%0, %1, %2, %3}, [%4];" : "=f"(v.x), "=f"(v.y), "=f"(v.z), "=f"(v.w) : "l"(p) : "memory"); return v; }
DEVINL void wait_cnt(const unsigned* p, unsigned target) {
  int it = 0;
  while ((int)(ld_rlx(p) - target) < 0) { SPIN_CHECK(it); __nanosleep(100); }
}

#define TRACE2(id)
#define TRACE3(id)
#define TRACE(id)
#define TRACE_CLK(id)

#define STAMP2(i)
#define STAMP(i)
DEVINL uint32_t fkey(float v) { const uint32_t u = __float_as_uint(v); return (u & 0x80000000u) ? ~u : (u | 0x80000000u); }
DEVINL float fkey_inv(uint32_t k) { return __uint_as_float((k & 0x80000000u) ? (k & 0x7FFFFFFFu) : ~k); }
DEVINL uint32_t redux_max(uint32_t v) { uint32_t r; asm volatile("redux.sync.max.u32 %0, %1, 0xffffffff;" : "=r"(r) : "r"(v)); return r; }
DEVINL void warp_top2(uint32_t key, uint32_t& k1, uint32_t& k2) { k1 = redux_max(key); k2 = redux_max(key == k1 ? 0u : key); }
DEVINL int key_row(uint32_t k) { return 2047 - (int)(k & 2047u); }
DEVINL int blk_src(int q, int cgrp) { const int f = q - 4, kk = (f * 37) >> 8, i = f - kk * 7; return f < 0 ? cgrp * 4 + q : (FK_SKIP ? i + (i >= cgrp) : i == cgrp ? 7 : i) * 4 + kk; }
DEVINL uint32_t pstage(int kk) { return ((0xABA4 >> (kk * 4)) & 15) * SLOT; }
DEVINL uint32_t buf_off(int u) { return ((0x42130 >> (u * 4)) & 15) * BUF; }
DEVINL int cnt_idx(int kb) { return kb < 4 ? (8 + kb) * 32 : (kb >> 2) * 32 + (kb & 3); }

__global__ void __launch_bounds__(384, 1) __cluster_dims__(2, 1, 1)
fused_kernel(const __nv_bfloat16* __restrict__ x, Scratch* const S, __nv_bfloat16* __restrict__ out, const __nv_bfloat16* __restrict__ cvec,
             const __nv_bfloat16* __restrict__ wd_re, const __nv_bfloat16* __restrict__ wd_im, const __grid_constant__ Params prm) {
  extern __shared__ __align__(1024) uint8_t smem_raw[];
  const uint32_t sb = smem_u32(smem_raw);
  const int tid = threadIdx.x, lane = tid & 31;
  const int warp = __shfl_sync(~0u, tid >> 5, 0);
  const int cl = blockIdx.x >> 1;
  const int rank = blockIdx.x & 1, c7 = ((cl - 36) * 37) >> 8;
  const int grp = cl < 4 ? 0 : cl < 36 ? (cl - 4) & 7 : cl - 35 - c7 * 7, gi = cl < 4 ? cl + 4 : cl < 36 ? (cl - 4) >> 3 : c7 + 4;
  const int j = gi >> 2, m4 = gi & 3, t = grp * 2 + rank;
  const int cgrp = m4 * 2 + j;
  const int b = t * 8 + cgrp;
  const bool moe = gi < 7;
  const int eb0 = j ? 64 + grp * 6 : grp * 8, eb = eb0 + m4 * 2 + rank;
  auto BAR = [&](int i) { return sb + BAR_OFF + i * 8; };

  uint4 xr[8];
  if ((warp & ~1) == 2) {
    const uint4* src = reinterpret_cast<const uint4*>(x + (size_t)(blockIdx.x * 2 + warp - 2) * D_) + lane;
#pragma unroll
    for (int i = 0; i < 4; i++) xr[i] = ldg_nc(src + 32 * i);
  }
  if (tid == 0) TRACE(0);
  if ((warp & ~1) != 2 && elect_one()) {
    const int w = warp < 2 ? warp : warp - 2;
#pragma unroll
    for (int k = 0; k < 5; k++) {
      const int i = w + 10 * k;
      if (i < B_NUM) mbar_init(BAR(i), (uint32_t)((i < 16 ? CNT0 : i < 32 ? CNT1 : CNT2) >> ((i & 15) * 4)) & 15u);
    }
    if (w < 4) mbar_expect_tx(BAR(B_FULL + w), STAGE);
    asm volatile("fence.mbarrier_init.release.cluster;" ::: "memory");
    if (w == 0) tma_2d(sb, &prm.ws[j], 0, t * 128, BAR(B_FULL), pol<0>());
    else prefetch_tmap(&prm.ws[1] + w);
  }
  if ((warp & ~1) != 2) { named_bar<4, 320>(); asm volatile("bar.arrive 3, 384;" ::: "memory"); }
  asm volatile("barrier.cluster.arrive.relaxed.aligned;" ::: "memory");

  if (warp < 4) {
    auto prefetch_piece = [&](int p) { if (!(FK_X & 1)) pf_bulk(prm.we[p >> 3] + (size_t)((p & 7) * 128 + b) * 7168, 7168); };
    auto weight_box = [&](int n, uint32_t bar) {
      if (moe && !(FK_X & 2)) {
        asm volatile("mbarrier.expect_tx.relaxed.cta.shared::cta.b64 [%0], 8192;" ::"r"(bar) : "memory");
        tma_2d(sb + SP_OFF + (n & 3) * 8192, &prm.wg + (n >> 3), eb * 32, (n & 7) * 128, bar, pol<3>());
      }
    };
    uint32_t tag = 0;
    if (warp == 0) {
      const unsigned* flagAddr = &S->cntN[cnt_idx(lane)];
      const unsigned tgt = (ld_rlx(S->epoch) + 1) * 64u;
      asm volatile("barrier.cluster.wait.acquire.aligned;" ::: "memory");
      unsigned ready = 0;
      if (lane >= 4) sts32v(sb + POLL_OFF + lane * 4, tgt - 1);
#pragma unroll 1
      for (int g = 0; g < 32; g++) {
        const int s = g & 3;
        const uint32_t sa = sb + s * STAGE, fb = BAR(B_FULL + s);
        if (!((ready >> g) & 1)) {
          unsigned v;
          asm volatile("ld.volatile.shared.u32 %0, [%1];" : "=r"(v) : "r"(sb + POLL_OFF + lane * 4) : "memory");
          ready |= __ballot_sync(~0u, v == tgt) & ~15u;
          int it = 0;
          while (!((ready >> g) & 1)) {
            ready |= __ballot_sync(~0u, (lane >> 2) == (g >> 2) && ld_rlx(flagAddr) == tgt);
            SPIN_CHECK(it);
          }
          fence_async_global();
        }
        if (g >= 4) {
          mbar_wait(BAR(B_EMPTY + s), ((g >> 2) - 1) & 1);
          if (lane < 8 && ((~ready >> (lane * 4)) & 15))
            asm volatile("cp.async.cg.shared.global [%0], [%1], 16;" ::"r"(sb + POLL_OFF + lane * 16), "l"(&S->cntN[lane * 32]) : "memory");
          if (elect_one()) { TRACE2(128 + g); mbar_expect_tx(fb, STAGE); tma_2d(sa, &prm.ws[j], g * 64, t * 128, fb, pol<0>()); }
        }
        if (elect_one()) {
          if (g < FK_NOMC) { tma_3d(sa + SLOT, &prm.n, g * 64, m4 * 4, fb, pol<4>()); tma_3d(sa + 2 * SLOT, &prm.n, g * 64, m4 * 4 + 2, fb, pol<4>()); }
          else tma_3d_mc(sa + SLOT + rank * SLOT, &prm.n, g * 64, m4 * 4 + rank * 2, fb, pol<4>());
          if (g > 0 && g < 4) tma_2d(sa, &prm.ws[j], g * 64, t * 128, fb, pol<0>());
          TRACE2(64 + g);
        }
        if ((unsigned)(g - FK_WSPF) < 4u)
          asm volatile("prefetch.global.L2 [%0];" ::"l"(prm.wsp[j] + (size_t)(t * 128 + m4 * 32 + (g - FK_WSPF) * 8 + (lane >> 2)) * 4096 + 3584 + (lane & 3) * 128));
      }
      asm volatile("cp.async.wait_all;" ::: "memory");
    }
    asm volatile("" ::: "memory");
    if (warp == 1) {
      tag = ld_rlx(S->epoch) + 1;
      if (elect_one()) prefetch_tmap(&prm.ps);
      const uint32_t rb = sb + (m4 * 32 + lane) * 128 + ((lane & 7) << 4);
      float a0 = 0.f, a1 = 0.f, a2 = 0.f, a3 = 0.f;
#pragma unroll 1
      for (int g = 0; g < 32; g++) {
        const int s = g & 3;
        mbar_wait(BAR(B_FULL + s), (g >> 2) & 1);
        uint4 u[8];
#pragma unroll
        for (int c = 0; c < 8; c++) u[c] = lds128u((rb + s * STAGE) ^ (c << 4));
        u[7].x = __shfl_sync(~0u, u[7].x, lane);
        if (elect_one()) {
          mbar_arrive(BAR(B_EMPTY + s)); TRACE2(160 + g);
          const int p = (g - FK_G0) >> FK_GS;
          if (g >= FK_G0 && !((g - FK_G0) & FK_GS) && (p < 8 ? moe && FK_TD : p < 12 && FK_TX)) {
            asm volatile("mbarrier.expect_tx.relaxed.cta.shared::cta.b64 [%0], 512;" ::"r"(BAR(B_RSDONE)) : "memory");
            tma_3d(sb + KEY_OFF, &prm.tch[p >> 3], p < 8 ? p : cgrp, p < 8 ? eb * 32 : t * 128 + (p - 8) * 32, BAR(B_RSDONE), POL_NORMAL);
          }
        }
#pragma unroll
        for (int c = 0; c < 8; c++) {
          a0 += bf_lo(u[c].x) + bf_lo(u[c].y); a1 += bf_hi(u[c].x) + bf_hi(u[c].y);
          a2 += bf_lo(u[c].z) + bf_lo(u[c].w); a3 += bf_hi(u[c].z) + bf_hi(u[c].w);
        }
      }
      if (lane == 0) mbar_arrive(BAR(B_RSDONE));
      mbar_wait(BAR(B_RSDONE), 0);
      st_msg8(&S->rs[j * S_ + t * 128 + m4 * 32 + lane], __float_as_uint((a0 + a1) + (a2 + a3)), tag);
    }
    asm volatile("" ::: "memory");
    if (warp >= 2) {
      const uint32_t ring = sb + SP_OFF + (warp - 2) * 16384, mf = BAR(B_MF + (warp - 2) * 4);
      const int jw = b >> 6, e0 = (b & 63) * 16;
      const __nv_bfloat16* src = (jw ? wd_im : wd_re) + (size_t)e0 * D_;
      int nc = 0;
#pragma unroll 1
      for (int G = 0; G < 8; G += (G == 0 && warp == 2) + 1) {
        if (G) { mbar_wait(mf + (nc & 3) * 8, (nc >> 2) & 1); nc++; }
        const uint32_t stg = ring + (nc & 3) * 4096, sl = stg + (G ? (lane >> 4) * 2048 + (lane & 15) * 16 : lane * 16), st = G ? 256 : 512;
        if (G) {
#pragma unroll
          for (int k = 0; k < 8; k++) xr[k] = lds128u(sl + k * 256);
        }
        float s0 = 0.f, s1 = 0.f, q0 = 0.f, q1 = 0.f, s2 = 0.f, s3 = 0.f, q2 = 0.f, q3 = 0.f;
        float v[64];
#pragma unroll
        for (int h = 0; h < 2; h++)
          if (h == 0 || G) {
#pragma unroll
            for (int k = 4 * h; k < 4 * h + 4; k++) {
              float* u = v + 8 * k;
              u[0] = bf_lo(xr[k].x); u[1] = bf_hi(xr[k].x); u[2] = bf_lo(xr[k].y); u[3] = bf_hi(xr[k].y);
              u[4] = bf_lo(xr[k].z); u[5] = bf_hi(xr[k].z); u[6] = bf_lo(xr[k].w); u[7] = bf_hi(xr[k].w);
#pragma unroll
              for (int i = 0; i < 8; i += 4) {
                s0 += u[i]; s1 += u[i + 1]; s2 += u[i + 2]; s3 += u[i + 3];
                q0 = fmaf(u[i], u[i], q0); q1 = fmaf(u[i + 1], u[i + 1], q1); q2 = fmaf(u[i + 2], u[i + 2], q2); q3 = fmaf(u[i + 3], u[i + 3], q3);
              }
            }
          }
        float sum = (s0 + s1) + (s2 + s3), sq = (q0 + q1) + (q2 + q3);
#pragma unroll
        for (int o = 1; o < 32; o <<= 1)
          if (o < 16 || !G) { sum += __shfl_xor_sync(~0u, sum, o); sq += __shfl_xor_sync(~0u, sq, o); }
        const float mean = sum * (1.f / D_);
        const float rstd = rsqrt_f(fmaxf(fmaf(-mean, mean, sq * (1.f / D_)), 0.f) + 1e-5f), nmr = -mean * rstd;
#pragma unroll
        for (int h = 0; h < 2; h++)
          if (h == 0 || G) {
#pragma unroll
            for (int k = 4 * h; k < 4 * h + 4; k++) {
              const float* u = v + 8 * k;
              sts128u(sl + k * st, pack_bf16(fmaf(u[0], rstd, nmr), fmaf(u[1], rstd, nmr)), pack_bf16(fmaf(u[2], rstd, nmr), fmaf(u[3], rstd, nmr)),
                      pack_bf16(fmaf(u[4], rstd, nmr), fmaf(u[5], rstd, nmr)), pack_bf16(fmaf(u[6], rstd, nmr), fmaf(u[7], rstd, nmr)));
            }
          }
        fence_async_smem();
        const int kq = blockIdx.x >> 5;
        if (elect_one()) {
          bulk_store(S->n + (size_t)(G * 256 + blockIdx.x * 2 + (G ? 0 : warp - 2)) * D_, stg, G ? 4096 : 2048); bulk_commit();
          if (G == 0) { bulk_wait<0>(); rel_fence<0>(); red_add(&S->cntN[cnt_idx(kq)], 1); TRACE(42 + warp); }
        }
        if (G == 0) named_bar<3, 384>();
        if (elect_one()) {
          if (G == 0 && warp == 2) mbar_wait(BAR(B_FULL), 0);
          if (G >= 4) { bulk_wait<1>(); red_add(&S->cntN[(G - 1) * 32 + kq], 2); }
#pragma unroll 1
          for (int k = G ? nc + 1 : 0; k < (warp == 2 ? nc + 2 : 1); k++) {
            mbar_expect_tx(mf + (k & 3) * 8, 4096);
            bulk_load(ring + ((k + 1) & 3) * 4096, k < 6 ? x + (size_t)((k + 4 - warp) * 256 + blockIdx.x * 2) * D_ : src + (k - 6) * 2 * D_, 4096, mf + (k & 3) * 8, k < 6 ? pol<7>() : pol<2>());
          }
          if (G == 1 || G == 2 || G == 7) { bulk_wait<0>(); rel_fence<1>(); red_add(&S->cntN[G * 32 + kq], 2); if (G > 1) TRACE(44 + (G & 3)); }
        }
        __syncwarp();
        if (warp == 3 && G) break;
      }
      tag = ld_rlx(S->epoch) + 1;
      float* const mod = S->mod[tag & 1];
      if (warp == 3) {
        const uint32_t stab = sb + TAB_OFF, stg = stab + 512;
        {
          const uint32_t cw = __ldg(reinterpret_cast<const uint32_t*>(cvec + t * 64) + lane);
          const uint32_t sp = pack_bf16(silu_f(bf_lo(cw)), silu_f(bf_hi(cw)));
          sts64u(stab + lane * 8, sp << 16, sp & 0xFFFF0000u);
        }
        float acc[8];
#pragma unroll
        for (int i = 0; i < 8; i++) acc[i] = 0.f;
#pragma unroll 1
        for (int n = -3; n < 24; n++) {
          if (n < 21 && elect_one()) {
            mbar_expect_tx(mf + (n & 3) * 8, 4096);
            tma_2d(ring + (n & 3) * 4096, &prm.wm, ((n + 3) >> 3) * 2048 + cgrp * 256, t * 64 + ((n + 3) & 7) * 8, mf + (n & 3) * 8, pol<1>());
          }
          if (n < 0) continue;
          const uint32_t sl = ring + ((n + 1) & 3) * 4096 + lane * 16;
          const float4 sv0 = lds128(stab + (n & 7) * 32), sv1 = lds128(stab + (n & 7) * 32 + 16);
          const float sc[8] = {sv0.x, sv0.y, sv0.z, sv0.w, sv1.x, sv1.y, sv1.z, sv1.w};
          mbar_wait(mf + ((n + 1) & 3) * 8, ((n + 1) >> 2) & 1);
          uint4 v[8];
#pragma unroll
          for (int u = 0; u < 8; u++) v[u] = lds128u(sl + u * 512);
#pragma unroll
          for (int u = 0; u < 8; u++) {
            acc[0] = fmaf(sc[u], bf_lo(v[u].x), acc[0]); acc[1] = fmaf(sc[u], bf_hi(v[u].x), acc[1]);
            acc[2] = fmaf(sc[u], bf_lo(v[u].y), acc[2]); acc[3] = fmaf(sc[u], bf_hi(v[u].y), acc[3]);
            acc[4] = fmaf(sc[u], bf_lo(v[u].z), acc[4]); acc[5] = fmaf(sc[u], bf_hi(v[u].z), acc[5]);
            acc[6] = fmaf(sc[u], bf_lo(v[u].w), acc[6]); acc[7] = fmaf(sc[u], bf_hi(v[u].w), acc[7]);
          }
          asm volatile("" : "+f"(acc[0]) :: "memory");
          if ((n & 7) == 7) {
            sts128(stg + lane * 32, acc[0], acc[1], acc[2], acc[3]); sts128(stg + lane * 32 + 16, acc[4], acc[5], acc[6], acc[7]);
#pragma unroll
            for (int i = 0; i < 8; i++) acc[i] = 0.f;
            fence_async_smem();
            if (elect_one()) {
              asm volatile("cp.reduce.async.bulk.global.shared::cta.bulk_group.add.f32 [%0], [%1], 1024;" ::"l"(mod + (n >> 3) * 2048 + cgrp * 256), "r"(stg) : "memory");
              bulk_commit();
              if (n != 15) { bulk_wait<0>(); rel_fence<2>(); red_add(&S->cntMod[n > 7 ? 32 : 0], 1); } else bulk_wait_read<0>();
              TRACE(n > 7 ? 34 + (n >> 3) : 9);
            }
          }
        }
      } else {
        wait_cnt(S->cntMod, tag * 128u);
        if (lane == 0) TRACE(10);
        float4 sa[8];
        {
          const float4 c0 = ldg_cg(mod + D_ + m4 * 256 + lane * 8), c1 = ldg_cg(mod + D_ + m4 * 256 + lane * 8 + 4);
#pragma unroll
          for (int i = 0; i < 8; i++) {
            const float4 sv = ldg_cg(mod + (i >> 1) * 256 + lane * 8 + (i & 1) * 4);
            const uint32_t s0 = pack_bf16(sv.x, sv.y), s1 = pack_bf16(sv.z, sv.w);
            sa[i] = make_float4(bf_lo(s0), bf_hi(s0), bf_lo(s1), bf_hi(s1));
          }
          const uint32_t cw[4] = {pack_bf16(c0.x, c0.y), pack_bf16(c0.z, c0.w), pack_bf16(c1.x, c1.y), pack_bf16(c1.z, c1.w)};
#pragma unroll
          for (int q = 0; q < 4; q++) sts32v(sb + T1_OFF + (lane >> 2) * 64 + q * 16 + (lane & 3) * 4, add_bf16x2(cw[q], 0x3F803F80u) ^ (j ? 0x80008000u : 0u));
        }
        float ul = 0.f;
#pragma unroll 1
        for (int r = 0; r < 8; r++) {
          if (r < 6 && elect_one()) {
            mbar_expect_tx(mf + ((nc + 2) & 3) * 8, 4096);
            bulk_load(ring + ((nc + 3) & 3) * 4096, src + (r + 2) * 2 * D_, 4096, mf + ((nc + 2) & 3) * 8, pol<2>());
          }
          mbar_wait(mf + (nc & 3) * 8, (nc >> 2) & 1); nc++;
          uint4 v[8];
          float u[4] = {0.f, 0.f, 0.f, 0.f};
#pragma unroll
          for (int i = 0; i < 8; i++) v[i] = lds128u(ring + (nc & 3) * 4096 + lane * 16 + i * 512);
#pragma unroll
          for (int i = 0; i < 8; i++) {
            const float4 s0 = sa[2 * (i & 3)], s1 = sa[2 * (i & 3) + 1];
            float &u0 = u[(i >> 2) * 2], &u1 = u[(i >> 2) * 2 + 1];
            u0 = fmaf(bf_lo(v[i].x), s0.x, u0); u1 = fmaf(bf_hi(v[i].x), s0.y, u1); u0 = fmaf(bf_lo(v[i].y), s0.z, u0); u1 = fmaf(bf_hi(v[i].y), s0.w, u1);
            u0 = fmaf(bf_lo(v[i].z), s1.x, u0); u1 = fmaf(bf_hi(v[i].z), s1.y, u1); u0 = fmaf(bf_lo(v[i].w), s1.z, u0); u1 = fmaf(bf_hi(v[i].w), s1.w, u1);
          }
          const float ua = u[0] + u[1], ub = u[2] + u[3];
          float us = ((lane & 1) ? ub : ua) + __shfl_xor_sync(~0u, (lane & 1) ? ua : ub, 1);
#pragma unroll
          for (int o = 16; o > 1; o >>= 1) us += __shfl_xor_sync(~0u, us, o);
          if ((lane >> 1) == r) ul = jw ? -us : us;
        }
        if (lane < 16) st_msg8(&S->u[jw * D_ + e0 + lane], __float_as_uint(ul), tag);
        if (lane == 0) TRACE(11);
#pragma unroll
        for (int i = 0; i < 4; i++) sts128u(ring + lane * 16 + i * 512, SENT, SENT, SENT, SENT);
        fence_async_smem();
        if (elect_one()) {
#pragma unroll 1
          for (int i = 0; i < 9; i++)
            bulk_store(i < 4 ? &S->part[b * 512 + i * 128] : i == 4 ? &S->stats[b * 128] : &S->rowsH[((i - 5) >> 1) * 4096 + (t * 2 + (i & 1)) * 128 + cgrp * 16], ring, i < 5 ? 2048 : 256);
          bulk_store(&S->flagP[b * 32], ring, 128);
          bulk_commit(); bulk_wait<0>(); rel_fence<4>();
          mbar_arrive(BAR(B_RSDONE)); TRACE(30);
        }
        if (lane < 12) reinterpret_cast<float4*>(S->mod[~tag & 1] + b * 48)[lane] = make_float4(0.f, 0.f, 0.f, 0.f);
      }
      named_bar<1, 64>();
    }
    asm volatile("setmaxnreg.dec.sync.aligned.u32 40;" ::: "memory");
    if (warp == 2) {
      const int scl = blk_src(lane, cgrp);
      const unsigned* flagAddr = &S->flagP[(t * 8 + (scl >> 2)) * 32 + (scl & 3)];
      const unsigned* cellAddr = &S->flagP[(t * 8 + (lane & 7)) * 32];
      sts32v(sb + PFLAG_OFF + lane * 4, tag - 1);
      if (lane < 4) mbar_arrive(BAR(B_FULL2 + lane));
      mbar_wait(BAR(B_PREADY), 0);
      unsigned ready = 15;
      int u = 4, i7 = 0, kk = 0; uint32_t ph = 1;
#pragma unroll 1
      for (int q = 4; q < 32; q++) {
        const int src = FK_SKIP ? i7 + (i7 >= cgrp) : i7 == cgrp ? 7 : i7;
        if (!((ready >> q) & 1)) {
          unsigned v;
          asm volatile("ld.volatile.shared.u32 %0, [%1];" : "=r"(v) : "r"(sb + PFLAG_OFF + scl * 4) : "memory");
          ready |= __ballot_sync(~0u, v == tag);
          int it = 0;
          while (!((ready >> q) & 1)) {
            ready |= __ballot_sync(~0u, (unsigned)(lane - q) < 7u && ld_rlx(flagAddr) == tag);
            SPIN_CHECK(it);
          }
          fence_async_global();
        }
        if ((q & ~4) == 8) mbar_wait(BAR(B_PS - 2 + (q >> 2)), 0);
        mbar_wait(BAR(q >= 8 ? B_EMPTY2 + u : q == 4 ? B_EMPTY + 2 : B_FULL2 + u), ph);
        if (q >= 8) grid_wait();
        if (elect_one()) {
          TRACE3(128 + q);
          mbar_expect_tx(BAR(B_FULL2 + u), SLOT);
          tma_2d(sb + buf_off(u), &prm.p, (src >> 1) * 256 + kk * 64, (src & 1) * S_ + t * 128, BAR(B_FULL2 + u), pol<5>());
        }
        if (((~ready >> q) & 15) && lane < 8)
          asm volatile("cp.async.cg.shared.global [%0], [%1], 16;" ::"r"(sb + PFLAG_OFF + lane * 16), "l"(cellAddr) : "memory");
        if (++u == 5) { u = 0; ph ^= 1; }
        if (++i7 == 7) { i7 = 0; kk++; }
      }
      asm volatile("cp.async.wait_all;" ::: "memory");
    }
    asm volatile("" ::: "memory");
    if (warp == 0) {
      int u = 0; uint32_t ph = 1;
#pragma unroll 1
      for (int q = 0; q < 32; q++) {
        const int sc = blk_src(q, cgrp);
        mbar_wait(BAR(q >= 5 ? B_EMPTY2 + u : q < 2 ? B_ADONE : q == 4 ? B_EMPTY + 3 : B_EMPTY + 1), q >= 2 ? ph : 0);
        if (elect_one()) {
          TRACE3(160 + q);
          mbar_expect_tx(BAR(B_FULL2 + u), SLOT);
          tma_2d_mc(sb + buf_off(u) + SLOT + rank * 8192, &prm.wd[(sc >> 2) & 1], (sc >> 3) * 256 + (sc & 3) * 64, cgrp * 128 + rank * 64, BAR(B_FULL2 + u), pol<6>());
          if (q & 1) { const int p = 4 + FK_NA + ((q - FK_QP) >> 1); if (q >= FK_QP && p < (FK_TD ? 16 : 24)) prefetch_piece(p); }
          else if (q >= 10 && q < 2 * FK_NL + 2) weight_box((q >> 1) - 1, BAR(B_FULL2 + (u == 4 ? 0 : u + 1)));
        }
        if (++u == 5) { u = 0; ph ^= 1; }
      }
      if (elect_one()) {
#pragma unroll 1
        for (int n = FK_NL; n < 15; n++) weight_box(n, BAR(B_WF));
        mbar_expect_tx(BAR(B_DN), moe ? 65536 : 0);
#pragma unroll 1
        for (int i = 0; i < 9; i++) {
          if ((i & 3) == 0) mbar_wait(BAR(B_EMPTY2 + 2 + (i >> 2)), 1);
          if (i == 0) { mbar_arrive(BAR(B_B27)); weight_box(15, BAR(B_WF)); mbar_arrive(BAR(B_WF)); }
          else if (moe)
            asm volatile("cp.async.bulk.tensor.5d.shared::cluster.global.mbarrier::complete_tx::bytes.L2::cache_hint [%0], [%1, {0, 0, 0, %3, %4}], [%2], %5;"
                         ::"r"(sb + RKA_OFF + (i + (i >> 3) * 4) * 8192), "l"(&prm.wdn), "r"(BAR(B_DN)), "r"(eb * 2), "r"(i * 2 - 2), "l"(pol<3>()) : "memory");
        }
      }
    }
    asm volatile("" ::: "memory");
    if (warp == 1) {
      if (elect_one()) {
#pragma unroll 1
        for (int kk = 0; kk < 4; kk++) {
          mbar_wait(BAR(B_PREADY + kk), 0);
#pragma unroll 1
          for (int i = 0; i < 4; i++) {
            tma_store_2d(&prm.ps, sb + pstage(kk) + i * 4096, m4 * 256 + kk * 64, j * S_ + t * 128 + i * 32);
            if (kk >= FK_PS0 && i < 3) { const unsigned next = clk32() + FK_PSPACE; while ((int)(clk32() - next) < 0) __nanosleep(20); }
          }
          bulk_commit(); bulk_wait<0>();
          if (kk < 2) mbar_arrive(BAR(B_PS + kk));
          rel_fence<3>();
          st_rlx(&S->flagP[b * 32 + kk], tag);
          TRACE(40 + kk); TRACE3(128 + kk);
        }
        prefetch_tmap(&prm.om);
        if (FK_XD) { const unsigned next = clk32() + FK_XD; while ((int)(clk32() - next) < 0) __nanosleep(20); }
        mbar_expect_tx(BAR(B_EFULL), (FK_X & 4) ? 0 : 32768);
#pragma unroll 1
        for (int i = 0; i < 8; i++) {
          if (!(FK_X & 4)) tma_3d(sb + E_OFF + i * 4096, &prm.xm, t * 128 + i * 16, cgrp * 2, BAR(B_EFULL), pol<8>());
          const unsigned next = clk32() + FK_SPACE;
          while ((int)(clk32() - next) < 0) __nanosleep(20);
        }
      }
      __syncwarp();
      mbar_wait(BAR(B_PREADY), 1);
      if (lane == 0) TRACE(60);
      const int lr = lds32u(sb + BK_OFF + (lane >> 4) * 4);
      {
        const uint4 v = lds128u(sb + E_OFF + (lr >> 4) * 4096 + (lane & 8) * 256 + (lr & 15) * 128 + (((lane ^ lr) & 7) << 4));
        st_msg(&S->rowsB[(t * 2 + (lane >> 4)) * 128 + cgrp * 16 + (lane & 15)], v.x, v.y, v.z, v.w);
      }
      const unsigned cmask = __reduce_or_sync(~0u, 1u << (lr >> 4)) | FK_OMASK;
      unsigned todo = ~cmask & 255, smask = 0;
      int r1 = 0, r2 = 0;
#pragma unroll 1
      for (int h = 0; h < 2; h++) {
        if (elect_one()) {
#pragma unroll 1
          for (; todo; todo &= todo - 1) {
            const int i = __ffs(todo) - 1;
            asm volatile("cp.async.bulk.tensor.3d.global.shared::cta.bulk_group.L2::cache_hint [%0, {0, %2, %3}], [%1], %4;"
                         ::"l"(&prm.om), "r"(sb + E_OFF + i * 4096), "r"(t * 128 + i * 16), "r"(cgrp * 2), "l"(pol<9>()) : "memory");
            if (FK_OSPACE && (h == 0 || FK_OSPACE2)) spin(h ? FK_OSPACE2 : FK_OSPACE);
          }
          TRACE(61 + h);
        }
        if (h) break;
        mbar_wait(BAR(B_SEL), 0);
        r1 = lds32u(sb + SEL_OFF) - t * 128; r2 = lds32u(sb + SEL_OFF + 4) - t * 128;
        smask = ((unsigned)r1 < 128u ? 1u << (r1 >> 4) : 0) | ((unsigned)r2 < 128u ? 1u << (r2 >> 4) : 0);
        todo = cmask & ~smask;
        if (FK_ODELAY) spin(FK_ODELAY);
      }
#pragma unroll 1
      for (; smask; smask &= smask - 1) {
        const int i = __ffs(smask) - 1;
#pragma unroll 2
        for (int r = lane >> 4; r < 16; r += 2) {
          const uint4 v = lds128u(sb + E_OFF + i * 4096 + (lane & 8) * 256 + r * 128 + (((lane ^ r) & 7) << 4));
          if (i * 16 + r != r1 && i * 16 + r != r2) reinterpret_cast<uint4*>(out + (size_t)(t * 128 + i * 16 + r) * D_)[cgrp * 16 + (lane & 15)] = v;
        }
      }
      if (elect_one()) { bulk_commit(); bulk_wait_read<0>(); TRACE(29); }
    }
    asm volatile("" ::: "memory");
    if (warp == 3) {
      if (elect_one()) {
        fence_async_smem();
        unsigned next = clk32();
#pragma unroll 1
        for (int n = 0; n < 4 + FK_NA; n++) {
          if (n < 4) weight_box(n, BAR(B_WF)); else prefetch_piece(n);
          if (n == 3) mbar_arrive(BAR(B_WF));
          if (!FK_TX && (unsigned)(n - FK_XN) < 4u) pf_bulk(x + (size_t)(b * 16 + (n - FK_XN) * 4) * D_, 8192);
          next += FK_PACE;
          while ((int)(clk32() - next) < 0) __nanosleep(20);
        }
        TRACE(37);
      }
      __syncwarp();
      int it = 0;
      wait_cnt(&S->cntMod[32], tag * 128u);
      mbar_wait(BAR(B_PREADY + 2), 0);
      {
        const float* mp = S->mod[tag & 1] + cgrp * 128 + lane * 4;
        const float4 ga = ldg_cg(mp + 2 * D_), sv = ldg_cg(mp + 3 * D_), cb = ldg_cg(mp + 4 * D_), gb = ldg_cg(mp + 5 * D_);
        const uint2 wr = __ldg(reinterpret_cast<const uint2*>(prm.w_r + cgrp * 128 + lane * 4));
        const uint32_t Aa = add_bf16x2(pack_bf16(cb.x, cb.y), 0x3F803F80u), Ab = add_bf16x2(pack_bf16(cb.z, cb.w), 0x3F803F80u);
        const uint32_t Sa = pack_bf16(sv.x, sv.y), Sb = pack_bf16(sv.z, sv.w), Ga = pack_bf16(gb.x, gb.y), Gb = pack_bf16(gb.z, gb.w);
        const float w0 = bf_lo(Aa) * bf_lo(wr.x), w1 = bf_hi(Aa) * bf_hi(wr.x), w2 = bf_lo(Ab) * bf_lo(wr.y), w3 = bf_hi(Ab) * bf_hi(wr.y);
        const uint32_t tb = sb + TAB_OFF + (lane >> 3) * 64 + (lane & 1) * 32 + ((lane >> 1) & 3) * 4, Wa = pack_bf16(w0, w1), Wb = pack_bf16(w2, w3);
        auto put = [&](int off, uint32_t a, uint32_t c) { sts32v(tb + off, a); sts32v(tb + off + 16, c); };
        put(T_WH, Wa, Wb); put(T_ONE, 0x3F803F80u, 0x3F803F80u);
        put(T_WL, pack_bf16(w0 - bf_lo(Wa), w1 - bf_hi(Wa)), pack_bf16(w2 - bf_lo(Wb), w3 - bf_hi(Wb)));
        put(T_GA, pack_bf16(ga.x, ga.y), pack_bf16(ga.z, ga.w)); put(T_A, Aa, Ab); put(T_S, Sa, Sb); put(T_G, Ga, Gb);
        float c1 = (w0 + w1) + (w2 + w3), c2 = (bf_lo(Sa) * bf_lo(wr.x) + bf_hi(Sa) * bf_hi(wr.x)) + (bf_lo(Sb) * bf_lo(wr.y) + bf_hi(Sb) * bf_hi(wr.y));
#pragma unroll 1
        for (int h = 0; h < 2; h++) {
#pragma unroll
          for (int o = 16; o; o >>= 1) { c1 += __shfl_xor_sync(~0u, c1, o); c2 += __shfl_xor_sync(~0u, c2, o); }
          if (h) break;
          if (t == 0 && lane == 0) st_msg(&S->cst[cgrp], __float_as_uint(c1), __float_as_uint(c2), tag, 0);
          uint4 cm; it = 0;
          while (true) {
            cm = ld_msg(&S->cst[lane & 7]);
            if (__all_sync(~0u, cm.z == tag)) break;
            SPIN_CHECK(it); __nanosleep(200);
          }
          c1 = 0.25f * __uint_as_float(cm.x); c2 = 0.25f * __uint_as_float(cm.y);
        }
        if (lane == 0) { sts128u(sb + CST_OFF, __float_as_uint(c1), __float_as_uint(c2), tag, b | eb << 8 | (int)moe << 16); TRACE(27); }
      }
      uint32_t rk[16];
#pragma unroll
      for (int h = 0; h < 2; h++) {
        const uint2* src = (h ? &S->u[cgrp * 128] : &S->rs[t * 128]) + lane;
        uint2 m[8]; it = 0;
        while (true) {
          bool ok = true;
#pragma unroll
          for (int i = 0; i < 8; i++) { m[i] = ld_msg8(src + (i >> 1) * 32 + (i & 1) * (h ? D_ : S_)); ok &= m[i].y == tag; }
          if (ok) break;
          SPIN_CHECK(it);
        }
#pragma unroll
        for (int i = 0; i < 4; i++) {
          const float r0 = __uint_as_float(m[2 * i].x) * (h ? 0.5f : 1.f), r1 = __uint_as_float(m[2 * i + 1].x) * (h ? 0.5f : 1.f);
          const uint32_t hi = pack_bf16(r0, r1);
          rk[h * 8 + 2 * i] = hi; rk[h * 8 + 2 * i + 1] = pack_bf16(r0 - bf_lo(hi), r1 - bf_hi(hi));
        }
      }
      mbar_wait(BAR(B_B27), 0);
#pragma unroll
      for (int i = 0; i < 4; i++) {
        sts128u(sb + RKA_OFF + (i * 32 + lane) * 16, rk[2 * i], rk[2 * i], rk[2 * i + 1], 0);
        sts128u(sb + RKB_OFF + (i * 32 + lane) * 16, rk[8 + 2 * i], rk[9 + 2 * i], rk[8 + 2 * i], 0);
      }
      fence_async_smem();
      __syncwarp();
      if (lane == 0) { mbar_arrive(BAR(B_TAB)); TRACE(26); }
    }
    asm volatile("" ::: "memory");
    if (warp == 2) {
      const uint4* cp = &S->cand[(lane >> 1) * 8];
      mbar_wait(BAR(B_B27), 0);
      uint4 m = ld_msg(cp);
      bool ok = __all_sync(~0u, m.z == tag);
      named_bar<5, 288>();
      uint32_t k1, k2;
      {
        const uint4 k4 = lds128u(sb + KEY_OFF + lane * 16);
        const uint32_t ka = max(k4.x, k4.y), kb = max(k4.z, k4.w), m1 = max(ka, kb), m2 = max(min(ka, kb), ka > kb ? min(k4.x, k4.y) : min(k4.z, k4.w));
        k1 = redux_max(m1); k2 = redux_max(m1 == k1 ? m2 : m1);
        if (lane == 0) { st_msg(&S->cand[t * 8], k1, k2, tag, 0); sts64u(sb + BK_OFF, key_row(k1) & 127, key_row(k2) & 127); mbar_arrive(BAR(B_BK)); TRACE(13); }
      }
      int it = 0;
      while (!ok) {
        m = ld_msg(cp);
        ok = __all_sync(~0u, m.z == tag);
        SPIN_CHECK(it);
      }
      warp_top2((lane & 1) ? m.y : m.x, k1, k2);
      const int r1 = key_row(k1), r2 = key_row(k2), slot1 = (r1 >> 7) * 2, slot2 = (r2 >> 7) * 2 + ((r1 >> 7) == (r2 >> 7));
      if (lane == 0) { sts64u(sb + SEL_OFF, r1, r2); sts64u(sb + SEL_OFF + 8, slot1 * 2048, slot2 * 2048); mbar_arrive(BAR(B_SEL)); TRACE(14); }
      const int fcol = (b >> 1) * 16 + (lane & 15);
      const float gb = round_bf16(__uint_as_float(ld_rlx(S->mod[tag & 1] + 5 * D_ + fcol)));
      const uint32_t* fbp = reinterpret_cast<const uint32_t*>(&S->rowsB[((b & 1) ? slot2 : slot1) * 128]) + (fcol >> 1);
      uint32_t fb;
      do { fb = ld_rlx(fbp); SPIN_CHECK(it); } while (fb == SENT);
      sts64u(sb + PFLAG_OFF + (lane & 15) * 8, (lane & 1) ? fb & 0xFFFF0000u : fb << 16, __float_as_uint(gb));
      __syncwarp();
      if (lane == 0) {
        sts32(sb + CST_OFF, round_bf16(sigmoid_f(round_bf16(fkey_inv((((b & 1) ? k2 : k1) & ~2047u) | 1024u)))));
        mbar_arrive(BAR(B_FIN));
        if (b == 0) S->epoch[0] = tag;
      }
    }
  } else {
    const int cw = (warp - 4) >> 2;
    const int cwarp = warp - 4;
    const bool elect = (tid & 127) == 0;
    uint32_t rel;
    asm volatile("mapa.shared::cluster.u32 %0, %1, %2;" : "=r"(rel) : "r"(BAR(0)), "r"(tid & 1));
    if (tid & 126) rel = 0;
    asm volatile("" : "+r"(rel));
    auto release = [&](int bar) {
      asm volatile("{\n.reg .pred p;\nsetp.ne.u32 p, %1, 0;\n@p mbarrier.arrive.shared::cluster.b64 _, [%0];\n}" ::"r"(rel + bar * 8), "r"(rel) : "memory");
    };
    const uint32_t da0 = desc_lo(sb + cw * 8192, 16), db0 = desc_lo(sb + SLOT, 8192), db2 = desc_lo(sb + SLOT, 16);
    asm volatile("barrier.cluster.wait.acquire.aligned;" ::: "memory");

    uint32_t wf[64], uf[64], df[64];
    uint32_t pk[64];
    uint32_t xw[32];
    float lo[64];
    int ln;
    uint32_t so, wo;
    auto p_ready = [&](int kk) { fence_async_smem(); if (elect_one()) mbar_arrive(BAR(B_PREADY + kk)); };
    {
      float pa[64], pb[64];
      {
        float acc[128];
#pragma unroll 1
        for (int g = 0; g < 28; g++) {
          const int s = g & 3;
          mbar_wait(BAR(B_FULL + s), (g >> 2) & 1);
          const uint32_t da = da0 + s * (STAGE >> 4), db = db0 + s * (STAGE >> 4);
          wg_fence();
          wgmma_n256<1>(acc, da, db, g > 0);
#pragma unroll
          for (int k = 1; k < 4; k++) wgmma_n256<1>(acc, da + k * 2, db + k * 128, 1);
          wg_commit();
          wg_wait<1>();
          if (g > 0) { release(B_EMPTY + ((g - 1) & 3)); if (elect) TRACE2(191 + g + cw * 32); }
          STAMP2(g);
        }
        wg_wait<0>();
        release(B_EMPTY + 3);
#pragma unroll
        for (int i = 0; i < 64; i++) {
          asm volatile("mov.b32 %0, %1;" : "=f"(pa[i]) : "f"(acc[i]));
          asm volatile("mov.b32 %0, %1;" : "=f"(pb[i]) : "f"(acc[64 + i]));
        }
      }
      if (elect) TRACE(3 + tr);
      STAMP2(28);
#pragma unroll 1
      for (int s = 0; s < 4; s++) {
        mbar_wait(BAR(B_FULL + s), 1);
        wg_fence();
#pragma unroll
        for (int k = 0; k < 4; k++) wgmma_n128<1>(pa, da0 + s * (STAGE >> 4) + k * 2, db0 + s * (STAGE >> 4) + k * 128);
        wg_commit();
        if (s == 2) { wg_wait<1>(); if (elect) mbar_arrive(BAR(B_A29)); }
      }
      auto b_block = [&](int s) {
        wg_fence();
#pragma unroll
        for (int k = 0; k < 4; k++) wgmma_n128<1>(pb, da0 + s * (STAGE >> 4) + k * 2, db0 + s * (STAGE >> 4) + 1024 + k * 128);
        wg_commit();
      };
      uint4 t0, t1;
      auto load_t = [&](int kk) { t0 = lds128u(sb + T1_OFF + kk * 128 + (ln & 3) * 16); t1 = lds128u(sb + T1_OFF + kk * 128 + 64 + (ln & 3) * 16); };
      auto pack_p = [&](int kk, const float* a) {
        const uint32_t A[8] = {t0.x, t0.y, t0.z, t0.w, t1.x, t1.y, t1.z, t1.w};
#pragma unroll
        for (int i = 0; i < 16; i++) pk[kk * 16 + i] = mul_bf16x2(pack_bf16(a[2 * i], a[2 * i + 1]), A[i >> 1]);
      };
      auto stage_p = [&](int kk) {
#pragma unroll
        for (int k = 0; k < 4; k++) stsm_x4((so ^ (k << 5)) + pstage(kk), pk + kk * 16 + k * 4);
      };
      auto own_block = [&](int q) {
        const uint32_t db = db2 + (buf_off(q) >> 4);
        wg_fence();
        if (q == 0) wgmma_n128_rs<0>(lo, pk, db); else wgmma_n128_rs<1>(lo, pk + q * 16, db);
#pragma unroll
        for (int k = 1; k < 4; k++) wgmma_n128_rs<1>(lo, pk + q * 16 + k * 4, db + k * 2);
        wg_commit();
      };
      b_block(0);
      mbar_wait(BAR(B_RSDONE), 0);
      asm volatile("setmaxnreg.inc.sync.aligned.u32 232;" ::: "memory");
      asm volatile("mov.u32 %0, %%laneid;" : "=r"(ln));
      so = sb + (uint32_t)(cwarp * 16 + (ln & 15)) * 128 + (((ln >> 4) ^ (ln & 7)) << 4);
      wo = sb + SP_OFF + cwarp * 1024 + ((ln & 7) + (ln >> 4) * 8) * 64 + ((((ln >> 3) & 1) ^ ((ln >> 1) & 3)) << 4);
      mbar_wait(BAR(B_A29), 0);
      load_t(0);
      wg_wait<1>();
      reg_fence(pa);
      release(B_ADONE);
      if (elect) TRACE(4 + tr);
      STAMP2(29);
      pack_p(0, pa); stage_p(0);
      if (FK_TR0) { p_ready(0); b_block(1); } else { b_block(1); p_ready(0); }
      if (elect) TRACE(2 + tr);
      wg_wait<1>(); release(B_EMPTY);
      load_t(1);
      b_block(2);
      pack_p(1, pa + 32);
      wg_wait<1>(); release(B_EMPTY + 1);
      STAMP2(30);
      load_t(2);
      b_block(3);
      mbar_wait(BAR(B_FULL2), 0);
      wg_wait<1>(); release(B_EMPTY + 2);
      if (FK_S1 == 0) { mbar_wait(BAR(B_ADONE), 0); stage_p(1); }
      own_block(0);
      if (FK_S1 == 0) p_ready(1);
      mbar_wait(BAR(B_FULL2 + 1), 0);
      if (FK_S1 == 1) mbar_wait(BAR(B_ADONE), 0);
      wg_wait<1>(); release(B_EMPTY + 3);
      reg_fence(pb);
      if (elect) TRACE(1 + tr);
      STAMP2(31);
      if (FK_S1 == 1) stage_p(1);
      own_block(1);
      if (FK_S1 == 1) p_ready(1);
      pack_p(2, pb);
      mbar_wait(BAR(B_FULL2 + 2), 0);
      wg_wait<1>(); release(B_EMPTY2);
      STAMP2(32);
      load_t(3);
      own_block(2);
      pack_p(3, pb + 32);
      mbar_wait(BAR(B_EMPTY + 3), 1);
      mbar_wait(BAR(B_FULL2 + 3), 0);
      wg_wait<1>(); release(B_EMPTY2 + 1);
      STAMP2(33);
      if (FK_S1 == 3) stage_p(1);
      own_block(3);
      if (FK_S1 == 3) p_ready(1);
      mbar_wait(BAR(B_WF), 0);
      wg_wait<1>(); release(B_EMPTY2 + 2);
      STAMP2(34);
    }
    {
      mbar_wait(BAR(B_FULL2 + 4), 0);
#pragma unroll
      for (int q = 4; q < 32; q++) {
        const uint32_t da = da0 + (buf_off(q % 5) >> 4) + (q << 16), db = db2 + (buf_off(q % 5) >> 4) + (q << 16);
        wg_fence();
#pragma unroll
        for (int k = 0; k < 4; k++) wgmma_n128<0>(lo, da + k * 2, db + k * 2);
        wg_commit();
        if (q == 31) break;
        if (FK_ORD == 1) { wg_wait<1>(); if (q == 28 && rel) rel = BAR(0); release(B_EMPTY2 + (q - 1) % 5); STAMP2(31 + q); }
        if (q == 8 || q == 14) p_ready(q >> 2);
        if (q == 27) mbar_wait(BAR(B_EFULL), 0);
        mbar_wait(BAR(B_FULL2 + (q + 1) % 5), ((q + 1) / 5) & 1);
        if (q >= 27) {
#pragma unroll
          for (int h = 0; h < 2; h++) ldsm_x4((so ^ ((q - 27) << 5)) + E_OFF + cwarp * 2048 + h * 2048, xw + (q - 27) * 4 + h * 16);
        } else if (!(q & 1)) {
          const int n = (q - 4) >> 1;
#pragma unroll
          for (int h = 0; h < 2; h++) ldsm_x4_t((wo ^ (h << 5)) + (n & 3) * 8192, (n < 8 ? wf + n * 8 : uf + (n - 8) * 8) + h * 4);
        } else if (q < 15 && q != 9) {
          const int i = (q - 5 - (q > 9) * 2) >> 1;
#pragma unroll
          for (int h = 0; h < 2; h++) stsm_x4((so ^ (((i & 1) * 2 + h) << 5)) + pstage(2 + (i >> 1)), pk + 32 + i * 8 + h * 4);
        }
        if (FK_ORD == 0) { wg_wait<1>(); if (q == 28 && rel) rel = BAR(0); release(B_EMPTY2 + (q - 1) % 5); STAMP2(31 + q); }
      }
    }
    mbar_wait(BAR(B_TAB), 0);
    wg_fence();
    wgmma_n128<0, 8>(lo, desc_lo(sb + RKA_OFF, 0) + (cwarp & 4) * 16, desc_lo(sb + RKB_OFF, 0));
    wg_commit();
    const int gq = ln >> 2, q4 = ln & 3, row0 = cwarp * 16 + gq;
    const bool odd = ln & 1;
    const uint32_t role = lds32u(sb + CST_OFF + 12), bq = role & 255;
    uint32_t tq = sb + TAB_OFF + q4 * 16, tb = tq + (gq & 1) * T_ONE + (gq & 2) * (T_WL / 2);
    const uint4* src = &S->stats[((bq & ~7) + (q4 >> 1) * 4) * 128 + row0 + 8 * (q4 & 1)];
    uint4* sdst = &S->stats[bq * 128 + row0 + 8 * q4];
    asm volatile("" : "+r"(tq), "+r"(tb), "+l"(src), "+l"(sdst));
    {
      uint4 gw[4];
#pragma unroll
      for (int a = 0; a < 4; a++) gw[a] = lds128u(tq + T_GA + a * 64);
      wg_wait<0>();
      reg_fence(lo);
      STAMP(0);
      if (elect) { TRACE(7 + tr); if (cw == 0) TRACE_CLK(121); }
      float c[2][4], e0[2][4], e1[2][4];
#pragma unroll
      for (int i = 0; i < 4; i++) c[0][i] = c[1][i] = e0[0][i] = e0[1][i] = e1[0][i] = e1[1][i] = 0.f;
#pragma unroll
      for (int a = 0; a < 4; a++) {
        const uint4 bw = lds128u(tb + a * 64);
        const uint32_t g[4] = {gw[a].x, gw[a].y, gw[a].z, gw[a].w};
#pragma unroll
        for (int i = 0; i < 8; i++) xw[a * 8 + i] = fma_bf16x2(g[i >> 1], pack_bf16(lo[a * 16 + 2 * i], lo[a * 16 + 2 * i + 1]), xw[a * 8 + i]);
#pragma unroll
        for (int h = 0; h < 2; h++) {
          const uint32_t* w = xw + a * 8 + h * 4;
          mma_1688(e0[0], w[0], w[1], w[0]); mma_1688(e1[0], w[0], w[1], w[1]); mma_1688(e0[1], w[2], w[3], w[2]); mma_1688(e1[1], w[2], w[3], w[3]);
          mma_16816(c[h], w, h ? bw.z : bw.x, h ? bw.w : bw.y);
        }
      }
      const float c0 = c[0][0] + c[1][0], c2 = c[0][2] + c[1][2];
      const float q0 = (gq & 1) ? e0[0][1] + e0[1][1] : e0[0][0] + e0[1][0], q1 = (gq & 1) ? e1[0][3] + e1[1][3] : e1[0][2] + e1[1][2];
      const int dl = (ln & ~3) | (gq >> 1);
      const float da = (odd ? c2 : c0) + __shfl_xor_sync(~0u, odd ? c0 : c2, 1), s1 = __shfl_xor_sync(~0u, c[0][3] + c[1][3], 1);
      const float qa = __shfl_sync(~0u, q0, dl), qb = __shfl_sync(~0u, q1, dl);
      if (q4 < 2) st_msg(sdst, __float_as_uint(odd ? s1 : c[0][1] + c[1][1]), __float_as_uint(odd ? qb : qa), __float_as_uint(da), 0);
    }
    if (elect) TRACE(8 + tr);
    STAMP(1);
    {
      uint4 m[4], tA[4], tS[4];
      mbar_wait(BAR(B_WF), 1);
#pragma unroll
      for (int i = 0; i < 4; i++) m[i] = ld_msg(src + 128 * i);
      const float2 cst = lds64(sb + CST_OFF);
#pragma unroll
      for (int i = 0; i < 8; i++) ldsm_x4_t((wo ^ ((i & 1) << 5)) + (i >> 1) * 8192, uf + 32 + i * 4);
#pragma unroll
      for (int a = 0; a < 4; a++) { tA[a] = lds128u(tq + T_A + a * 64); tS[a] = lds128u(tq + T_S + a * 64); }
      uint32_t kaddr = sb + KEY_OFF + (row0 + 8 * (q4 & 1)) * 4, kidx = 2047 - ((bq >> 3) * 128 + row0 + 8 * (q4 & 1));
      asm volatile("" : "+r"(kaddr), "+r"(kidx));
      STAMP(2);
      int it = 0;
      while (!__all_sync(~0u, (m[0].w | m[1].w | m[2].w | m[3].w) == 0)) {
#pragma unroll
        for (int i = 0; i < 4; i++) m[i] = ld_msg(src + 128 * i);
        SPIN_CHECK(it);
      }
      STAMP(3);
      float sa = (__uint_as_float(m[0].x) + __uint_as_float(m[1].x)) + (__uint_as_float(m[2].x) + __uint_as_float(m[3].x));
      float qa = (__uint_as_float(m[0].y) + __uint_as_float(m[1].y)) + (__uint_as_float(m[2].y) + __uint_as_float(m[3].y));
      float da = (__uint_as_float(m[0].z) + __uint_as_float(m[1].z)) + (__uint_as_float(m[2].z) + __uint_as_float(m[3].z));
      sa += __shfl_xor_sync(~0u, sa, 2); qa += __shfl_xor_sync(~0u, qa, 2); da += __shfl_xor_sync(~0u, da, 2);
      const float mean = sa * (1.f / D_);
      const float rs = rsqrt_f(fmaxf(fmaf(-mean, mean, qa * (1.f / D_)), 0.f) + 1e-5f);
      sts32v(kaddr, (fkey(fmaf(rs, fmaf(-mean, cst.x, da), cst.y)) & ~2047u) | kidx);
      uint32_t one;
      asm volatile("bar.arrive 5, 288;\nld.volatile.shared.u32 %0, [%1];" : "=r"(one) : "r"(sb + TAB_OFF + T_ONE) : "memory");
      if (tid == 128) TRACE(12 + 16);
      STAMP(4);
      const uint32_t h0 = pack_bf16(rs, rs), l0 = mul_bf16x2(pack_bf16(rs - bf_lo(h0), -mean * rs), one), hx = __shfl_xor_sync(~0u, h0, 1), lx = __shfl_xor_sync(~0u, l0, 1);
      const uint32_t rh[2] = {odd ? hx : h0, odd ? h0 : hx};
      const uint32_t rl[2] = {__byte_perm(odd ? lx : l0, 0, 0x1010), __byte_perm(odd ? l0 : lx, 0, 0x1010)};
      const uint32_t nm[2] = {__byte_perm(odd ? lx : l0, 0, 0x3232), __byte_perm(odd ? l0 : lx, 0, 0x3232)};
      uint32_t h[32];
#pragma unroll
      for (int a = 0; a < 4; a++) {
        const uint32_t A[4] = {tA[a].x, tA[a].y, tA[a].z, tA[a].w}, B[4] = {tS[a].x, tS[a].y, tS[a].z, tS[a].w};
#pragma unroll
        for (int i = 0; i < 8; i++) {
          const uint32_t w = xw[a * 8 + (i & 3) * 2 + (i >> 2)];
          h[a * 8 + i] = fma_bf16x2(fma_bf16x2(w, rh[i >> 2], fma_bf16x2(w, rl[i >> 2], nm[i >> 2])), A[i & 3], B[i & 3]);
        }
      }
      uint4* cp = &S->rowsH[(bq >> 3) * 256 + (bq & 7) * 16 + q4];
#pragma unroll
      for (int i = 0; i < 32; i++) asm volatile("" : "+r"(h[i]));
      asm volatile("" : "+l"(cp));
      mbar_wait(BAR(B_BK), 0);
      STAMP(5);
      const float2 bk = lds64(sb + BK_OFF);
#pragma unroll
      for (int r = 0; r < 2; r++) {
        const bool second = row0 + 8 * r == __float_as_int(bk.y);
        if (second || row0 + 8 * r == __float_as_int(bk.x)) {
#pragma unroll
          for (int a = 0; a < 4; a++) st_msg(cp + (second ? 128 : 0) + a * 4, h[a * 8 + r * 4], h[a * 8 + r * 4 + 1], h[a * 8 + r * 4 + 2], h[a * 8 + r * 4 + 3]);
        }
      }
      mbar_wait(BAR(B_DN), 0);
#pragma unroll
      for (int a = 0; a < 4; a++) {
        const uint4 tG = lds128u(tq + T_G + a * 64);
        const uint32_t G[4] = {tG.x, tG.y, tG.z, tG.w};
#pragma unroll
        for (int i = 0; i < 8; i++) xw[a * 8 + i] = fma_bf16x2(G[i >> 1], h[a * 8 + (i & 1) * 4 + (i >> 1)], xw[a * 8 + i]);
#pragma unroll
        for (int k = 0; k < 2; k++) stsm_x4((so ^ ((((a & 1) * 2) + k) << 5)) + E_OFF + cwarp * 2048 + (a >> 1) * 2048, xw + a * 8 + k * 4);
      }
    }
    fence_async_smem();
    if (elect_one()) mbar_arrive(BAR(B_PREADY));
    STAMP(6);
    if (tid == 128) TRACE(15);
    if (role >> 16) {
      const char* hp = reinterpret_cast<const char*>(&S->rowsH[(cwarp >> 1) * 4 + q4]) + (cwarp & 1) * 8;
      uint32_t db = sb + DN_OFF + (cwarp + (cwarp == 7) * 4) * 8192 + ((ln & 7) + (ln >> 4) * 8) * 128 + ((((ln >> 3) & 1) ^ (ln & 7)) << 4), sa = sb + SEL_OFF + 8 + (gq & 1) * 4;
      asm volatile("" : "+l"(hp), "+r"(db), "+r"(sa));
      STAMP(7);
      mbar_wait(BAR(B_SEL), 0);
      STAMP(8);
      { const uint32_t off = lds32u(sa); hp += off; db += off >> 31; }
      uint2 hb[8];
#pragma unroll
      for (int i = 0; i < 8; i++) hb[i] = ld_msg8(hp + i * 256);
      STAMP(9);
#pragma unroll
      for (int i = 0; i < 16; i++) ldsm_x4_t((db ^ (((i >> 1) & 3) << 5)) + (i >> 3) * 4096 + (i & 1) * 2048, df + i * 4);
      int it = 0;
      while (!__all_sync(~0u, max(max(max(hb[0].x, hb[1].x), max(hb[2].x, hb[3].x)), max(max(hb[4].x, hb[5].x), max(hb[6].x, hb[7].x))) != SENT)) {
#pragma unroll
        for (int i = 0; i < 8; i++) hb[i] = ld_msg8(hp + i * 256);
        SPIN_CHECK(it);
      }
      if (tid == 128) TRACE(16);
      STAMP(10);
      float c[4][4];
#pragma unroll
      for (int i = 0; i < 4; i++) c[i][0] = c[i][1] = c[i][2] = c[i][3] = 0.f;
#pragma unroll
      for (int ks = 0; ks < 8; ks++) {
        const uint32_t b0 = hb[ks].x, b1 = hb[ks].y;
        mma_16816(c[0], wf + ks * 8, b0, b1); mma_16816(c[1], wf + ks * 8 + 4, b0, b1);
        mma_16816(c[2], uf + ks * 8, b0, b1); mma_16816(c[3], uf + ks * 8 + 4, b0, b1);
      }
      {
        float v[4];
#pragma unroll
        for (int i = 0; i < 4; i++) v[i] = (q4 & 2) ? (odd ? c[3][i] : c[2][i]) : (odd ? c[1][i] : c[0][i]);
        sts128(sb + RED_OFF + cwarp * 512 + (q4 * 8 + (gq ^ (q4 * 2))) * 16, v[0], v[2], v[1], v[3]);
      }
      uint2* pp = reinterpret_cast<uint2*>(&S->part[((cwarp * 16 + q4 * 2) * 128 + ((role >> 8) & 255)) * 4]) + gq;
      uint32_t ra = sb + RED_OFF + ((ln * 8) ^ ((ln & 16) * 2));
      asm volatile("" : "+l"(pp), "+r"(ra));
      STAMP(11);
      named_bar<2, 256>();
      STAMP(12);
      float g0 = 0.f, g1 = 0.f, u0 = 0.f, u1 = 0.f;
#pragma unroll
      for (int w = 0; w < 8; w++) {
        const float2 gv = lds64(ra + w * 512), uv = lds64((ra ^ 64) + w * 512 + 256);
        g0 += gv.x; g1 += gv.y; u0 += uv.x; u1 += uv.y;
      }
      const uint32_t gp = pack_bf16(g0, g1), up = pack_bf16(u0, u1), sp = pack_bf16(silu_f(bf_lo(gp)), silu_f(bf_hi(gp)));
      const uint32_t act = pack_bf16(bf_lo(sp) * bf_lo(up), bf_hi(sp) * bf_hi(up));
      uint32_t ab[4];
#pragma unroll
      for (int i = 0; i < 4; i++) ab[i] = __shfl_sync(~0u, act, i * 8 + q4 * 2 + (gq & 1));
      if (tid == 128) TRACE(31);
      STAMP(13);
#pragma unroll
      for (int T = 0; T < 2; T++) {
#pragma unroll
        for (int i = 0; i < 4; i++) {
          c[i][0] = c[i][1] = c[i][2] = c[i][3] = 0.f;
          mma_16816(c[i], df + (T * 4 + i) * 8, ab[0], ab[1]); mma_16816(c[i], df + (T * 4 + i) * 8 + 4, ab[2], ab[3]);
        }
        float v[4];
#pragma unroll
        for (int i = 0; i < 4; i++) v[i] = (q4 & 2) ? (odd ? c[3][i] : c[2][i]) : (odd ? c[1][i] : c[0][i]);
        st_msg8(pp + T * 8192, __float_as_uint(v[0]), __float_as_uint(v[2])); st_msg8(pp + T * 8192 + 1024, __float_as_uint(v[1]), __float_as_uint(v[3]));
      }
      if (tid == 128) TRACE(32);
      STAMP(14);
    }
    if (cwarp == 0) {
      const unsigned t0 = clk32();
      mbar_wait(BAR(B_FIN), 0);
      const int fc = q4 * 2 + ((ln >> 2) & 1) + (ln & 8);
      const float2 fo = lds64(sb + PFLAG_OFF + fc * 8);
      const float sg = __uint_as_float(lds32u(sb + CST_OFF));
      __nv_bfloat16* op = out + (size_t)lds32u(sb + SEL_OFF + (bq & 1) * 4) * D_ + (bq >> 1) * 16 + fc;
      const uint4* ip = &S->part[bq * 512 + ln];
      asm volatile("" : "+l"(op), "+l"(ip));
      if (role >> 16) { while (clk32() - t0 < FK_PDELAY) {} } else spin(FK_PDELAY + 600);
      int it = 0;
      uint4 m[14];
      while (true) {
        bool ok = true;
#pragma unroll
        for (int i = 0; i < 14; i++) { m[i] = ld_msg(ip + i * 32); ok &= m[i].x != SENT && m[i].z != SENT; }
        if (__all_sync(~0u, ok)) break;
        SPIN_CHECK(it);
      }
      if (lane == 0) TRACE(33);
      STAMP(15);
      float y[4] = {0.f, 0.f, 0.f, 0.f};
#pragma unroll
      for (int i = 0; i < 14; i++) { y[0] += __uint_as_float(m[i].x); y[1] += __uint_as_float(m[i].y); y[2] += __uint_as_float(m[i].z); y[3] += __uint_as_float(m[i].w); }
      const bool b2 = ln & 4;
      float y0 = (b2 ? y[2] : y[0]) + __shfl_xor_sync(~0u, b2 ? y[0] : y[2], 4), y1 = (b2 ? y[3] : y[1]) + __shfl_xor_sync(~0u, b2 ? y[1] : y[3], 4);
      y0 = ((ln & 8) ? y1 : y0) + __shfl_xor_sync(~0u, (ln & 8) ? y0 : y1, 8);
      y0 += __shfl_xor_sync(~0u, y0, 16);
      const float upd = round_bf16(round_bf16(y0) * sg);
      if (ln < 16) *op = __float2bfloat16_rn(fmaf(fo.y, upd, fo.x));
      if (lane == 0) {
        TRACE(34); TRACE_CLK(122);
      }
    }
  }
}

typedef CUresult (*PFN_encodeTiled)(CUtensorMap*, CUtensorMapDataType, cuuint32_t, void*, const cuuint64_t*, const cuuint64_t*,
                                    const cuuint32_t*, const cuuint32_t*, CUtensorMapInterleave, CUtensorMapSwizzle,
                                    CUtensorMapL2promotion, CUtensorMapFloatOOBfill);

static void mapnd(PFN_encodeTiled enc, CUtensorMap* m, const void* p, int nd, const cuuint64_t* dims, const cuuint64_t* str, const cuuint32_t* box,
                  CUtensorMapSwizzle sw, CUtensorMapL2promotion pr) {
  const cuuint32_t es[5] = {1, 1, 1, 1, 1};
  enc(m, CU_TENSOR_MAP_DATA_TYPE_BFLOAT16, nd, (void*)p, dims, str, box, es, CU_TENSOR_MAP_INTERLEAVE_NONE, sw, pr, CU_TENSOR_MAP_FLOAT_OOB_FILL_NONE);
}
static void map2d(PFN_encodeTiled enc, CUtensorMap* m, const void* p, uint64_t rows, uint64_t cols, uint32_t brows, uint32_t bcols,
                  CUtensorMapSwizzle sw = CU_TENSOR_MAP_SWIZZLE_128B, CUtensorMapL2promotion pr = CU_TENSOR_MAP_L2_PROMOTION_L2_128B) {
  const cuuint64_t dims[2] = {cols, rows}, str[1] = {cols * 2}; const cuuint32_t box[2] = {bcols, brows};
  mapnd(enc, m, p, 2, dims, str, box, sw, pr);
}
static void map3d(PFN_encodeTiled enc, CUtensorMap* m, const void* p, uint64_t rows, uint64_t cols, uint32_t brows, uint32_t bgroups) {
  const cuuint64_t dims[3] = {64, rows, cols / 64}, str[2] = {cols * 2, 128}; const cuuint32_t box[3] = {64, brows, bgroups};
  mapnd(enc, m, p, 3, dims, str, box, CU_TENSOR_MAP_SWIZZLE_128B, CU_TENSOR_MAP_L2_PROMOTION_L2_128B);
}

}

extern "C" void kernel_launch(void* const* d_in, const int* in_sizes, int n_in, void* d_out, int out_size) {
  using namespace fk;
  (void)in_sizes; (void)n_in; (void)out_size;
  static PFN_encodeTiled enc = nullptr;
  static Scratch* scr = nullptr;
  if (!enc) {
    void* fn = nullptr; cudaDriverEntryPointQueryResult qr;
    cudaGetDriverEntryPoint("cuTensorMapEncodeTiled", &fn, cudaEnableDefault, &qr);
    enc = (PFN_encodeTiled)fn;
    cudaGetSymbolAddress((void**)&scr, g_scr);
    cudaFuncSetAttribute(fused_kernel, cudaFuncAttributeMaxDynamicSharedMemorySize, SMEM_BYTES);
  }
  typedef const __nv_bfloat16* bp;
  Params prm;
  prm.w_r = (bp)d_in[6];
  prm.wsp[0] = (const char*)d_in[1]; prm.wsp[1] = (const char*)d_in[2];
  map2d(enc, &prm.ws[0], d_in[1], S_, S_, 128, 64);
  map2d(enc, &prm.ws[1], d_in[2], S_, S_, 128, 64);
  map3d(enc, &prm.n, scr->n, S_, D_, 64, 2);
  map2d(enc, &prm.wm, d_in[11], D_, 6 * D_, 8, 256, CU_TENSOR_MAP_SWIZZLE_NONE, CU_TENSOR_MAP_L2_PROMOTION_L2_256B);
  map2d(enc, &prm.p, scr->P, 2 * S_, D_, 128, 64);
  map2d(enc, &prm.wd[0], d_in[3], D_, D_, 64, 64);
  map2d(enc, &prm.wd[1], d_in[4], D_, D_, 64, 64);
  map2d(enc, &prm.wg, d_in[7], D_, F_, 128, 32, CU_TENSOR_MAP_SWIZZLE_64B);
  map2d(enc, &prm.wu, d_in[8], D_, F_, 128, 32, CU_TENSOR_MAP_SWIZZLE_64B);
  for (int i = 0; i < 3; i++) prm.we[i] = (const char*)d_in[7 + i];
  map2d(enc, &prm.ps, scr->P, 2 * S_, D_, 32, 64);
  for (int i = 0; i < 2; i++) {
    const cuuint64_t dims[3] = {128, 8, i ? 2048u : 3584u}, str[2] = {256, 2048}; const cuuint32_t box[3] = {8, 1, 32};
    mapnd(enc, &prm.tch[i], d_in[i ? 0 : 9], 3, dims, str, box, CU_TENSOR_MAP_SWIZZLE_NONE, CU_TENSOR_MAP_L2_PROMOTION_L2_256B);
  }
  map3d(enc, &prm.xm, d_in[0], S_, D_, 16, 2);
  map3d(enc, &prm.om, d_out, S_, D_, 16, 2);
  {
    const cuuint64_t dims[5] = {64, 2, 8, 224, 16}, str[4] = {8 * 2048, 2048, 16 * 2048, 128}; const cuuint32_t box[5] = {64, 2, 8, 2, 2};
    mapnd(enc, &prm.wdn, d_in[9], 5, dims, str, box, CU_TENSOR_MAP_SWIZZLE_128B, CU_TENSOR_MAP_L2_PROMOTION_L2_128B);
  }

  fused_kernel<<<NCTA, 384, SMEM_BYTES, cudaStreamPerThread>>>((bp)d_in[0], scr, (__nv_bfloat16*)d_out, (bp)d_in[10], (bp)d_in[3], (bp)d_in[4], prm);
}
```

```cpp
#include <cuda_runtime.h>
#include <cuda_bf16.h>
#include <cuda.h>
#include <stdint.h>

#define DEVINL __device__ __forceinline__

namespace fk {

constexpr int S_ = 2048, D_ = 1024, F_ = 3584;
constexpr int NCTA = 128;
constexpr int SLOT = 16384;
constexpr int STAGE = 3 * SLOT;
constexpr int BUF = 2 * SLOT;
constexpr int E_OFF = 5 * BUF;
constexpr int SP_OFF = 4 * STAGE;
constexpr int MISC_OFF = SP_OFF + 32768;
constexpr int SMEM_BYTES = MISC_OFF + 3072;
constexpr int BAR_OFF = MISC_OFF;
constexpr int SEL_OFF = MISC_OFF + 344;
constexpr int BK_OFF = MISC_OFF + 360;
constexpr int CST_OFF = MISC_OFF + 368;
constexpr int PFLAG_OFF = MISC_OFF + 384;
constexpr int TAB_OFF = MISC_OFF + 512;
enum { T_WH = 0, T_ONE = 320, T_WL = 576, T_GA = 896, T_A = 1152, T_S = 1408, T_G = 1664 };
constexpr int KEY_OFF = TAB_OFF + 2048;
constexpr int POLL_OFF = TAB_OFF + 256;
constexpr int T1_OFF = TAB_OFF + 1536;
constexpr int RKA_OFF = BUF;
constexpr int RKB_OFF = RKA_OFF + 2048;
constexpr int RED_OFF = RKB_OFF + 2048;
constexpr int DN_OFF = RED_OFF + 4096;

enum { B_FULL = 0, B_EMPTY = 4, B_PREADY = 8, B_MF = 12  , B_FULL2 = 20  , B_EMPTY2 = 25  , B_A29 = 30, B_ADONE = 31,
       B_RSDONE = 32, B_TAB = 33, B_B27 = 34, B_SEL = 35, B_DN = 36, B_EFULL = 37, B_PS = 38  , B_WF = 40, B_BK = 41, B_FIN = 42, B_NUM = 43 };
constexpr unsigned long long CNT0 = 0x1111888855551111ull, CNT1 = 0x4244444222221111ull, CNT2 = 0x1111111111111112ull;

#define FK_SKIP 0
#define FK_X 0
#define FK_PS0 1
#define FK_XN 0
#define FK_S1 0
#define FK_NL 15
#define FK_XD 0
#define FK_GS 1
#define FK_TD 0
#define FK_TX 1
#define FK_ODELAY 100
#define FK_OMASK 0
#define FK_OSPACE2 0
#define FK_REL 0x14
#define FK_WSPF 22
#define FK_SPACE 300
#define FK_OSPACE 200
#define FK_NOMC 4
#define FK_TR0 0
#define FK_G0 5
#define FK_NA 6
#define FK_PACE 800
#define FK_QP 3
#define FK_PSPACE 400
#define FK_ORD 0
#define FK_PDELAY 700
constexpr int SPIN_LIMIT = 1 << 20;
constexpr uint32_t SENT = 0xFFFFFFFFu;

struct Scratch {
  uint4 part[128 * 128 * 4];
  uint4 stats[128 * 128];
  uint4 rowsH[32 * 128];
  uint4 rowsB[32 * 128];
  uint4 cand[16 * 8];
  uint2 rs[2 * S_];
  uint4 cst[8];
  float mod[2][6 * D_];
  uint2 u[2 * D_];
  unsigned flagP[128 * 4 * 8];
  unsigned cntN[12 * 32];
  unsigned cntMod[2 * 32];
  unsigned epoch[32];
  unsigned claim[64 * 8];
  alignas(1024) __nv_bfloat16 n[S_ * D_];
  __nv_bfloat16 P[2 * S_ * D_];
};
__device__ __align__(1024) Scratch g_scr;

struct Params {
  CUtensorMap ws[2];
  CUtensorMap n;
  CUtensorMap wm;
  CUtensorMap p;
  CUtensorMap wg, wu;
  CUtensorMap xm;
  CUtensorMap wdn;
  CUtensorMap wd[2];
  CUtensorMap om;
  CUtensorMap ps;
  CUtensorMap tch[2];
  const __nv_bfloat16* w_r;
  const char* wsp[2];
  const char* we[3];
};

DEVINL uint32_t smem_u32(const void* p) { return (uint32_t)__cvta_generic_to_shared(p); }
DEVINL void mbar_init(uint32_t bar, uint32_t cnt) { asm volatile("mbarrier.init.shared::cta.b64 [%0], %1;" ::"r"(bar), "r"(cnt) : "memory"); }
DEVINL void mbar_expect_tx(uint32_t bar, uint32_t bytes) { asm volatile("mbarrier.arrive.expect_tx.shared::cta.b64 _, [%0], %1;" ::"r"(bar), "r"(bytes) : "memory"); }
DEVINL void mbar_arrive(uint32_t bar) { asm volatile("mbarrier.arrive.shared::cta.b64 _, [%0];" ::"r"(bar) : "memory"); }
DEVINL void mbar_wait(uint32_t bar, uint32_t parity) {
  asm volatile("{\n.reg .pred p;\n.reg .u32 c;\nmov.u32 c, 0;\n"
               "LW:\nmbarrier.try_wait.parity.shared::cta.b64 p, [%0], %1;\n@p bra LD;\n"
               "add.u32 c, c, 1;\nsetp.lt.u32 p, c, 1048576;\n@p bra LW;\ntrap;\nLD:\n}" ::"r"(bar), "r"(parity) : "memory");
}
DEVINL void mbar_wait_cluster(uint32_t bar, uint32_t parity) {
  asm volatile("{\n.reg .pred p;\n.reg .u32 c;\nmov.u32 c, 0;\n"
               "LW:\nmbarrier.try_wait.parity.acquire.cluster.shared::cta.b64 p, [%0], %1;\n@p bra LD;\n"
               "add.u32 c, c, 1;\nsetp.lt.u32 p, c, 1048576;\n@p bra LW;\ntrap;\nLD:\n}" ::"r"(bar), "r"(parity) : "memory");
}
#define SPIN_CHECK(it) if (++(it) > SPIN_LIMIT) __trap()
DEVINL void fence_async_smem() { asm volatile("fence.proxy.async.shared::cta;" ::: "memory"); }
DEVINL void fence_async_global() { asm volatile("fence.proxy.async.global;" ::: "memory"); }
template <int BIT> DEVINL void rel_fence() { if ((FK_REL >> BIT) & 1) asm volatile("fence.acq_rel.gpu;" ::: "memory"); }
DEVINL void fence_gpu() { asm volatile("fence.acq_rel.gpu;" ::: "memory"); }
template <int ID, int N> DEVINL void named_bar() { asm volatile("bar.sync %0, %1;" ::"n"(ID), "n"(N) : "memory"); }
DEVINL bool elect_one() { uint32_t p; asm volatile("{\n.reg .pred e;\nelect.sync _|e, 0xffffffff;\nselp.u32 %0, 1, 0, e;\n}" : "=r"(p)); return p; }
DEVINL unsigned clk32() { unsigned c; asm volatile("mov.u32 %0, %%clock;" : "=r"(c)); return c; }
#define FK_GRIDW 32
#define FK_GRID 0
DEVINL void grid_wait() {
  if (FK_GRID) {
    unsigned t0, t1;
    asm volatile("mov.u32 %0, %%globaltimer_lo;" : "=r"(t0));
    do { asm volatile("mov.u32 %0, %%globaltimer_lo;" : "=r"(t1)); } while (((t0 - FK_GRIDW) ^ t1) < FK_GRID + 0u + !FK_GRID);
  }
}
DEVINL void spin(unsigned n) { const unsigned c = clk32(); while (clk32() - c < n) {} }

constexpr uint64_t POL_NORMAL = 0x1000000000000000ull, POL_FIRST = 0x12F0000000000000ull;
#define FK_HINTS 0x30B
template <int BIT> DEVINL constexpr uint64_t pol() { return ((FK_HINTS >> BIT) & 1) ? POL_FIRST : POL_NORMAL; }
DEVINL void tma_2d(uint32_t dst, const CUtensorMap* m, int x, int y, uint32_t bar, uint64_t pol) {
  asm volatile("cp.async.bulk.tensor.2d.shared::cluster.global.mbarrier::complete_tx::bytes.L2::cache_hint [%0], [%1, {%3, %4}], [%2], %5;"
               ::"r"(dst), "l"(m), "r"(bar), "r"(x), "r"(y), "l"(pol) : "memory");
}
DEVINL void tma_3d(uint32_t dst, const CUtensorMap* m, int y, int z, uint32_t bar, uint64_t pol) {
  asm volatile("cp.async.bulk.tensor.3d.shared::cluster.global.mbarrier::complete_tx::bytes.L2::cache_hint [%0], [%1, {0, %3, %4}], [%2], %5;"
               ::"r"(dst), "l"(m), "r"(bar), "r"(y), "r"(z), "l"(pol) : "memory");
}
DEVINL void tma_3d_mc(uint32_t dst, const CUtensorMap* m, int y, int z, uint32_t bar, uint64_t pol) {
  asm volatile("cp.async.bulk.tensor.3d.shared::cluster.global.mbarrier::complete_tx::bytes.multicast::cluster.L2::cache_hint [%0], [%1, {0, %3, %4}], [%2], %5, %6;"
               ::"r"(dst), "l"(m), "r"(bar), "r"(y), "r"(z), "h"((unsigned short)3), "l"(pol) : "memory");
}
DEVINL void tma_2d_mc(uint32_t dst, const CUtensorMap* m, int x, int y, uint32_t bar, uint64_t pol) {
  asm volatile("cp.async.bulk.tensor.2d.shared::cluster.global.mbarrier::complete_tx::bytes.multicast::cluster.L2::cache_hint [%0], [%1, {%3, %4}], [%2], %5, %6;"
               ::"r"(dst), "l"(m), "r"(bar), "r"(x), "r"(y), "h"((unsigned short)3), "l"(pol) : "memory");
}
DEVINL void tma_store_2d(const CUtensorMap* m, uint32_t src, int x, int y) {
  asm volatile("cp.async.bulk.tensor.2d.global.shared::cta.bulk_group [%0, {%2, %3}], [%1];" ::"l"(m), "r"(src), "r"(x), "r"(y) : "memory");
}
DEVINL void bulk_store(void* dst, uint32_t src, uint32_t bytes) {
  asm volatile("cp.async.bulk.global.shared::cta.bulk_group [%0], [%1], %2;" ::"l"(dst), "r"(src), "r"(bytes) : "memory");
}
DEVINL void bulk_load(uint32_t dst, const void* src, uint32_t bytes, uint32_t bar, uint64_t pol) {
  asm volatile("cp.async.bulk.shared::cluster.global.mbarrier::complete_tx::bytes.L2::cache_hint [%0], [%1], %2, [%3], %4;" ::"r"(dst), "l"(src), "r"(bytes), "r"(bar), "l"(pol) : "memory");
}
template <int N> DEVINL void bulk_wait_read() { asm volatile("cp.async.bulk.wait_group.read %0;" ::"n"(N) : "memory"); }
DEVINL void pf_bulk(const void* p, uint32_t bytes) { asm volatile("cp.async.bulk.prefetch.L2.global [%0], %1;" ::"l"(p), "r"(bytes) : "memory"); }
DEVINL void bulk_commit() { asm volatile("cp.async.bulk.commit_group;" ::: "memory"); }
template <int N> DEVINL void bulk_wait() { asm volatile("cp.async.bulk.wait_group %0;" ::"n"(N) : "memory"); }
DEVINL void prefetch_tmap(const CUtensorMap* m) { asm volatile("prefetch.tensormap [%0];" ::"l"(m) : "memory"); }

DEVINL void wg_fence() { asm volatile("wgmma.fence.sync.aligned;" ::: "memory"); }
DEVINL void wg_commit() { asm volatile("wgmma.commit_group.sync.aligned;" ::: "memory"); }
template <int N> DEVINL void wg_wait() { asm volatile("wgmma.wait_group.sync.aligned %0;" ::"n"(N) : "memory"); }
DEVINL uint32_t desc_lo(uint32_t addr, uint32_t lbo) { return ((addr & 0x3FFFF) >> 4) | ((lbo >> 4) << 16); }

#define R8(a, o) "+f"(a[o]), "+f"(a[o + 1]), "+f"(a[o + 2]), "+f"(a[o + 3]), "+f"(a[o + 4]), "+f"(a[o + 5]), "+f"(a[o + 6]), "+f"(a[o + 7])
#define R64(a, o) R8(a, o), R8(a, o + 8), R8(a, o + 16), R8(a, o + 24), R8(a, o + 32), R8(a, o + 40), R8(a, o + 48), R8(a, o + 56)
#define ACC64 "{%0, %1, %2, %3, %4, %5, %6, %7, %8, %9, %10, %11, %12, %13, %14, %15, "              \
              "%16, %17, %18, %19, %20, %21, %22, %23, %24, %25, %26, %27, %28, %29, %30, %31, "    \
              "%32, %33, %34, %35, %36, %37, %38, %39, %40, %41, %42, %43, %44, %45, %46, %47, "    \
              "%48, %49, %50, %51, %52, %53, %54, %55, %56, %57, %58, %59, %60, %61, %62, %63"
#define ACC128 ACC64 ", %64, %65, %66, %67, %68, %69, %70, %71, %72, %73, %74, %75, %76, %77, %78, %79, "      \
              "%80, %81, %82, %83, %84, %85, %86, %87, %88, %89, %90, %91, %92, %93, %94, %95, "               \
              "%96, %97, %98, %99, %100, %101, %102, %103, %104, %105, %106, %107, %108, %109, %110, %111, "   \
              "%112, %113, %114, %115, %116, %117, %118, %119, %120, %121, %122, %123, %124, %125, %126, %127"
template <int TB> DEVINL void wgmma_n256(float (&d)[128], uint32_t da, uint32_t db, int scale_d) {
  asm volatile("{\n.reg .pred p;\n.reg .b64 a, b;\nsetp.ne.b32 p, %130, 0;\nmov.b64 a, {%128, 0x40000040};\nmov.b64 b, {%129, 0x40000040};\n"
               "wgmma.mma_async.sync.aligned.m64n256k16.f32.bf16.bf16 " ACC128 "}, a, b, p, 1, 1, 0, %131;\n}\n"
               : R64(d, 0), R64(d, 64) : "r"(da), "r"(db), "r"(scale_d), "n"(TB));
}
template <int TB, int HI = 0x40000040> DEVINL void wgmma_n128(float (&d)[64], uint32_t da, uint32_t db) {
  asm volatile("{\n.reg .b64 a, b;\nmov.b64 a, {%64, %67};\nmov.b64 b, {%65, %67};\n"
               "wgmma.mma_async.sync.aligned.m64n128k16.f32.bf16.bf16 " ACC64 "}, a, b, 1, 1, 1, 0, %66;\n}\n" : R64(d, 0) : "r"(da), "r"(db), "n"(TB), "n"(HI));
}
template <int SC> DEVINL void wgmma_n128_rs(float (&d)[64], const uint32_t* a, uint32_t db) {
  asm volatile("{\n.reg .pred p;\n.reg .b64 b;\nsetp.ne.b32 p, %69, 0;\nmov.b64 b, {%68, 0x40000040};\n"
               "wgmma.mma_async.sync.aligned.m64n128k16.f32.bf16.bf16 " ACC64 "}, {%64, %65, %66, %67}, b, p, 1, 1, 0;\n}\n"
               : R64(d, 0) : "r"(a[0]), "r"(a[1]), "r"(a[2]), "r"(a[3]), "r"(db), "n"(SC));
}
template <int N> DEVINL void reg_fence(float (&a)[N]) {
#pragma unroll
  for (int i = 0; i < N; i++) asm volatile("" : "+f"(a[i])::"memory");
}

DEVINL uint32_t pack_bf16(float lo, float hi) { uint32_t r; asm("cvt.rn.bf16x2.f32 %0, %1, %2;" : "=r"(r) : "f"(hi), "f"(lo)); return r; }
DEVINL uint32_t add_bf16x2(uint32_t a, uint32_t b) { uint32_t r; asm("add.rn.bf16x2 %0, %1, %2;" : "=r"(r) : "r"(a), "r"(b)); return r; }
DEVINL uint32_t mul_bf16x2(uint32_t a, uint32_t b) { uint32_t r; asm("mul.rn.bf16x2 %0, %1, %2;" : "=r"(r) : "r"(a), "r"(b)); return r; }
DEVINL uint32_t fma_bf16x2(uint32_t a, uint32_t b, uint32_t c) { uint32_t r; asm("fma.rn.bf16x2 %0, %1, %2, %3;" : "=r"(r) : "r"(a), "r"(b), "r"(c)); return r; }
DEVINL float bf_lo(uint32_t w) { return __uint_as_float(w << 16); }
DEVINL float bf_hi(uint32_t w) { return __uint_as_float(w & 0xFFFF0000u); }
DEVINL float round_bf16(float v) { return bf_lo(pack_bf16(v, 0.f)); }
DEVINL float sigmoid_f(float v) { float r; asm("rcp.approx.ftz.f32 %0, %1;" : "=f"(r) : "f"(1.f + __expf(-v))); return r; }
DEVINL float rsqrt_f(float v) { float r; asm("rsqrt.approx.ftz.f32 %0, %1;" : "=f"(r) : "f"(v)); return r; }
DEVINL float silu_f(float v) { return v * sigmoid_f(v); }
DEVINL void stsm_x4(uint32_t addr, const uint32_t* r) {
  asm volatile("stmatrix.sync.aligned.m8n8.x4.shared.b16 [%0], {%1, %2, %3, %4};" ::"r"(addr), "r"(r[0]), "r"(r[1]), "r"(r[2]), "r"(r[3]) : "memory");
}
DEVINL void ldsm_x4(uint32_t addr, uint32_t* r) {
  asm volatile("ldmatrix.sync.aligned.m8n8.x4.shared.b16 {%0, %1, %2, %3}, [%4];" : "=r"(r[0]), "=r"(r[1]), "=r"(r[2]), "=r"(r[3]) : "r"(addr) : "memory");
}
DEVINL void ldsm_x4_t(uint32_t addr, uint32_t* r) {
  asm volatile("ldmatrix.sync.aligned.m8n8.x4.trans.shared.b16 {%0, %1, %2, %3}, [%4];" : "=r"(r[0]), "=r"(r[1]), "=r"(r[2]), "=r"(r[3]) : "r"(addr) : "memory");
}
DEVINL void mma_16816(float (&c)[4], const uint32_t* a, uint32_t b0, uint32_t b1) {
  asm("mma.sync.aligned.m16n8k16.row.col.f32.bf16.bf16.f32 {%0, %1, %2, %3}, {%4, %5, %6, %7}, {%8, %9}, {%0, %1, %2, %3};"
      : "+f"(c[0]), "+f"(c[1]), "+f"(c[2]), "+f"(c[3]) : "r"(a[0]), "r"(a[1]), "r"(a[2]), "r"(a[3]), "r"(b0), "r"(b1));
}
DEVINL void mma_1688(float (&c)[4], uint32_t a0, uint32_t a1, uint32_t b0) {
  asm("mma.sync.aligned.m16n8k8.row.col.f32.bf16.bf16.f32 {%0, %1, %2, %3}, {%4, %5}, {%6}, {%0, %1, %2, %3};"
      : "+f"(c[0]), "+f"(c[1]), "+f"(c[2]), "+f"(c[3]) : "r"(a0), "r"(a1), "r"(b0));
}
DEVINL float4 lds128(uint32_t a) { float4 v; asm volatile("ld.shared.v4.f32 {%0, %1, %2, %3}, [%4];" : "=f"(v.x), "=f"(v.y), "=f"(v.z), "=f"(v.w) : "r"(a)); return v; }
DEVINL uint4 lds128u(uint32_t a) { uint4 v; asm volatile("ld.shared.v4.u32 {%0, %1, %2, %3}, [%4];" : "=r"(v.x), "=r"(v.y), "=r"(v.z), "=r"(v.w) : "r"(a)); return v; }
DEVINL float2 lds64(uint32_t a) { float2 v; asm volatile("ld.shared.v2.f32 {%0, %1}, [%2];" : "=f"(v.x), "=f"(v.y) : "r"(a)); return v; }
DEVINL uint32_t lds32u(uint32_t a) { uint32_t v; asm volatile("ld.shared.u32 %0, [%1];" : "=r"(v) : "r"(a)); return v; }
DEVINL void sts128(uint32_t a, float x, float y, float z, float w) { asm volatile("st.shared.v4.f32 [%0], {%1, %2, %3, %4};" ::"r"(a), "f"(x), "f"(y), "f"(z), "f"(w) : "memory"); }
DEVINL void sts128u(uint32_t a, uint32_t x, uint32_t y, uint32_t z, uint32_t w) { asm volatile("st.shared.v4.u32 [%0], {%1, %2, %3, %4};" ::"r"(a), "r"(x), "r"(y), "r"(z), "r"(w) : "memory"); }
DEVINL void sts64u(uint32_t a, uint32_t x, uint32_t y) { asm volatile("st.shared.v2.u32 [%0], {%1, %2};" ::"r"(a), "r"(x), "r"(y) : "memory"); }
DEVINL void sts32v(uint32_t a, uint32_t v) { asm volatile("st.volatile.shared.u32 [%0], %1;" ::"r"(a), "r"(v) : "memory"); }
DEVINL void sts32(uint32_t a, float v) { asm volatile("st.shared.f32 [%0], %1;" ::"r"(a), "f"(v) : "memory"); }

DEVINL uint4 ld_msg(const void* p) {
  unsigned long long a, b;
  asm volatile("{\n.reg .b128 r;\nld.relaxed.gpu.global.b128 r, [%2];\nmov.b128 {%0, %1}, r;\n}" : "=l"(a), "=l"(b) : "l"(p) : "memory");
  return make_uint4((uint32_t)a, (uint32_t)(a >> 32), (uint32_t)b, (uint32_t)(b >> 32));
}
DEVINL void st_msg(void* p, uint32_t x, uint32_t y, uint32_t z, uint32_t w) {
  unsigned long long a = (unsigned long long)x | ((unsigned long long)y << 32), b = (unsigned long long)z | ((unsigned long long)w << 32);
  asm volatile("{\n.reg .b128 r;\nmov.b128 r, {%1, %2};\nst.relaxed.gpu.global.b128 [%0], r;\n}" ::"l"(p), "l"(a), "l"(b) : "memory");
}
DEVINL uint2 ld_msg8(const void* p) {
  unsigned long long a;
  asm volatile("ld.relaxed.gpu.global.b64 %0, [%1];" : "=l"(a) : "l"(p) : "memory");
  return make_uint2((uint32_t)a, (uint32_t)(a >> 32));
}
DEVINL void st_msg8(void* p, uint32_t x, uint32_t y) {
  asm volatile("st.relaxed.gpu.global.b64 [%0], %1;" ::"l"(p), "l"((unsigned long long)x | ((unsigned long long)y << 32)) : "memory");
}
DEVINL unsigned ld_rlx(const void* p) { unsigned v; asm volatile("ld.relaxed.gpu.global.u32 %0, [%1];" : "=r"(v) : "l"(p) : "memory"); return v; }
DEVINL void st_rlx(unsigned* p, unsigned v) { asm volatile("st.relaxed.gpu.global.u32 [%0], %1;" ::"l"(p), "r"(v) : "memory"); }
DEVINL void red_add(unsigned* p, unsigned v) { asm volatile("red.relaxed.gpu.global.add.u32 [%0], %1;" ::"l"(p), "r"(v) : "memory"); }
DEVINL uint4 ldg_nc(const void* p) {
  uint4 v;
  asm volatile("ld.global.nc.L1::no_allocate.v4.u32 {%0, %1, %2, %3}, [%4];" : "=r"(v.x), "=r"(v.y), "=r"(v.z), "=r"(v.w) : "l"(p));
  return v;
}
DEVINL float4 ldg_cg(const float* p) { float4 v; asm volatile("ld.global.cg.v4.f32 {%0, %1, %2, %3}, [%4];" : "=f"(v.x), "=f"(v.y), "=f"(v.z), "=f"(v.w) : "l"(p) : "memory"); return v; }
DEVINL void wait_cnt(const unsigned* p, unsigned target) {
  int it = 0;
  while ((int)(ld_rlx(p) - target) < 0) { SPIN_CHECK(it); __nanosleep(100); }
}

#define TRACE2(id)
#define TRACE3(id)
#define TRACE(id)
#define TRACE_CLK(id)

#define STAMP2(i)
#define STAMP(i)
DEVINL uint32_t fkey(float v) { const uint32_t u = __float_as_uint(v); return (u & 0x80000000u) ? ~u : (u | 0x80000000u); }
DEVINL float fkey_inv(uint32_t k) { return __uint_as_float((k & 0x80000000u) ? (k & 0x7FFFFFFFu) : ~k); }
DEVINL uint32_t redux_max(uint32_t v) { uint32_t r; asm volatile("redux.sync.max.u32 %0, %1, 0xffffffff;" : "=r"(r) : "r"(v)); return r; }
DEVINL void warp_top2(uint32_t key, uint32_t& k1, uint32_t& k2) { k1 = redux_max(key); k2 = redux_max(key == k1 ? 0u : key); }
DEVINL int key_row(uint32_t k) { return 2047 - (int)(k & 2047u); }
DEVINL int blk_src(int q, int cgrp) { const int f = q - 4, kk = (f * 37) >> 8, i = f - kk * 7; return f < 0 ? cgrp * 4 + q : (FK_SKIP ? i + (i >= cgrp) : i == cgrp ? 7 : i) * 4 + kk; }
DEVINL void split_assign(int c, int& grp, int& gi) {
  const int c7 = ((c - 36) * 37) >> 8;
  grp = c < 4 ? 0 : c < 36 ? (c - 4) & 7 : c - 35 - c7 * 7; gi = c < 4 ? c + 4 : c < 36 ? (c - 4) >> 3 : c7 + 4;
}
DEVINL uint32_t pstage(int kk) { return ((0xABA4 >> (kk * 4)) & 15) * SLOT; }
DEVINL uint32_t buf_off(int u) { return ((0x42130 >> (u * 4)) & 15) * BUF; }
DEVINL int cnt_idx(int kb) { return kb < 4 ? (8 + kb) * 32 : (kb >> 2) * 32 + (kb & 3); }

__global__ void __launch_bounds__(384, 1) __cluster_dims__(2, 1, 1)
fused_kernel(const __nv_bfloat16* __restrict__ x, Scratch* const S, __nv_bfloat16* __restrict__ out, const __nv_bfloat16* __restrict__ cvec,
             const __nv_bfloat16* __restrict__ wd_re, const __nv_bfloat16* __restrict__ wd_im, const __grid_constant__ Params prm) {
  extern __shared__ __align__(1024) uint8_t smem_raw[];
  const uint32_t sb = smem_u32(smem_raw);
  const int tid = threadIdx.x, lane = tid & 31;
  const int warp = __shfl_sync(~0u, tid >> 5, 0);
  const int bx = blockIdx.x, rank = bx & 1;
  auto BAR = [&](int i) { return sb + BAR_OFF + i * 8; };

  uint4 xr[8];
  if ((warp & ~1) == 2) {
    const uint4* src = reinterpret_cast<const uint4*>(x + (size_t)(bx * 2 + warp - 2) * D_) + lane;
#pragma unroll
    for (int i = 0; i < 4; i++) xr[i] = ldg_nc(src + 32 * i);
  }
  if (tid == 0) TRACE(0);
  if ((warp & ~1) != 2 && elect_one()) {
    const int w = warp < 2 ? warp : warp - 2;
#pragma unroll
    for (int k = 0; k < 5; k++) {
      const int i = w + 10 * k;
      if (i < B_NUM) mbar_init(BAR(i), (uint32_t)((i < 16 ? CNT0 : i < 32 ? CNT1 : CNT2) >> ((i & 15) * 4)) & 15u);
    }
    if (w < 4) mbar_expect_tx(BAR(B_FULL + w), STAGE);
    asm volatile("fence.mbarrier_init.release.cluster;" ::: "memory");
    if (w) prefetch_tmap(&prm.ws[1] + w);
  }
  if ((warp & ~1) != 2) { named_bar<4, 320>(); asm volatile("bar.arrive 3, 384;" ::: "memory"); }
  if (warp < 2 && elect_one()) {
    unsigned smid; asm volatile("mov.u32 %0, %%smid;" : "=r"(smid));
    int c = ((smid >> 1) + ((smid >> 1) >= 62 ? 2 : 4)) & 63;
    if (warp == 0) {
      int g0, i0; split_assign(c, g0, i0);
      asm volatile("cp.async.bulk.prefetch.tensor.2d.L2.global [%0, {0, %1}];" ::"l"(&prm.ws[i0 >> 2]), "r"((g0 * 2 + rank) * 128) : "memory");
    } else if (rank == 0) {
      int it = 0;
      while (atomicExch(&S->claim[c * 8], 1u)) { c = (c + 1) & 63; if (++it > 64) __trap(); }
      sts32v(sb + BK_OFF, c);
      asm volatile("fence.acq_rel.cta;" ::: "memory");
    }
  }
  uint32_t tag = 0;
  if (warp == 0) tag = ld_rlx(S->epoch);
  __syncwarp();
  asm volatile("barrier.cluster.arrive.relaxed.aligned;" ::: "memory");
  const uint32_t ring = sb + SP_OFF + (warp - 2) * 16384, mf = BAR(B_MF + (warp - 2) * 4);
  const int jw = bx >> 6, e0 = (bx & 63) * 16;
  const __nv_bfloat16* src = (jw ? wd_im : wd_re) + (size_t)e0 * D_;
  int nc = 0;
  if ((warp & ~1) == 2) {
#pragma unroll 1
    for (int G = 0; G < 8; G += (G == 0 && warp == 2) + 1) {
      if (G) { mbar_wait(mf + (nc & 3) * 8, (nc >> 2) & 1); nc++; }
      const uint32_t stg = ring + (nc & 3) * 4096, sl = stg + (G ? (lane >> 4) * 2048 + (lane & 15) * 16 : lane * 16), st = G ? 256 : 512;
      if (G) {
#pragma unroll
        for (int k = 0; k < 8; k++) xr[k] = lds128u(sl + k * 256);
      }
      float s0 = 0.f, s1 = 0.f, q0 = 0.f, q1 = 0.f, s2 = 0.f, s3 = 0.f, q2 = 0.f, q3 = 0.f;
      float v[64];
#pragma unroll
      for (int h = 0; h < 2; h++)
        if (h == 0 || G) {
#pragma unroll
          for (int k = 4 * h; k < 4 * h + 4; k++) {
            float* u = v + 8 * k;
            u[0] = bf_lo(xr[k].x); u[1] = bf_hi(xr[k].x); u[2] = bf_lo(xr[k].y); u[3] = bf_hi(xr[k].y);
            u[4] = bf_lo(xr[k].z); u[5] = bf_hi(xr[k].z); u[6] = bf_lo(xr[k].w); u[7] = bf_hi(xr[k].w);
#pragma unroll
            for (int i = 0; i < 8; i += 4) {
              s0 += u[i]; s1 += u[i + 1]; s2 += u[i + 2]; s3 += u[i + 3];
              q0 = fmaf(u[i], u[i], q0); q1 = fmaf(u[i + 1], u[i + 1], q1); q2 = fmaf(u[i + 2], u[i + 2], q2); q3 = fmaf(u[i + 3], u[i + 3], q3);
            }
          }
        }
      float sum = (s0 + s1) + (s2 + s3), sq = (q0 + q1) + (q2 + q3);
#pragma unroll
      for (int o = 1; o < 32; o <<= 1)
        if (o < 16 || !G) { sum += __shfl_xor_sync(~0u, sum, o); sq += __shfl_xor_sync(~0u, sq, o); }
      const float mean = sum * (1.f / D_);
      const float rstd = rsqrt_f(fmaxf(fmaf(-mean, mean, sq * (1.f / D_)), 0.f) + 1e-5f), nmr = -mean * rstd;
#pragma unroll
      for (int h = 0; h < 2; h++)
        if (h == 0 || G) {
#pragma unroll
          for (int k = 4 * h; k < 4 * h + 4; k++) {
            const float* u = v + 8 * k;
            sts128u(sl + k * st, pack_bf16(fmaf(u[0], rstd, nmr), fmaf(u[1], rstd, nmr)), pack_bf16(fmaf(u[2], rstd, nmr), fmaf(u[3], rstd, nmr)),
                    pack_bf16(fmaf(u[4], rstd, nmr), fmaf(u[5], rstd, nmr)), pack_bf16(fmaf(u[6], rstd, nmr), fmaf(u[7], rstd, nmr)));
          }
        }
      fence_async_smem();
      const int kq = bx >> 5;
      if (elect_one()) {
        bulk_store(S->n + (size_t)(G * 256 + bx * 2 + (G ? 0 : warp - 2)) * D_, stg, G ? 4096 : 2048); bulk_commit();
        if (G == 0) { bulk_wait<0>(); rel_fence<0>(); red_add(&S->cntN[cnt_idx(kq)], 1); TRACE(42 + warp); }
      }
      if (G == 0) named_bar<3, 384>();
      if (elect_one()) {
        if (G == 0 && warp == 2) mbar_wait(BAR(B_FULL), 0);
        if (G >= 4) { bulk_wait<1>(); red_add(&S->cntN[(G - 1) * 32 + kq], 2); }
#pragma unroll 1
        for (int k = G ? nc + 1 : 0; k < (warp == 2 ? nc + 2 : 1); k++) {
          mbar_expect_tx(mf + (k & 3) * 8, 4096);
          bulk_load(ring + ((k + 1) & 3) * 4096, k < 6 ? x + (size_t)((k + 4 - warp) * 256 + bx * 2) * D_ : src + (k - 6) * 2 * D_, 4096, mf + (k & 3) * 8, k < 6 ? pol<7>() : pol<2>());
        }
        if (G == 1 || G == 2 || G == 7) { bulk_wait<0>(); rel_fence<1>(); red_add(&S->cntN[G * 32 + kq], 2); if (G > 1) TRACE(44 + (G & 3)); }
      }
      __syncwarp();
      if (warp == 3 && G) break;
    }
  }
  asm volatile("barrier.cluster.wait.acquire.aligned;" ::: "memory");
  int cl, grp, gi;
  asm volatile("{\n.reg .b32 ra;\nmapa.shared::cluster.u32 ra, %1, 0;\nld.volatile.shared::cluster.u32 %0, [ra];\n}" : "=r"(cl) : "r"(sb + BK_OFF) : "memory");
  cl = __shfl_sync(~0u, cl, 0);
  split_assign(cl, grp, gi);
  const int j = gi >> 2, m4 = gi & 3, t = grp * 2 + rank;
  const int cgrp = m4 * 2 + j;
  const int b = t * 8 + cgrp;
  const bool moe = gi < 7;
  const int eb = (j ? 64 + grp * 6 : grp * 8) + m4 * 2 + rank;

  if (warp < 4) {
    auto prefetch_piece = [&](int p) { if (!(FK_X & 1)) pf_bulk(prm.we[p >> 3] + (size_t)((p & 7) * 128 + b) * 7168, 7168); };
    auto weight_box = [&](int n, uint32_t bar) {
      if (moe && !(FK_X & 2)) {
        asm volatile("mbarrier.expect_tx.relaxed.cta.shared::cta.b64 [%0], 8192;" ::"r"(bar) : "memory");
        tma_2d(sb + SP_OFF + (n & 3) * 8192, &prm.wg + (n >> 3), eb * 32, (n & 7) * 128, bar, pol<3>());
      }
    };
    if (warp == 0) {
      const unsigned* flagAddr = &S->cntN[cnt_idx(lane)];
      const unsigned tgt = (tag + 1) * 64u;
      if (elect_one()) tma_2d(sb, &prm.ws[j], 0, t * 128, BAR(B_FULL), pol<0>());
      unsigned ready = 0;
      if (lane >= 4) sts32v(sb + POLL_OFF + lane * 4, tgt - 1);
#pragma unroll 1
      for (int g = 0; g < 32; g++) {
        const int s = g & 3;
        const uint32_t sa = sb + s * STAGE, fb = BAR(B_FULL + s);
        if (!((ready >> g) & 1)) {
          unsigned v;
          asm volatile("ld.volatile.shared.u32 %0, [%1];" : "=r"(v) : "r"(sb + POLL_OFF + lane * 4) : "memory");
          ready |= __ballot_sync(~0u, v == tgt) & ~15u;
          int it = 0;
          while (!((ready >> g) & 1)) {
            ready |= __ballot_sync(~0u, (lane >> 2) == (g >> 2) && ld_rlx(flagAddr) == tgt);
            SPIN_CHECK(it);
          }
          fence_async_global();
        }
        if (g >= 4) {
          mbar_wait(BAR(B_EMPTY + s), ((g >> 2) - 1) & 1);
          if (lane < 8 && ((~ready >> (lane * 4)) & 15))
            asm volatile("cp.async.cg.shared.global [%0], [%1], 16;" ::"r"(sb + POLL_OFF + lane * 16), "l"(&S->cntN[lane * 32]) : "memory");
          if (elect_one()) { TRACE2(128 + g); mbar_expect_tx(fb, STAGE); tma_2d(sa, &prm.ws[j], g * 64, t * 128, fb, pol<0>()); }
        }
        if (elect_one()) {
          if (g < FK_NOMC) { tma_3d(sa + SLOT, &prm.n, g * 64, m4 * 4, fb, pol<4>()); tma_3d(sa + 2 * SLOT, &prm.n, g * 64, m4 * 4 + 2, fb, pol<4>()); }
          else tma_3d_mc(sa + SLOT + rank * SLOT, &prm.n, g * 64, m4 * 4 + rank * 2, fb, pol<4>());
          if (g > 0 && g < 4) tma_2d(sa, &prm.ws[j], g * 64, t * 128, fb, pol<0>());
          TRACE2(64 + g);
        }
        if ((unsigned)(g - FK_WSPF) < 4u)
          asm volatile("prefetch.global.L2 [%0];" ::"l"(prm.wsp[j] + (size_t)(t * 128 + m4 * 32 + (g - FK_WSPF) * 8 + (lane >> 2)) * 4096 + 3584 + (lane & 3) * 128));
      }
      asm volatile("cp.async.wait_all;" ::: "memory");
    }
    asm volatile("" ::: "memory");
    if (warp == 1) {
      tag = ld_rlx(S->epoch) + 1;
      if (elect_one()) prefetch_tmap(&prm.ps);
      const uint32_t rb = sb + (m4 * 32 + lane) * 128 + ((lane & 7) << 4);
      float a0 = 0.f, a1 = 0.f, a2 = 0.f, a3 = 0.f;
#pragma unroll 1
      for (int g = 0; g < 32; g++) {
        const int s = g & 3;
        mbar_wait(BAR(B_FULL + s), (g >> 2) & 1);
        uint4 u[8];
#pragma unroll
        for (int c = 0; c < 8; c++) u[c] = lds128u((rb + s * STAGE) ^ (c << 4));
        u[7].x = __shfl_sync(~0u, u[7].x, lane);
        if (elect_one()) {
          mbar_arrive(BAR(B_EMPTY + s)); TRACE2(160 + g);
          const int p = (g - FK_G0) >> FK_GS;
          if (g >= FK_G0 && !((g - FK_G0) & FK_GS) && (p < 8 ? moe && FK_TD : p < 12 && FK_TX)) {
            asm volatile("mbarrier.expect_tx.relaxed.cta.shared::cta.b64 [%0], 512;" ::"r"(BAR(B_RSDONE)) : "memory");
            tma_3d(sb + KEY_OFF, &prm.tch[p >> 3], p < 8 ? p : cgrp, p < 8 ? eb * 32 : t * 128 + (p - 8) * 32, BAR(B_RSDONE), POL_NORMAL);
          }
        }
#pragma unroll
        for (int c = 0; c < 8; c++) {
          a0 += bf_lo(u[c].x) + bf_lo(u[c].y); a1 += bf_hi(u[c].x) + bf_hi(u[c].y);
          a2 += bf_lo(u[c].z) + bf_lo(u[c].w); a3 += bf_hi(u[c].z) + bf_hi(u[c].w);
        }
      }
      if (lane == 0) mbar_arrive(BAR(B_RSDONE));
      mbar_wait(BAR(B_RSDONE), 0);
      st_msg8(&S->rs[j * S_ + t * 128 + m4 * 32 + lane], __float_as_uint((a0 + a1) + (a2 + a3)), tag);
    }
    asm volatile("" ::: "memory");
    if (warp >= 2) {
      tag = ld_rlx(S->epoch) + 1;
      float* const mod = S->mod[tag & 1];
      if (warp == 3) {
        const uint32_t stab = sb + TAB_OFF, stg = stab + 512;
        {
          const uint32_t cw = __ldg(reinterpret_cast<const uint32_t*>(cvec + t * 64) + lane);
          const uint32_t sp = pack_bf16(silu_f(bf_lo(cw)), silu_f(bf_hi(cw)));
          sts64u(stab + lane * 8, sp << 16, sp & 0xFFFF0000u);
        }
        float acc[8];
#pragma unroll
        for (int i = 0; i < 8; i++) acc[i] = 0.f;
#pragma unroll 1
        for (int n = -3; n < 24; n++) {
          if (n < 21 && elect_one()) {
            mbar_expect_tx(mf + (n & 3) * 8, 4096);
            tma_2d(ring + (n & 3) * 4096, &prm.wm, ((n + 3) >> 3) * 2048 + cgrp * 256, t * 64 + ((n + 3) & 7) * 8, mf + (n & 3) * 8, pol<1>());
          }
          if (n < 0) continue;
          const uint32_t sl = ring + ((n + 1) & 3) * 4096 + lane * 16;
          const float4 sv0 = lds128(stab + (n & 7) * 32), sv1 = lds128(stab + (n & 7) * 32 + 16);
          const float sc[8] = {sv0.x, sv0.y, sv0.z, sv0.w, sv1.x, sv1.y, sv1.z, sv1.w};
          mbar_wait(mf + ((n + 1) & 3) * 8, ((n + 1) >> 2) & 1);
          uint4 v[8];
#pragma unroll
          for (int u = 0; u < 8; u++) v[u] = lds128u(sl + u * 512);
#pragma unroll
          for (int u = 0; u < 8; u++) {
            acc[0] = fmaf(sc[u], bf_lo(v[u].x), acc[0]); acc[1] = fmaf(sc[u], bf_hi(v[u].x), acc[1]);
            acc[2] = fmaf(sc[u], bf_lo(v[u].y), acc[2]); acc[3] = fmaf(sc[u], bf_hi(v[u].y), acc[3]);
            acc[4] = fmaf(sc[u], bf_lo(v[u].z), acc[4]); acc[5] = fmaf(sc[u], bf_hi(v[u].z), acc[5]);
            acc[6] = fmaf(sc[u], bf_lo(v[u].w), acc[6]); acc[7] = fmaf(sc[u], bf_hi(v[u].w), acc[7]);
          }
          asm volatile("" : "+f"(acc[0]) :: "memory");
          if ((n & 7) == 7) {
            sts128(stg + lane * 32, acc[0], acc[1], acc[2], acc[3]); sts128(stg + lane * 32 + 16, acc[4], acc[5], acc[6], acc[7]);
#pragma unroll
            for (int i = 0; i < 8; i++) acc[i] = 0.f;
            fence_async_smem();
            if (elect_one()) {
              asm volatile("cp.reduce.async.bulk.global.shared::cta.bulk_group.add.f32 [%0], [%1], 1024;" ::"l"(mod + (n >> 3) * 2048 + cgrp * 256), "r"(stg) : "memory");
              bulk_commit();
              if (n != 15) { bulk_wait<0>(); rel_fence<2>(); red_add(&S->cntMod[n > 7 ? 32 : 0], 1); } else bulk_wait_read<0>();
              TRACE(n > 7 ? 34 + (n >> 3) : 9);
            }
          }
        }
      } else {
        wait_cnt(S->cntMod, tag * 128u);
        if (lane == 0) TRACE(10);
        float4 sa[8];
        {
          const float4 c0 = ldg_cg(mod + D_ + m4 * 256 + lane * 8), c1 = ldg_cg(mod + D_ + m4 * 256 + lane * 8 + 4);
#pragma unroll
          for (int i = 0; i < 8; i++) {
            const float4 sv = ldg_cg(mod + (i >> 1) * 256 + lane * 8 + (i & 1) * 4);
            const uint32_t s0 = pack_bf16(sv.x, sv.y), s1 = pack_bf16(sv.z, sv.w);
            sa[i] = make_float4(bf_lo(s0), bf_hi(s0), bf_lo(s1), bf_hi(s1));
          }
          const uint32_t cw[4] = {pack_bf16(c0.x, c0.y), pack_bf16(c0.z, c0.w), pack_bf16(c1.x, c1.y), pack_bf16(c1.z, c1.w)};
#pragma unroll
          for (int q = 0; q < 4; q++) sts32v(sb + T1_OFF + (lane >> 2) * 64 + q * 16 + (lane & 3) * 4, add_bf16x2(cw[q], 0x3F803F80u) ^ (j ? 0x80008000u : 0u));
        }
        float ul = 0.f;
#pragma unroll 1
        for (int r = 0; r < 8; r++) {
          if (r < 6 && elect_one()) {
            mbar_expect_tx(mf + ((nc + 2) & 3) * 8, 4096);
            bulk_load(ring + ((nc + 3) & 3) * 4096, src + (r + 2) * 2 * D_, 4096, mf + ((nc + 2) & 3) * 8, pol<2>());
          }
          mbar_wait(mf + (nc & 3) * 8, (nc >> 2) & 1); nc++;
          uint4 v[8];
          float u[4] = {0.f, 0.f, 0.f, 0.f};
#pragma unroll
          for (int i = 0; i < 8; i++) v[i] = lds128u(ring + (nc & 3) * 4096 + lane * 16 + i * 512);
#pragma unroll
          for (int i = 0; i < 8; i++) {
            const float4 s0 = sa[2 * (i & 3)], s1 = sa[2 * (i & 3) + 1];
            float &u0 = u[(i >> 2) * 2], &u1 = u[(i >> 2) * 2 + 1];
            u0 = fmaf(bf_lo(v[i].x), s0.x, u0); u1 = fmaf(bf_hi(v[i].x), s0.y, u1); u0 = fmaf(bf_lo(v[i].y), s0.z, u0); u1 = fmaf(bf_hi(v[i].y), s0.w, u1);
            u0 = fmaf(bf_lo(v[i].z), s1.x, u0); u1 = fmaf(bf_hi(v[i].z), s1.y, u1); u0 = fmaf(bf_lo(v[i].w), s1.z, u0); u1 = fmaf(bf_hi(v[i].w), s1.w, u1);
          }
          const float ua = u[0] + u[1], ub = u[2] + u[3];
          float us = ((lane & 1) ? ub : ua) + __shfl_xor_sync(~0u, (lane & 1) ? ua : ub, 1);
#pragma unroll
          for (int o = 16; o > 1; o >>= 1) us += __shfl_xor_sync(~0u, us, o);
          if ((lane >> 1) == r) ul = jw ? -us : us;
        }
        if (lane < 16) st_msg8(&S->u[jw * D_ + e0 + lane], __float_as_uint(ul), tag);
        if (lane == 0) TRACE(11);
#pragma unroll
        for (int i = 0; i < 4; i++) sts128u(ring + lane * 16 + i * 512, SENT, SENT, SENT, SENT);
        fence_async_smem();
        if (elect_one()) {
#pragma unroll 1
          for (int i = 0; i < 9; i++)
            bulk_store(i < 4 ? &S->part[b * 512 + i * 128] : i == 4 ? &S->stats[b * 128] : &S->rowsH[((i - 5) >> 1) * 4096 + (t * 2 + (i & 1)) * 128 + cgrp * 16], ring, i < 5 ? 2048 : 256);
          bulk_store(&S->flagP[b * 32], ring, 128);
          bulk_commit(); bulk_wait<0>(); rel_fence<4>();
          mbar_arrive(BAR(B_RSDONE)); TRACE(30);
        }
        if (lane == 12) S->claim[cl * 8] = 0;
        if (lane < 12) reinterpret_cast<float4*>(S->mod[~tag & 1] + b * 48)[lane] = make_float4(0.f, 0.f, 0.f, 0.f);
      }
      named_bar<1, 64>();
    }
    asm volatile("setmaxnreg.dec.sync.aligned.u32 40;" ::: "memory");
    if (warp == 2) {
      const int scl = blk_src(lane, cgrp);
      const unsigned* flagAddr = &S->flagP[(t * 8 + (scl >> 2)) * 32 + (scl & 3)];
      const unsigned* cellAddr = &S->flagP[(t * 8 + (lane & 7)) * 32];
      sts32v(sb + PFLAG_OFF + lane * 4, tag - 1);
      if (lane < 4) mbar_arrive(BAR(B_FULL2 + lane));
      mbar_wait(BAR(B_PREADY), 0);
      unsigned ready = 15;
      int u = 4, i7 = 0, kk = 0; uint32_t ph = 1;
#pragma unroll 1
      for (int q = 4; q < 32; q++) {
        const int src = FK_SKIP ? i7 + (i7 >= cgrp) : i7 == cgrp ? 7 : i7;
        if (!((ready >> q) & 1)) {
          unsigned v;
          asm volatile("ld.volatile.shared.u32 %0, [%1];" : "=r"(v) : "r"(sb + PFLAG_OFF + scl * 4) : "memory");
          ready |= __ballot_sync(~0u, v == tag);
          int it = 0;
          while (!((ready >> q) & 1)) {
            ready |= __ballot_sync(~0u, (unsigned)(lane - q) < 7u && ld_rlx(flagAddr) == tag);
            SPIN_CHECK(it);
          }
          fence_async_global();
        }
        if ((q & ~4) == 8) mbar_wait(BAR(B_PS - 2 + (q >> 2)), 0);
        mbar_wait(BAR(q >= 8 ? B_EMPTY2 + u : q == 4 ? B_EMPTY + 2 : B_FULL2 + u), ph);
        if (q >= 8) grid_wait();
        if (elect_one()) {
          TRACE3(128 + q);
          mbar_expect_tx(BAR(B_FULL2 + u), SLOT);
          tma_2d(sb + buf_off(u), &prm.p, (src >> 1) * 256 + kk * 64, (src & 1) * S_ + t * 128, BAR(B_FULL2 + u), pol<5>());
        }
        if (((~ready >> q) & 15) && lane < 8)
          asm volatile("cp.async.cg.shared.global [%0], [%1], 16;" ::"r"(sb + PFLAG_OFF + lane * 16), "l"(cellAddr) : "memory");
        if (++u == 5) { u = 0; ph ^= 1; }
        if (++i7 == 7) { i7 = 0; kk++; }
      }
      asm volatile("cp.async.wait_all;" ::: "memory");
    }
    asm volatile("" ::: "memory");
    if (warp == 0) {
      int u = 0; uint32_t ph = 1;
#pragma unroll 1
      for (int q = 0; q < 32; q++) {
        const int sc = blk_src(q, cgrp);
        mbar_wait(BAR(q >= 5 ? B_EMPTY2 + u : q < 2 ? B_ADONE : q == 4 ? B_EMPTY + 3 : B_EMPTY + 1), q >= 2 ? ph : 0);
        if (elect_one()) {
          TRACE3(160 + q);
          mbar_expect_tx(BAR(B_FULL2 + u), SLOT);
          tma_2d_mc(sb + buf_off(u) + SLOT + rank * 8192, &prm.wd[(sc >> 2) & 1], (sc >> 3) * 256 + (sc & 3) * 64, cgrp * 128 + rank * 64, BAR(B_FULL2 + u), pol<6>());
          if (q & 1) { const int p = 4 + FK_NA + ((q - FK_QP) >> 1); if (q >= FK_QP && p < (FK_TD ? 16 : 24)) prefetch_piece(p); }
          else if (q >= 10 && q < 2 * FK_NL + 2) weight_box((q >> 1) - 1, BAR(B_FULL2 + (u == 4 ? 0 : u + 1)));
        }
        if (++u == 5) { u = 0; ph ^= 1; }
      }
      if (elect_one()) {
#pragma unroll 1
        for (int n = FK_NL; n < 15; n++) weight_box(n, BAR(B_WF));
        mbar_expect_tx(BAR(B_DN), moe ? 65536 : 0);
#pragma unroll 1
        for (int i = 0; i < 9; i++) {
          if ((i & 3) == 0) mbar_wait(BAR(B_EMPTY2 + 2 + (i >> 2)), 1);
          if (i == 0) { mbar_arrive(BAR(B_B27)); weight_box(15, BAR(B_WF)); mbar_arrive(BAR(B_WF)); }
          else if (moe)
            asm volatile("cp.async.bulk.tensor.5d.shared::cluster.global.mbarrier::complete_tx::bytes.L2::cache_hint [%0], [%1, {0, 0, 0, %3, %4}], [%2], %5;"
                         ::"r"(sb + RKA_OFF + (i + (i >> 3) * 4) * 8192), "l"(&prm.wdn), "r"(BAR(B_DN)), "r"(eb * 2), "r"(i * 2 - 2), "l"(pol<3>()) : "memory");
        }
      }
    }
    asm volatile("" ::: "memory");
    if (warp == 1) {
      if (elect_one()) {
#pragma unroll 1
        for (int kk = 0; kk < 4; kk++) {
          mbar_wait(BAR(B_PREADY + kk), 0);
#pragma unroll 1
          for (int i = 0; i < 4; i++) {
            tma_store_2d(&prm.ps, sb + pstage(kk) + i * 4096, m4 * 256 + kk * 64, j * S_ + t * 128 + i * 32);
            if (kk >= FK_PS0 && i < 3) { const unsigned next = clk32() + FK_PSPACE; while ((int)(clk32() - next) < 0) __nanosleep(20); }
          }
          bulk_commit(); bulk_wait<0>();
          if (kk < 2) mbar_arrive(BAR(B_PS + kk));
          rel_fence<3>();
          st_rlx(&S->flagP[b * 32 + kk], tag);
          TRACE(40 + kk); TRACE3(128 + kk);
        }
        prefetch_tmap(&prm.om);
        if (FK_XD) { const unsigned next = clk32() + FK_XD; while ((int)(clk32() - next) < 0) __nanosleep(20); }
        mbar_expect_tx(BAR(B_EFULL), (FK_X & 4) ? 0 : 32768);
#pragma unroll 1
        for (int i = 0; i < 8; i++) {
          if (!(FK_X & 4)) tma_3d(sb + E_OFF + i * 4096, &prm.xm, t * 128 + i * 16, cgrp * 2, BAR(B_EFULL), pol<8>());
          const unsigned next = clk32() + FK_SPACE;
          while ((int)(clk32() - next) < 0) __nanosleep(20);
        }
      }
      __syncwarp();
      mbar_wait(BAR(B_PREADY), 1);
      if (lane == 0) TRACE(60);
      const int lr = lds32u(sb + BK_OFF + (lane >> 4) * 4);
      {
        const uint4 v = lds128u(sb + E_OFF + (lr >> 4) * 4096 + (lane & 8) * 256 + (lr & 15) * 128 + (((lane ^ lr) & 7) << 4));
        st_msg(&S->rowsB[(t * 2 + (lane >> 4)) * 128 + cgrp * 16 + (lane & 15)], v.x, v.y, v.z, v.w);
      }
      const unsigned cmask = __reduce_or_sync(~0u, 1u << (lr >> 4)) | FK_OMASK;
      unsigned todo = ~cmask & 255, smask = 0;
      int r1 = 0, r2 = 0;
#pragma unroll 1
      for (int h = 0; h < 2; h++) {
        if (elect_one()) {
#pragma unroll 1
          for (; todo; todo &= todo - 1) {
            const int i = __ffs(todo) - 1;
            asm volatile("cp.async.bulk.tensor.3d.global.shared::cta.bulk_group.L2::cache_hint [%0, {0, %2, %3}], [%1], %4;"
                         ::"l"(&prm.om), "r"(sb + E_OFF + i * 4096), "r"(t * 128 + i * 16), "r"(cgrp * 2), "l"(pol<9>()) : "memory");
            if (FK_OSPACE && (h == 0 || FK_OSPACE2)) spin(h ? FK_OSPACE2 : FK_OSPACE);
          }
          TRACE(61 + h);
        }
        if (h) break;
        mbar_wait(BAR(B_SEL), 0);
        r1 = lds32u(sb + SEL_OFF) - t * 128; r2 = lds32u(sb + SEL_OFF + 4) - t * 128;
        smask = ((unsigned)r1 < 128u ? 1u << (r1 >> 4) : 0) | ((unsigned)r2 < 128u ? 1u << (r2 >> 4) : 0);
        todo = cmask & ~smask;
        if (FK_ODELAY) spin(FK_ODELAY);
      }
#pragma unroll 1
      for (; smask; smask &= smask - 1) {
        const int i = __ffs(smask) - 1;
#pragma unroll 2
        for (int r = lane >> 4; r < 16; r += 2) {
          const uint4 v = lds128u(sb + E_OFF + i * 4096 + (lane & 8) * 256 + r * 128 + (((lane ^ r) & 7) << 4));
          if (i * 16 + r != r1 && i * 16 + r != r2) reinterpret_cast<uint4*>(out + (size_t)(t * 128 + i * 16 + r) * D_)[cgrp * 16 + (lane & 15)] = v;
        }
      }
      if (elect_one()) { bulk_commit(); bulk_wait_read<0>(); TRACE(29); }
    }
    asm volatile("" ::: "memory");
    if (warp == 3) {
      if (elect_one()) {
        fence_async_smem();
        unsigned next = clk32();
#pragma unroll 1
        for (int n = 0; n < 4 + FK_NA; n++) {
          if (n < 4) weight_box(n, BAR(B_WF)); else prefetch_piece(n);
          if (n == 3) mbar_arrive(BAR(B_WF));
          if (!FK_TX && (unsigned)(n - FK_XN) < 4u) pf_bulk(x + (size_t)(b * 16 + (n - FK_XN) * 4) * D_, 8192);
          next += FK_PACE;
          while ((int)(clk32() - next) < 0) __nanosleep(20);
        }
        TRACE(37);
      }
      __syncwarp();
      int it = 0;
      wait_cnt(&S->cntMod[32], tag * 128u);
      mbar_wait(BAR(B_PREADY + 2), 0);
      {
        const float* mp = S->mod[tag & 1] + cgrp * 128 + lane * 4;
        const float4 ga = ldg_cg(mp + 2 * D_), sv = ldg_cg(mp + 3 * D_), cb = ldg_cg(mp + 4 * D_), gb = ldg_cg(mp + 5 * D_);
        const uint2 wr = __ldg(reinterpret_cast<const uint2*>(prm.w_r + cgrp * 128 + lane * 4));
        const uint32_t Aa = add_bf16x2(pack_bf16(cb.x, cb.y), 0x3F803F80u), Ab = add_bf16x2(pack_bf16(cb.z, cb.w), 0x3F803F80u);
        const uint32_t Sa = pack_bf16(sv.x, sv.y), Sb = pack_bf16(sv.z, sv.w), Ga = pack_bf16(gb.x, gb.y), Gb = pack_bf16(gb.z, gb.w);
        const float w0 = bf_lo(Aa) * bf_lo(wr.x), w1 = bf_hi(Aa) * bf_hi(wr.x), w2 = bf_lo(Ab) * bf_lo(wr.y), w3 = bf_hi(Ab) * bf_hi(wr.y);
        const uint32_t tb = sb + TAB_OFF + (lane >> 3) * 64 + (lane & 1) * 32 + ((lane >> 1) & 3) * 4, Wa = pack_bf16(w0, w1), Wb = pack_bf16(w2, w3);
        auto put = [&](int off, uint32_t a, uint32_t c) { sts32v(tb + off, a); sts32v(tb + off + 16, c); };
        put(T_WH, Wa, Wb); put(T_ONE, 0x3F803F80u, 0x3F803F80u);
        put(T_WL, pack_bf16(w0 - bf_lo(Wa), w1 - bf_hi(Wa)), pack_bf16(w2 - bf_lo(Wb), w3 - bf_hi(Wb)));
        put(T_GA, pack_bf16(ga.x, ga.y), pack_bf16(ga.z, ga.w)); put(T_A, Aa, Ab); put(T_S, Sa, Sb); put(T_G, Ga, Gb);
        float c1 = (w0 + w1) + (w2 + w3), c2 = (bf_lo(Sa) * bf_lo(wr.x) + bf_hi(Sa) * bf_hi(wr.x)) + (bf_lo(Sb) * bf_lo(wr.y) + bf_hi(Sb) * bf_hi(wr.y));
#pragma unroll 1
        for (int h = 0; h < 2; h++) {
#pragma unroll
          for (int o = 16; o; o >>= 1) { c1 += __shfl_xor_sync(~0u, c1, o); c2 += __shfl_xor_sync(~0u, c2, o); }
          if (h) break;
          if (t == 0 && lane == 0) st_msg(&S->cst[cgrp], __float_as_uint(c1), __float_as_uint(c2), tag, 0);
          uint4 cm; it = 0;
          while (true) {
            cm = ld_msg(&S->cst[lane & 7]);
            if (__all_sync(~0u, cm.z == tag)) break;
            SPIN_CHECK(it); __nanosleep(200);
          }
          c1 = 0.25f * __uint_as_float(cm.x); c2 = 0.25f * __uint_as_float(cm.y);
        }
        if (lane == 0) { sts128u(sb + CST_OFF, __float_as_uint(c1), __float_as_uint(c2), tag, b | eb << 8 | (int)moe << 16); TRACE(27); }
      }
      uint32_t rk[16];
#pragma unroll
      for (int h = 0; h < 2; h++) {
        const uint2* src = (h ? &S->u[cgrp * 128] : &S->rs[t * 128]) + lane;
        uint2 m[8]; it = 0;
        while (true) {
          bool ok = true;
#pragma unroll
          for (int i = 0; i < 8; i++) { m[i] = ld_msg8(src + (i >> 1) * 32 + (i & 1) * (h ? D_ : S_)); ok &= m[i].y == tag; }
          if (ok) break;
          SPIN_CHECK(it);
        }
#pragma unroll
        for (int i = 0; i < 4; i++) {
          const float r0 = __uint_as_float(m[2 * i].x) * (h ? 0.5f : 1.f), r1 = __uint_as_float(m[2 * i + 1].x) * (h ? 0.5f : 1.f);
          const uint32_t hi = pack_bf16(r0, r1);
          rk[h * 8 + 2 * i] = hi; rk[h * 8 + 2 * i + 1] = pack_bf16(r0 - bf_lo(hi), r1 - bf_hi(hi));
        }
      }
      mbar_wait(BAR(B_B27), 0);
#pragma unroll
      for (int i = 0; i < 4; i++) {
        sts128u(sb + RKA_OFF + (i * 32 + lane) * 16, rk[2 * i], rk[2 * i], rk[2 * i + 1], 0);
        sts128u(sb + RKB_OFF + (i * 32 + lane) * 16, rk[8 + 2 * i], rk[9 + 2 * i], rk[8 + 2 * i], 0);
      }
      fence_async_smem();
      __syncwarp();
      if (lane == 0) { mbar_arrive(BAR(B_TAB)); TRACE(26); }
    }
    asm volatile("" ::: "memory");
    if (warp == 2) {
      const uint4* cp = &S->cand[(lane >> 1) * 8];
      mbar_wait(BAR(B_B27), 0);
      uint4 m = ld_msg(cp);
      bool ok = __all_sync(~0u, m.z == tag);
      named_bar<5, 288>();
      uint32_t k1, k2;
      {
        const uint4 k4 = lds128u(sb + KEY_OFF + lane * 16);
        const uint32_t ka = max(k4.x, k4.y), kb = max(k4.z, k4.w), m1 = max(ka, kb), m2 = max(min(ka, kb), ka > kb ? min(k4.x, k4.y) : min(k4.z, k4.w));
        k1 = redux_max(m1); k2 = redux_max(m1 == k1 ? m2 : m1);
        if (lane == 0) { st_msg(&S->cand[t * 8], k1, k2, tag, 0); sts64u(sb + BK_OFF, key_row(k1) & 127, key_row(k2) & 127); mbar_arrive(BAR(B_BK)); TRACE(13); }
      }
      int it = 0;
      while (!ok) {
        m = ld_msg(cp);
        ok = __all_sync(~0u, m.z == tag);
        SPIN_CHECK(it);
      }
      warp_top2((lane & 1) ? m.y : m.x, k1, k2);
      const int r1 = key_row(k1), r2 = key_row(k2), slot1 = (r1 >> 7) * 2, slot2 = (r2 >> 7) * 2 + ((r1 >> 7) == (r2 >> 7));
      if (lane == 0) { sts64u(sb + SEL_OFF, r1, r2); sts64u(sb + SEL_OFF + 8, slot1 * 2048, slot2 * 2048); mbar_arrive(BAR(B_SEL)); TRACE(14); }
      const int fcol = (b >> 1) * 16 + (lane & 15);
      const float gb = round_bf16(__uint_as_float(ld_rlx(S->mod[tag & 1] + 5 * D_ + fcol)));
      const uint32_t* fbp = reinterpret_cast<const uint32_t*>(&S->rowsB[((b & 1) ? slot2 : slot1) * 128]) + (fcol >> 1);
      uint32_t fb;
      do { fb = ld_rlx(fbp); SPIN_CHECK(it); } while (fb == SENT);
      sts64u(sb + PFLAG_OFF + (lane & 15) * 8, (lane & 1) ? fb & 0xFFFF0000u : fb << 16, __float_as_uint(gb));
      __syncwarp();
      if (lane == 0) {
        sts32(sb + CST_OFF, round_bf16(sigmoid_f(round_bf16(fkey_inv((((b & 1) ? k2 : k1) & ~2047u) | 1024u)))));
        mbar_arrive(BAR(B_FIN));
        if (b == 0) S->epoch[0] = tag;
      }
    }
  } else {
    const int cw = (warp - 4) >> 2;
    const int cwarp = warp - 4;
    const bool elect = (tid & 127) == 0;
    uint32_t rel;
    asm volatile("mapa.shared::cluster.u32 %0, %1, %2;" : "=r"(rel) : "r"(BAR(0)), "r"(tid & 1));
    if (tid & 126) rel = 0;
    asm volatile("" : "+r"(rel));
    auto release = [&](int bar) {
      asm volatile("{\n.reg .pred p;\nsetp.ne.u32 p, %1, 0;\n@p mbarrier.arrive.shared::cluster.b64 _, [%0];\n}" ::"r"(rel + bar * 8), "r"(rel) : "memory");
    };
    const uint32_t da0 = desc_lo(sb + cw * 8192, 16), db0 = desc_lo(sb + SLOT, 8192), db2 = desc_lo(sb + SLOT, 16);

    uint32_t wf[64], uf[64], df[64];
    uint32_t pk[64];
    uint32_t xw[32];
    float lo[64];
    int ln;
    uint32_t so, wo;
    auto p_ready = [&](int kk) { fence_async_smem(); if (elect_one()) mbar_arrive(BAR(B_PREADY + kk)); };
    {
      float pa[64], pb[64];
      {
        float acc[128];
#pragma unroll 1
        for (int g = 0; g < 28; g++) {
          const int s = g & 3;
          mbar_wait(BAR(B_FULL + s), (g >> 2) & 1);
          const uint32_t da = da0 + s * (STAGE >> 4), db = db0 + s * (STAGE >> 4);
          wg_fence();
          wgmma_n256<1>(acc, da, db, g > 0);
#pragma unroll
          for (int k = 1; k < 4; k++) wgmma_n256<1>(acc, da + k * 2, db + k * 128, 1);
          wg_commit();
          wg_wait<1>();
          if (g > 0) { release(B_EMPTY + ((g - 1) & 3)); if (elect) TRACE2(191 + g + cw * 32); }
          STAMP2(g);
        }
        wg_wait<0>();
        release(B_EMPTY + 3);
#pragma unroll
        for (int i = 0; i < 64; i++) {
          asm volatile("mov.b32 %0, %1;" : "=f"(pa[i]) : "f"(acc[i]));
          asm volatile("mov.b32 %0, %1;" : "=f"(pb[i]) : "f"(acc[64 + i]));
        }
      }
      if (elect) TRACE(3 + tr);
      STAMP2(28);
#pragma unroll 1
      for (int s = 0; s < 4; s++) {
        mbar_wait(BAR(B_FULL + s), 1);
        wg_fence();
#pragma unroll
        for (int k = 0; k < 4; k++) wgmma_n128<1>(pa, da0 + s * (STAGE >> 4) + k * 2, db0 + s * (STAGE >> 4) + k * 128);
        wg_commit();
        if (s == 2) { wg_wait<1>(); if (elect) mbar_arrive(BAR(B_A29)); }
      }
      auto b_block = [&](int s) {
        wg_fence();
#pragma unroll
        for (int k = 0; k < 4; k++) wgmma_n128<1>(pb, da0 + s * (STAGE >> 4) + k * 2, db0 + s * (STAGE >> 4) + 1024 + k * 128);
        wg_commit();
      };
      uint4 t0, t1;
      auto load_t = [&](int kk) { t0 = lds128u(sb + T1_OFF + kk * 128 + (ln & 3) * 16); t1 = lds128u(sb + T1_OFF + kk * 128 + 64 + (ln & 3) * 16); };
      auto pack_p = [&](int kk, const float* a) {
        const uint32_t A[8] = {t0.x, t0.y, t0.z, t0.w, t1.x, t1.y, t1.z, t1.w};
#pragma unroll
        for (int i = 0; i < 16; i++) pk[kk * 16 + i] = mul_bf16x2(pack_bf16(a[2 * i], a[2 * i + 1]), A[i >> 1]);
      };
      auto stage_p = [&](int kk) {
#pragma unroll
        for (int k = 0; k < 4; k++) stsm_x4((so ^ (k << 5)) + pstage(kk), pk + kk * 16 + k * 4);
      };
      auto own_block = [&](int q) {
        const uint32_t db = db2 + (buf_off(q) >> 4);
        wg_fence();
        if (q == 0) wgmma_n128_rs<0>(lo, pk, db); else wgmma_n128_rs<1>(lo, pk + q * 16, db);
#pragma unroll
        for (int k = 1; k < 4; k++) wgmma_n128_rs<1>(lo, pk + q * 16 + k * 4, db + k * 2);
        wg_commit();
      };
      b_block(0);
      mbar_wait(BAR(B_RSDONE), 0);
      asm volatile("setmaxnreg.inc.sync.aligned.u32 232;" ::: "memory");
      asm volatile("mov.u32 %0, %%laneid;" : "=r"(ln));
      so = sb + (uint32_t)(cwarp * 16 + (ln & 15)) * 128 + (((ln >> 4) ^ (ln & 7)) << 4);
      wo = sb + SP_OFF + cwarp * 1024 + ((ln & 7) + (ln >> 4) * 8) * 64 + ((((ln >> 3) & 1) ^ ((ln >> 1) & 3)) << 4);
      mbar_wait(BAR(B_A29), 0);
      load_t(0);
      wg_wait<1>();
      reg_fence(pa);
      release(B_ADONE);
      if (elect) TRACE(4 + tr);
      STAMP2(29);
      pack_p(0, pa); stage_p(0);
      if (FK_TR0) { p_ready(0); b_block(1); } else { b_block(1); p_ready(0); }
      if (elect) TRACE(2 + tr);
      wg_wait<1>(); release(B_EMPTY);
      load_t(1);
      b_block(2);
      pack_p(1, pa + 32);
      wg_wait<1>(); release(B_EMPTY + 1);
      STAMP2(30);
      load_t(2);
      b_block(3);
      mbar_wait(BAR(B_FULL2), 0);
      wg_wait<1>(); release(B_EMPTY + 2);
      if (FK_S1 == 0) { mbar_wait(BAR(B_ADONE), 0); stage_p(1); }
      own_block(0);
      if (FK_S1 == 0) p_ready(1);
      mbar_wait(BAR(B_FULL2 + 1), 0);
      if (FK_S1 == 1) mbar_wait(BAR(B_ADONE), 0);
      wg_wait<1>(); release(B_EMPTY + 3);
      reg_fence(pb);
      if (elect) TRACE(1 + tr);
      STAMP2(31);
      if (FK_S1 == 1) stage_p(1);
      own_block(1);
      if (FK_S1 == 1) p_ready(1);
      pack_p(2, pb);
      mbar_wait(BAR(B_FULL2 + 2), 0);
      wg_wait<1>(); release(B_EMPTY2);
      STAMP2(32);
      load_t(3);
      own_block(2);
      pack_p(3, pb + 32);
      mbar_wait(BAR(B_EMPTY + 3), 1);
      mbar_wait(BAR(B_FULL2 + 3), 0);
      wg_wait<1>(); release(B_EMPTY2 + 1);
      STAMP2(33);
      if (FK_S1 == 3) stage_p(1);
      own_block(3);
      if (FK_S1 == 3) p_ready(1);
      mbar_wait(BAR(B_WF), 0);
      wg_wait<1>(); release(B_EMPTY2 + 2);
      STAMP2(34);
    }
    {
      mbar_wait(BAR(B_FULL2 + 4), 0);
#pragma unroll
      for (int q = 4; q < 32; q++) {
        const uint32_t da = da0 + (buf_off(q % 5) >> 4) + (q << 16), db = db2 + (buf_off(q % 5) >> 4) + (q << 16);
        wg_fence();
#pragma unroll
        for (int k = 0; k < 4; k++) wgmma_n128<0>(lo, da + k * 2, db + k * 2);
        wg_commit();
        if (q == 31) break;
        if (FK_ORD == 1) { wg_wait<1>(); if (q == 28 && rel) rel = BAR(0); release(B_EMPTY2 + (q - 1) % 5); STAMP2(31 + q); }
        if (q == 8 || q == 14) p_ready(q >> 2);
        if (q == 27) mbar_wait(BAR(B_EFULL), 0);
        mbar_wait(BAR(B_FULL2 + (q + 1) % 5), ((q + 1) / 5) & 1);
        if (q >= 27) {
#pragma unroll
          for (int h = 0; h < 2; h++) ldsm_x4((so ^ ((q - 27) << 5)) + E_OFF + cwarp * 2048 + h * 2048, xw + (q - 27) * 4 + h * 16);
        } else if (!(q & 1)) {
          const int n = (q - 4) >> 1;
#pragma unroll
          for (int h = 0; h < 2; h++) ldsm_x4_t((wo ^ (h << 5)) + (n & 3) * 8192, (n < 8 ? wf + n * 8 : uf + (n - 8) * 8) + h * 4);
        } else if (q < 15 && q != 9) {
          const int i = (q - 5 - (q > 9) * 2) >> 1;
#pragma unroll
          for (int h = 0; h < 2; h++) stsm_x4((so ^ (((i & 1) * 2 + h) << 5)) + pstage(2 + (i >> 1)), pk + 32 + i * 8 + h * 4);
        }
        if (FK_ORD == 0) { wg_wait<1>(); if (q == 28 && rel) rel = BAR(0); release(B_EMPTY2 + (q - 1) % 5); STAMP2(31 + q); }
      }
    }
    mbar_wait(BAR(B_TAB), 0);
    wg_fence();
    wgmma_n128<0, 8>(lo, desc_lo(sb + RKA_OFF, 0) + (cwarp & 4) * 16, desc_lo(sb + RKB_OFF, 0));
    wg_commit();
    const int gq = ln >> 2, q4 = ln & 3, row0 = cwarp * 16 + gq;
    const bool odd = ln & 1;
    const uint32_t role = lds32u(sb + CST_OFF + 12), bq = role & 255;
    uint32_t tq = sb + TAB_OFF + q4 * 16, tb = tq + (gq & 1) * T_ONE + (gq & 2) * (T_WL / 2);
    const uint4* src = &S->stats[((bq & ~7) + (q4 >> 1) * 4) * 128 + row0 + 8 * (q4 & 1)];
    uint4* sdst = &S->stats[bq * 128 + row0 + 8 * q4];
    asm volatile("" : "+r"(tq), "+r"(tb), "+l"(src), "+l"(sdst));
    {
      uint4 gw[4];
#pragma unroll
      for (int a = 0; a < 4; a++) gw[a] = lds128u(tq + T_GA + a * 64);
      wg_wait<0>();
      reg_fence(lo);
      STAMP(0);
      if (elect) { TRACE(7 + tr); if (cw == 0) TRACE_CLK(121); }
      float c[2][4], e0[2][4], e1[2][4];
#pragma unroll
      for (int i = 0; i < 4; i++) c[0][i] = c[1][i] = e0[0][i] = e0[1][i] = e1[0][i] = e1[1][i] = 0.f;
#pragma unroll
      for (int a = 0; a < 4; a++) {
        const uint4 bw = lds128u(tb + a * 64);
        const uint32_t g[4] = {gw[a].x, gw[a].y, gw[a].z, gw[a].w};
#pragma unroll
        for (int i = 0; i < 8; i++) xw[a * 8 + i] = fma_bf16x2(g[i >> 1], pack_bf16(lo[a * 16 + 2 * i], lo[a * 16 + 2 * i + 1]), xw[a * 8 + i]);
#pragma unroll
        for (int h = 0; h < 2; h++) {
          const uint32_t* w = xw + a * 8 + h * 4;
          mma_1688(e0[0], w[0], w[1], w[0]); mma_1688(e1[0], w[0], w[1], w[1]); mma_1688(e0[1], w[2], w[3], w[2]); mma_1688(e1[1], w[2], w[3], w[3]);
          mma_16816(c[h], w, h ? bw.z : bw.x, h ? bw.w : bw.y);
        }
      }
      const float c0 = c[0][0] + c[1][0], c2 = c[0][2] + c[1][2];
      const float q0 = (gq & 1) ? e0[0][1] + e0[1][1] : e0[0][0] + e0[1][0], q1 = (gq & 1) ? e1[0][3] + e1[1][3] : e1[0][2] + e1[1][2];
      const int dl = (ln & ~3) | (gq >> 1);
      const float da = (odd ? c2 : c0) + __shfl_xor_sync(~0u, odd ? c0 : c2, 1), s1 = __shfl_xor_sync(~0u, c[0][3] + c[1][3], 1);
      const float qa = __shfl_sync(~0u, q0, dl), qb = __shfl_sync(~0u, q1, dl);
      if (q4 < 2) st_msg(sdst, __float_as_uint(odd ? s1 : c[0][1] + c[1][1]), __float_as_uint(odd ? qb : qa), __float_as_uint(da), 0);
    }
    if (elect) TRACE(8 + tr);
    STAMP(1);
    {
      uint4 m[4], tA[4], tS[4];
      mbar_wait(BAR(B_WF), 1);
#pragma unroll
      for (int i = 0; i < 4; i++) m[i] = ld_msg(src + 128 * i);
      const float2 cst = lds64(sb + CST_OFF);
#pragma unroll
      for (int i = 0; i < 8; i++) ldsm_x4_t((wo ^ ((i & 1) << 5)) + (i >> 1) * 8192, uf + 32 + i * 4);
#pragma unroll
      for (int a = 0; a < 4; a++) { tA[a] = lds128u(tq + T_A + a * 64); tS[a] = lds128u(tq + T_S + a * 64); }
      uint32_t kaddr = sb + KEY_OFF + (row0 + 8 * (q4 & 1)) * 4, kidx = 2047 - ((bq >> 3) * 128 + row0 + 8 * (q4 & 1));
      asm volatile("" : "+r"(kaddr), "+r"(kidx));
      STAMP(2);
      int it = 0;
      while (!__all_sync(~0u, (m[0].w | m[1].w | m[2].w | m[3].w) == 0)) {
#pragma unroll
        for (int i = 0; i < 4; i++) m[i] = ld_msg(src + 128 * i);
        SPIN_CHECK(it);
      }
      STAMP(3);
      float sa = (__uint_as_float(m[0].x) + __uint_as_float(m[1].x)) + (__uint_as_float(m[2].x) + __uint_as_float(m[3].x));
      float qa = (__uint_as_float(m[0].y) + __uint_as_float(m[1].y)) + (__uint_as_float(m[2].y) + __uint_as_float(m[3].y));
      float da = (__uint_as_float(m[0].z) + __uint_as_float(m[1].z)) + (__uint_as_float(m[2].z) + __uint_as_float(m[3].z));
      sa += __shfl_xor_sync(~0u, sa, 2); qa += __shfl_xor_sync(~0u, qa, 2); da += __shfl_xor_sync(~0u, da, 2);
      const float mean = sa * (1.f / D_);
      const float rs = rsqrt_f(fmaxf(fmaf(-mean, mean, qa * (1.f / D_)), 0.f) + 1e-5f);
      sts32v(kaddr, (fkey(fmaf(rs, fmaf(-mean, cst.x, da), cst.y)) & ~2047u) | kidx);
      uint32_t one;
      asm volatile("bar.arrive 5, 288;\nld.volatile.shared.u32 %0, [%1];" : "=r"(one) : "r"(sb + TAB_OFF + T_ONE) : "memory");
      if (tid == 128) TRACE(12 + 16);
      STAMP(4);
      const uint32_t h0 = pack_bf16(rs, rs), l0 = mul_bf16x2(pack_bf16(rs - bf_lo(h0), -mean * rs), one), hx = __shfl_xor_sync(~0u, h0, 1), lx = __shfl_xor_sync(~0u, l0, 1);
      const uint32_t rh[2] = {odd ? hx : h0, odd ? h0 : hx};
      const uint32_t rl[2] = {__byte_perm(odd ? lx : l0, 0, 0x1010), __byte_perm(odd ? l0 : lx, 0, 0x1010)};
      const uint32_t nm[2] = {__byte_perm(odd ? lx : l0, 0, 0x3232), __byte_perm(odd ? l0 : lx, 0, 0x3232)};
      uint32_t h[32];
#pragma unroll
      for (int a = 0; a < 4; a++) {
        const uint32_t A[4] = {tA[a].x, tA[a].y, tA[a].z, tA[a].w}, B[4] = {tS[a].x, tS[a].y, tS[a].z, tS[a].w};
#pragma unroll
        for (int i = 0; i < 8; i++) {
          const uint32_t w = xw[a * 8 + (i & 3) * 2 + (i >> 2)];
          h[a * 8 + i] = fma_bf16x2(fma_bf16x2(w, rh[i >> 2], fma_bf16x2(w, rl[i >> 2], nm[i >> 2])), A[i & 3], B[i & 3]);
        }
      }
      uint4* cp = &S->rowsH[(bq >> 3) * 256 + (bq & 7) * 16 + q4];
#pragma unroll
      for (int i = 0; i < 32; i++) asm volatile("" : "+r"(h[i]));
      asm volatile("" : "+l"(cp));
      mbar_wait(BAR(B_BK), 0);
      STAMP(5);
      const float2 bk = lds64(sb + BK_OFF);
#pragma unroll
      for (int r = 0; r < 2; r++) {
        const bool second = row0 + 8 * r == __float_as_int(bk.y);
        if (second || row0 + 8 * r == __float_as_int(bk.x)) {
#pragma unroll
          for (int a = 0; a < 4; a++) st_msg(cp + (second ? 128 : 0) + a * 4, h[a * 8 + r * 4], h[a * 8 + r * 4 + 1], h[a * 8 + r * 4 + 2], h[a * 8 + r * 4 + 3]);
        }
      }
      mbar_wait(BAR(B_DN), 0);
#pragma unroll
      for (int a = 0; a < 4; a++) {
        const uint4 tG = lds128u(tq + T_G + a * 64);
        const uint32_t G[4] = {tG.x, tG.y, tG.z, tG.w};
#pragma unroll
        for (int i = 0; i < 8; i++) xw[a * 8 + i] = fma_bf16x2(G[i >> 1], h[a * 8 + (i & 1) * 4 + (i >> 1)], xw[a * 8 + i]);
#pragma unroll
        for (int k = 0; k < 2; k++) stsm_x4((so ^ ((((a & 1) * 2) + k) << 5)) + E_OFF + cwarp * 2048 + (a >> 1) * 2048, xw + a * 8 + k * 4);
      }
    }
    fence_async_smem();
    if (elect_one()) mbar_arrive(BAR(B_PREADY));
    STAMP(6);
    if (tid == 128) TRACE(15);
    if (role >> 16) {
      const char* hp = reinterpret_cast<const char*>(&S->rowsH[(cwarp >> 1) * 4 + q4]) + (cwarp & 1) * 8;
      uint32_t db = sb + DN_OFF + (cwarp + (cwarp == 7) * 4) * 8192 + ((ln & 7) + (ln >> 4) * 8) * 128 + ((((ln >> 3) & 1) ^ (ln & 7)) << 4), sa = sb + SEL_OFF + 8 + (gq & 1) * 4;
      asm volatile("" : "+l"(hp), "+r"(db), "+r"(sa));
      STAMP(7);
      mbar_wait(BAR(B_SEL), 0);
      STAMP(8);
      { const uint32_t off = lds32u(sa); hp += off; db += off >> 31; }
      uint2 hb[8];
#pragma unroll
      for (int i = 0; i < 8; i++) hb[i] = ld_msg8(hp + i * 256);
      STAMP(9);
#pragma unroll
      for (int i = 0; i < 16; i++) ldsm_x4_t((db ^ (((i >> 1) & 3) << 5)) + (i >> 3) * 4096 + (i & 1) * 2048, df + i * 4);
      int it = 0;
      while (!__all_sync(~0u, max(max(max(hb[0].x, hb[1].x), max(hb[2].x, hb[3].x)), max(max(hb[4].x, hb[5].x), max(hb[6].x, hb[7].x))) != SENT)) {
#pragma unroll
        for (int i = 0; i < 8; i++) hb[i] = ld_msg8(hp + i * 256);
        SPIN_CHECK(it);
      }
      if (tid == 128) TRACE(16);
      STAMP(10);
      float c[4][4];
#pragma unroll
      for (int i = 0; i < 4; i++) c[i][0] = c[i][1] = c[i][2] = c[i][3] = 0.f;
#pragma unroll
      for (int ks = 0; ks < 8; ks++) {
        const uint32_t b0 = hb[ks].x, b1 = hb[ks].y;
        mma_16816(c[0], wf + ks * 8, b0, b1); mma_16816(c[1], wf + ks * 8 + 4, b0, b1);
        mma_16816(c[2], uf + ks * 8, b0, b1); mma_16816(c[3], uf + ks * 8 + 4, b0, b1);
      }
      {
        float v[4];
#pragma unroll
        for (int i = 0; i < 4; i++) v[i] = (q4 & 2) ? (odd ? c[3][i] : c[2][i]) : (odd ? c[1][i] : c[0][i]);
        sts128(sb + RED_OFF + cwarp * 512 + (q4 * 8 + (gq ^ (q4 * 2))) * 16, v[0], v[2], v[1], v[3]);
      }
      uint2* pp = reinterpret_cast<uint2*>(&S->part[((cwarp * 16 + q4 * 2) * 128 + ((role >> 8) & 255)) * 4]) + gq;
      uint32_t ra = sb + RED_OFF + ((ln * 8) ^ ((ln & 16) * 2));
      asm volatile("" : "+l"(pp), "+r"(ra));
      STAMP(11);
      named_bar<2, 256>();
      STAMP(12);
      float g0 = 0.f, g1 = 0.f, u0 = 0.f, u1 = 0.f;
#pragma unroll
      for (int w = 0; w < 8; w++) {
        const float2 gv = lds64(ra + w * 512), uv = lds64((ra ^ 64) + w * 512 + 256);
        g0 += gv.x; g1 += gv.y; u0 += uv.x; u1 += uv.y;
      }
      const uint32_t gp = pack_bf16(g0, g1), up = pack_bf16(u0, u1), sp = pack_bf16(silu_f(bf_lo(gp)), silu_f(bf_hi(gp)));
      const uint32_t act = pack_bf16(bf_lo(sp) * bf_lo(up), bf_hi(sp) * bf_hi(up));
      uint32_t ab[4];
#pragma unroll
      for (int i = 0; i < 4; i++) ab[i] = __shfl_sync(~0u, act, i * 8 + q4 * 2 + (gq & 1));
      if (tid == 128) TRACE(31);
      STAMP(13);
#pragma unroll
      for (int T = 0; T < 2; T++) {
#pragma unroll
        for (int i = 0; i < 4; i++) {
          c[i][0] = c[i][1] = c[i][2] = c[i][3] = 0.f;
          mma_16816(c[i], df + (T * 4 + i) * 8, ab[0], ab[1]); mma_16816(c[i], df + (T * 4 + i) * 8 + 4, ab[2], ab[3]);
        }
        float v[4];
#pragma unroll
        for (int i = 0; i < 4; i++) v[i] = (q4 & 2) ? (odd ? c[3][i] : c[2][i]) : (odd ? c[1][i] : c[0][i]);
        st_msg8(pp + T * 8192, __float_as_uint(v[0]), __float_as_uint(v[2])); st_msg8(pp + T * 8192 + 1024, __float_as_uint(v[1]), __float_as_uint(v[3]));
      }
      if (tid == 128) TRACE(32);
      STAMP(14);
    }
    if (cwarp == 0) {
      const unsigned t0 = clk32();
      mbar_wait(BAR(B_FIN), 0);
      const int fc = q4 * 2 + ((ln >> 2) & 1) + (ln & 8);
      const float2 fo = lds64(sb + PFLAG_OFF + fc * 8);
      const float sg = __uint_as_float(lds32u(sb + CST_OFF));
      __nv_bfloat16* op = out + (size_t)lds32u(sb + SEL_OFF + (bq & 1) * 4) * D_ + (bq >> 1) * 16 + fc;
      const uint4* ip = &S->part[bq * 512 + ln];
      asm volatile("" : "+l"(op), "+l"(ip));
      if (role >> 16) { while (clk32() - t0 < FK_PDELAY) {} } else spin(FK_PDELAY + 600);
      int it = 0;
      uint4 m[14];
      while (true) {
        bool ok = true;
#pragma unroll
        for (int i = 0; i < 14; i++) { m[i] = ld_msg(ip + i * 32); ok &= m[i].x != SENT && m[i].z != SENT; }
        if (__all_sync(~0u, ok)) break;
        SPIN_CHECK(it);
      }
      if (lane == 0) TRACE(33);
      STAMP(15);
      float y[4] = {0.f, 0.f, 0.f, 0.f};
#pragma unroll
      for (int i = 0; i < 14; i++) { y[0] += __uint_as_float(m[i].x); y[1] += __uint_as_float(m[i].y); y[2] += __uint_as_float(m[i].z); y[3] += __uint_as_float(m[i].w); }
      const bool b2 = ln & 4;
      float y0 = (b2 ? y[2] : y[0]) + __shfl_xor_sync(~0u, b2 ? y[0] : y[2], 4), y1 = (b2 ? y[3] : y[1]) + __shfl_xor_sync(~0u, b2 ? y[1] : y[3], 4);
      y0 = ((ln & 8) ? y1 : y0) + __shfl_xor_sync(~0u, (ln & 8) ? y0 : y1, 8);
      y0 += __shfl_xor_sync(~0u, y0, 16);
      const float upd = round_bf16(round_bf16(y0) * sg);
      if (ln < 16) *op = __float2bfloat16_rn(fmaf(fo.y, upd, fo.x));
      if (lane == 0) {
        TRACE(34); TRACE_CLK(122);
      }
    }
  }
}

typedef CUresult (*PFN_encodeTiled)(CUtensorMap*, CUtensorMapDataType, cuuint32_t, void*, const cuuint64_t*, const cuuint64_t*,
                                    const cuuint32_t*, const cuuint32_t*, CUtensorMapInterleave, CUtensorMapSwizzle,
                                    CUtensorMapL2promotion, CUtensorMapFloatOOBfill);

static void mapnd(PFN_encodeTiled enc, CUtensorMap* m, const void* p, int nd, const cuuint64_t* dims, const cuuint64_t* str, const cuuint32_t* box,
                  CUtensorMapSwizzle sw, CUtensorMapL2promotion pr) {
  const cuuint32_t es[5] = {1, 1, 1, 1, 1};
  enc(m, CU_TENSOR_MAP_DATA_TYPE_BFLOAT16, nd, (void*)p, dims, str, box, es, CU_TENSOR_MAP_INTERLEAVE_NONE, sw, pr, CU_TENSOR_MAP_FLOAT_OOB_FILL_NONE);
}
static void map2d(PFN_encodeTiled enc, CUtensorMap* m, const void* p, uint64_t rows, uint64_t cols, uint32_t brows, uint32_t bcols,
                  CUtensorMapSwizzle sw = CU_TENSOR_MAP_SWIZZLE_128B, CUtensorMapL2promotion pr = CU_TENSOR_MAP_L2_PROMOTION_L2_128B) {
  const cuuint64_t dims[2] = {cols, rows}, str[1] = {cols * 2}; const cuuint32_t box[2] = {bcols, brows};
  mapnd(enc, m, p, 2, dims, str, box, sw, pr);
}
static void map3d(PFN_encodeTiled enc, CUtensorMap* m, const void* p, uint64_t rows, uint64_t cols, uint32_t brows, uint32_t bgroups) {
  const cuuint64_t dims[3] = {64, rows, cols / 64}, str[2] = {cols * 2, 128}; const cuuint32_t box[3] = {64, brows, bgroups};
  mapnd(enc, m, p, 3, dims, str, box, CU_TENSOR_MAP_SWIZZLE_128B, CU_TENSOR_MAP_L2_PROMOTION_L2_128B);
}

}

extern "C" void kernel_launch(void* const* d_in, const int* in_sizes, int n_in, void* d_out, int out_size) {
  using namespace fk;
  (void)in_sizes; (void)n_in; (void)out_size;
  static PFN_encodeTiled enc = nullptr;
  static Scratch* scr = nullptr;
  if (!enc) {
    void* fn = nullptr; cudaDriverEntryPointQueryResult qr;
    cudaGetDriverEntryPoint("cuTensorMapEncodeTiled", &fn, cudaEnableDefault, &qr);
    enc = (PFN_encodeTiled)fn;
    cudaGetSymbolAddress((void**)&scr, g_scr);
    cudaFuncSetAttribute(fused_kernel, cudaFuncAttributeMaxDynamicSharedMemorySize, SMEM_BYTES);
  }
  typedef const __nv_bfloat16* bp;
  Params prm;
  prm.w_r = (bp)d_in[6];
  prm.wsp[0] = (const char*)d_in[1]; prm.wsp[1] = (const char*)d_in[2];
  map2d(enc, &prm.ws[0], d_in[1], S_, S_, 128, 64);
  map2d(enc, &prm.ws[1], d_in[2], S_, S_, 128, 64);
  map3d(enc, &prm.n, scr->n, S_, D_, 64, 2);
  map2d(enc, &prm.wm, d_in[11], D_, 6 * D_, 8, 256, CU_TENSOR_MAP_SWIZZLE_NONE, CU_TENSOR_MAP_L2_PROMOTION_L2_256B);
  map2d(enc, &prm.p, scr->P, 2 * S_, D_, 128, 64);
  map2d(enc, &prm.wd[0], d_in[3], D_, D_, 64, 64);
  map2d(enc, &prm.wd[1], d_in[4], D_, D_, 64, 64);
  map2d(enc, &prm.wg, d_in[7], D_, F_, 128, 32, CU_TENSOR_MAP_SWIZZLE_64B);
  map2d(enc, &prm.wu, d_in[8], D_, F_, 128, 32, CU_TENSOR_MAP_SWIZZLE_64B);
  for (int i = 0; i < 3; i++) prm.we[i] = (const char*)d_in[7 + i];
  map2d(enc, &prm.ps, scr->P, 2 * S_, D_, 32, 64);
  for (int i = 0; i < 2; i++) {
    const cuuint64_t dims[3] = {128, 8, i ? 2048u : 3584u}, str[2] = {256, 2048}; const cuuint32_t box[3] = {8, 1, 32};
    mapnd(enc, &prm.tch[i], d_in[i ? 0 : 9], 3, dims, str, box, CU_TENSOR_MAP_SWIZZLE_NONE, CU_TENSOR_MAP_L2_PROMOTION_L2_256B);
  }
  map3d(enc, &prm.xm, d_in[0], S_, D_, 16, 2);
  map3d(enc, &prm.om, d_out, S_, D_, 16, 2);
  {
    const cuuint64_t dims[5] = {64, 2, 8, 224, 16}, str[4] = {8 * 2048, 2048, 16 * 2048, 128}; const cuuint32_t box[5] = {64, 2, 8, 2, 2};
    mapnd(enc, &prm.wdn, d_in[9], 5, dims, str, box, CU_TENSOR_MAP_SWIZZLE_128B, CU_TENSOR_MAP_L2_PROMOTION_L2_128B);
  }

  fused_kernel<<<NCTA, 384, SMEM_BYTES, cudaStreamPerThread>>>((bp)d_in[0], scr, (__nv_bfloat16*)d_out, (bp)d_in[10], (bp)d_in[3], (bp)d_in[4], prm);
}
```

```cpp
#include <cuda_runtime.h>
#include <cuda_bf16.h>
#include <cuda.h>
#include <stdint.h>

#define DEVINL __device__ __forceinline__

namespace fk {

constexpr int S_ = 2048, D_ = 1024, F_ = 3584;
constexpr int NCTA = 128;
constexpr int SLOT = 16384;
constexpr int STAGE = 3 * SLOT;
constexpr int BUF = 2 * SLOT;
constexpr int E_OFF = 5 * BUF;
constexpr int SP_OFF = 4 * STAGE;
constexpr int MISC_OFF = SP_OFF + 32768;
constexpr int SMEM_BYTES = MISC_OFF + 3072;
constexpr int BAR_OFF = MISC_OFF;
constexpr int SEL_OFF = MISC_OFF + 344;
constexpr int BK_OFF = MISC_OFF + 360;
constexpr int CST_OFF = MISC_OFF + 368;
constexpr int PFLAG_OFF = MISC_OFF + 384;
constexpr int TAB_OFF = MISC_OFF + 512;
enum { T_WH = 0, T_ONE = 320, T_WL = 576, T_GA = 896, T_A = 1152, T_S = 1408, T_G = 1664 };
constexpr int KEY_OFF = TAB_OFF + 2048;
constexpr int POLL_OFF = TAB_OFF + 256;
constexpr int T1_OFF = TAB_OFF + 1536;
constexpr int RKA_OFF = BUF;
constexpr int RKB_OFF = RKA_OFF + 2048;
constexpr int RED_OFF = RKB_OFF + 2048;
constexpr int DN_OFF = RED_OFF + 4096;

enum { B_FULL = 0, B_EMPTY = 4, B_PREADY = 8, B_MF = 12  , B_FULL2 = 20  , B_EMPTY2 = 25  , B_A29 = 30, B_ADONE = 31,
       B_RSDONE = 32, B_TAB = 33, B_B27 = 34, B_SEL = 35, B_DN = 36, B_EFULL = 37, B_PS = 38  , B_WF = 40, B_BK = 41, B_FIN = 42, B_NUM = 43 };
constexpr unsigned long long CNT0 = 0x1111888855551111ull, CNT1 = 0x4244444222221111ull, CNT2 = 0x1111111111111122ull;

#define FK_SKIP 0
#define FK_X 0
#define FK_PS0 1
#define FK_XN 0
#define FK_S1 0
#define FK_NL 12
#define FK_XD 0
#define FK_GS 1
#define FK_TD 1
#define FK_TX 1
#define FK_ODELAY 100
#define FK_OMASK 0
#define FK_OSPACE2 0
#define FK_NP 0
#define FK_G1 20
#define FK_GP 2
#define FK_QR 31
#define FK_H1 1
#define FK_REL 0x14
#define FK_WSPF 22
#define FK_SPACE 300
#define FK_OSPACE 200
#define FK_NOMC 4
#define FK_TR0 0
#define FK_G0 3
#define FK_NA 0
#define FK_PACE 800
#define FK_QP 5
#define FK_PSPACE 400
#define FK_ORD 0
#define FK_PDELAY 700
constexpr int SPIN_LIMIT = 1 << 20;
constexpr uint32_t SENT = 0xFFFFFFFFu;

struct Scratch {
  uint4 part[128 * 128 * 4];
  uint4 stats[128 * 128];
  uint4 rowsH[32 * 128];
  uint4 rowsB[32 * 128];
  uint4 cand[16 * 8];
  uint2 rs[2 * S_];
  uint4 cst[8];
  float mod[2][6 * D_];
  uint2 u[2 * D_];
  unsigned flagP[128 * 4 * 8];
  unsigned cntN[12 * 32];
  unsigned cntMod[2 * 32];
  unsigned epoch[32];
  unsigned claim[64 * 8];
  alignas(1024) __nv_bfloat16 n[S_ * D_];
  __nv_bfloat16 P[2 * S_ * D_];
};
__device__ __align__(1024) Scratch g_scr;

struct Params {
  CUtensorMap ws[2];
  CUtensorMap n;
  CUtensorMap wm;
  CUtensorMap p;
  CUtensorMap wg, wu;
  CUtensorMap xm;
  CUtensorMap wdn;
  CUtensorMap wd[2];
  CUtensorMap om;
  CUtensorMap ps;
  CUtensorMap tch[2];
  const __nv_bfloat16* w_r;
  const char* wsp[2];
  const char* we[3];
};

DEVINL uint32_t smem_u32(const void* p) { return (uint32_t)__cvta_generic_to_shared(p); }
DEVINL void mbar_init(uint32_t bar, uint32_t cnt) { asm volatile("mbarrier.init.shared::cta.b64 [%0], %1;" ::"r"(bar), "r"(cnt) : "memory"); }
DEVINL void mbar_expect_tx(uint32_t bar, uint32_t bytes) { asm volatile("mbarrier.arrive.expect_tx.shared::cta.b64 _, [%0], %1;" ::"r"(bar), "r"(bytes) : "memory"); }
DEVINL void mbar_arrive(uint32_t bar) { asm volatile("mbarrier.arrive.shared::cta.b64 _, [%0];" ::"r"(bar) : "memory"); }
DEVINL void mbar_wait(uint32_t bar, uint32_t parity) {
  asm volatile("{\n.reg .pred p;\n.reg .u32 c;\nmov.u32 c, 0;\n"
               "LW:\nmbarrier.try_wait.parity.shared::cta.b64 p, [%0], %1;\n@p bra LD;\n"
               "add.u32 c, c, 1;\nsetp.lt.u32 p, c, 1048576;\n@p bra LW;\ntrap;\nLD:\n}" ::"r"(bar), "r"(parity) : "memory");
}
DEVINL void mbar_wait_cluster(uint32_t bar, uint32_t parity) {
  asm volatile("{\n.reg .pred p;\n.reg .u32 c;\nmov.u32 c, 0;\n"
               "LW:\nmbarrier.try_wait.parity.acquire.cluster.shared::cta.b64 p, [%0], %1;\n@p bra LD;\n"
               "add.u32 c, c, 1;\nsetp.lt.u32 p, c, 1048576;\n@p bra LW;\ntrap;\nLD:\n}" ::"r"(bar), "r"(parity) : "memory");
}
#define SPIN_CHECK(it) asm volatile("{\n.reg .pred p;\nsetp.gt.s32 p, %0, %1;\n@p trap;\n}" ::"r"(++(it)), "n"(SPIN_LIMIT))
DEVINL void fence_async_smem() { asm volatile("fence.proxy.async.shared::cta;" ::: "memory"); }
DEVINL void fence_async_global() { asm volatile("fence.proxy.async.global;" ::: "memory"); }
template <int BIT> DEVINL void rel_fence() { if ((FK_REL >> BIT) & 1) asm volatile("fence.acq_rel.gpu;" ::: "memory"); }
DEVINL void fence_gpu() { asm volatile("fence.acq_rel.gpu;" ::: "memory"); }
template <int ID, int N> DEVINL void named_bar() { asm volatile("bar.sync %0, %1;" ::"n"(ID), "n"(N) : "memory"); }
DEVINL bool elect_one() { uint32_t p; asm volatile("{\n.reg .pred e;\nelect.sync _|e, 0xffffffff;\nselp.u32 %0, 1, 0, e;\n}" : "=r"(p)); return p; }
DEVINL unsigned clk32() { unsigned c; asm volatile("mov.u32 %0, %%clock;" : "=r"(c)); return c; }
#define FK_GRIDW 32
#define FK_GRID 0
DEVINL void grid_wait() {
  if (FK_GRID) {
    unsigned t0, t1;
    asm volatile("mov.u32 %0, %%globaltimer_lo;" : "=r"(t0));
    do { asm volatile("mov.u32 %0, %%globaltimer_lo;" : "=r"(t1)); } while (((t0 - FK_GRIDW) ^ t1) < FK_GRID + 0u + !FK_GRID);
  }
}
DEVINL void spin(unsigned n) { const unsigned c = clk32(); while (clk32() - c < n) {} }

constexpr uint64_t POL_NORMAL = 0x1000000000000000ull, POL_FIRST = 0x12F0000000000000ull;
#define FK_HINTS 0x30B
template <int BIT> DEVINL constexpr uint64_t pol() { return ((FK_HINTS >> BIT) & 1) ? POL_FIRST : POL_NORMAL; }
DEVINL void tma_2d(uint32_t dst, const CUtensorMap* m, int x, int y, uint32_t bar, uint64_t pol) {
  asm volatile("cp.async.bulk.tensor.2d.shared::cluster.global.mbarrier::complete_tx::bytes.L2::cache_hint [%0], [%1, {%3, %4}], [%2], %5;"
               ::"r"(dst), "l"(m), "r"(bar), "r"(x), "r"(y), "l"(pol) : "memory");
}
DEVINL void tma_3d(uint32_t dst, const CUtensorMap* m, int y, int z, uint32_t bar, uint64_t pol) {
  asm volatile("cp.async.bulk.tensor.3d.shared::cluster.global.mbarrier::complete_tx::bytes.L2::cache_hint [%0], [%1, {0, %3, %4}], [%2], %5;"
               ::"r"(dst), "l"(m), "r"(bar), "r"(y), "r"(z), "l"(pol) : "memory");
}
DEVINL void tma_3d_mc(uint32_t dst, const CUtensorMap* m, int y, int z, uint32_t bar, uint64_t pol) {
  asm volatile("cp.async.bulk.tensor.3d.shared::cluster.global.mbarrier::complete_tx::bytes.multicast::cluster.L2::cache_hint [%0], [%1, {0, %3, %4}], [%2], %5, %6;"
               ::"r"(dst), "l"(m), "r"(bar), "r"(y), "r"(z), "h"((unsigned short)3), "l"(pol) : "memory");
}
DEVINL void tma_2d_mc(uint32_t dst, const CUtensorMap* m, int x, int y, uint32_t bar, uint64_t pol) {
  asm volatile("cp.async.bulk.tensor.2d.shared::cluster.global.mbarrier::complete_tx::bytes.multicast::cluster.L2::cache_hint [%0], [%1, {%3, %4}], [%2], %5, %6;"
               ::"r"(dst), "l"(m), "r"(bar), "r"(x), "r"(y), "h"((unsigned short)3), "l"(pol) : "memory");
}
DEVINL void tma_store_2d(const CUtensorMap* m, uint32_t src, int x, int y) {
  asm volatile("cp.async.bulk.tensor.2d.global.shared::cta.bulk_group [%0, {%2, %3}], [%1];" ::"l"(m), "r"(src), "r"(x), "r"(y) : "memory");
}
DEVINL void bulk_store(void* dst, uint32_t src, uint32_t bytes) {
  asm volatile("cp.async.bulk.global.shared::cta.bulk_group [%0], [%1], %2;" ::"l"(dst), "r"(src), "r"(bytes) : "memory");
}
DEVINL void bulk_load(uint32_t dst, const void* src, uint32_t bytes, uint32_t bar, uint64_t pol) {
  asm volatile("cp.async.bulk.shared::cluster.global.mbarrier::complete_tx::bytes.L2::cache_hint [%0], [%1], %2, [%3], %4;" ::"r"(dst), "l"(src), "r"(bytes), "r"(bar), "l"(pol) : "memory");
}
template <int N> DEVINL void bulk_wait_read() { asm volatile("cp.async.bulk.wait_group.read %0;" ::"n"(N) : "memory"); }
DEVINL void pf_bulk(const void* p, uint32_t bytes) { asm volatile("cp.async.bulk.prefetch.L2.global [%0], %1;" ::"l"(p), "r"(bytes) : "memory"); }
DEVINL void bulk_commit() { asm volatile("cp.async.bulk.commit_group;" ::: "memory"); }
template <int N> DEVINL void bulk_wait() { asm volatile("cp.async.bulk.wait_group %0;" ::"n"(N) : "memory"); }
DEVINL void prefetch_tmap(const CUtensorMap* m) { asm volatile("prefetch.tensormap [%0];" ::"l"(m) : "memory"); }

DEVINL void wg_fence() { asm volatile("wgmma.fence.sync.aligned;" ::: "memory"); }
DEVINL void wg_commit() { asm volatile("wgmma.commit_group.sync.aligned;" ::: "memory"); }
template <int N> DEVINL void wg_wait() { asm volatile("wgmma.wait_group.sync.aligned %0;" ::"n"(N) : "memory"); }
DEVINL uint32_t desc_lo(uint32_t addr, uint32_t lbo) { return ((addr & 0x3FFFF) >> 4) | ((lbo >> 4) << 16); }

#define R8(a, o) "+f"(a[o]), "+f"(a[o + 1]), "+f"(a[o + 2]), "+f"(a[o + 3]), "+f"(a[o + 4]), "+f"(a[o + 5]), "+f"(a[o + 6]), "+f"(a[o + 7])
#define R64(a, o) R8(a, o), R8(a, o + 8), R8(a, o + 16), R8(a, o + 24), R8(a, o + 32), R8(a, o + 40), R8(a, o + 48), R8(a, o + 56)
#define ACC64 "{%0, %1, %2, %3, %4, %5, %6, %7, %8, %9, %10, %11, %12, %13, %14, %15, "              \
              "%16, %17, %18, %19, %20, %21, %22, %23, %24, %25, %26, %27, %28, %29, %30, %31, "    \
              "%32, %33, %34, %35, %36, %37, %38, %39, %40, %41, %42, %43, %44, %45, %46, %47, "    \
              "%48, %49, %50, %51, %52, %53, %54, %55, %56, %57, %58, %59, %60, %61, %62, %63"
#define ACC128 ACC64 ", %64, %65, %66, %67, %68, %69, %70, %71, %72, %73, %74, %75, %76, %77, %78, %79, "      \
              "%80, %81, %82, %83, %84, %85, %86, %87, %88, %89, %90, %91, %92, %93, %94, %95, "               \
              "%96, %97, %98, %99, %100, %101, %102, %103, %104, %105, %106, %107, %108, %109, %110, %111, "   \
              "%112, %113, %114, %115, %116, %117, %118, %119, %120, %121, %122, %123, %124, %125, %126, %127"
template <int TB> DEVINL void wgmma_n256(float (&d)[128], uint32_t da, uint32_t db, int scale_d) {
  asm volatile("{\n.reg .pred p;\n.reg .b64 a, b;\nsetp.ne.b32 p, %130, 0;\nmov.b64 a, {%128, 0x40000040};\nmov.b64 b, {%129, 0x40000040};\n"
               "wgmma.mma_async.sync.aligned.m64n256k16.f32.bf16.bf16 " ACC128 "}, a, b, p, 1, 1, 0, %131;\n}\n"
               : R64(d, 0), R64(d, 64) : "r"(da), "r"(db), "r"(scale_d), "n"(TB));
}
template <int TB, int HI = 0x40000040> DEVINL void wgmma_n128(float (&d)[64], uint32_t da, uint32_t db) {
  asm volatile("{\n.reg .b64 a, b;\nmov.b64 a, {%64, %67};\nmov.b64 b, {%65, %67};\n"
               "wgmma.mma_async.sync.aligned.m64n128k16.f32.bf16.bf16 " ACC64 "}, a, b, 1, 1, 1, 0, %66;\n}\n" : R64(d, 0) : "r"(da), "r"(db), "n"(TB), "n"(HI));
}
template <int SC> DEVINL void wgmma_n128_rs(float (&d)[64], const uint32_t* a, uint32_t db) {
  asm volatile("{\n.reg .pred p;\n.reg .b64 b;\nsetp.ne.b32 p, %69, 0;\nmov.b64 b, {%68, 0x40000040};\n"
               "wgmma.mma_async.sync.aligned.m64n128k16.f32.bf16.bf16 " ACC64 "}, {%64, %65, %66, %67}, b, p, 1, 1, 0;\n}\n"
               : R64(d, 0) : "r"(a[0]), "r"(a[1]), "r"(a[2]), "r"(a[3]), "r"(db), "n"(SC));
}
template <int N> DEVINL void reg_fence(float (&a)[N]) {
#pragma unroll
  for (int i = 0; i < N; i++) asm volatile("" : "+f"(a[i])::"memory");
}

DEVINL uint32_t pack_bf16(float lo, float hi) { uint32_t r; asm("cvt.rn.bf16x2.f32 %0, %1, %2;" : "=r"(r) : "f"(hi), "f"(lo)); return r; }
DEVINL uint32_t add_bf16x2(uint32_t a, uint32_t b) { uint32_t r; asm("add.rn.bf16x2 %0, %1, %2;" : "=r"(r) : "r"(a), "r"(b)); return r; }
DEVINL uint32_t mul_bf16x2(uint32_t a, uint32_t b) { uint32_t r; asm("mul.rn.bf16x2 %0, %1, %2;" : "=r"(r) : "r"(a), "r"(b)); return r; }
DEVINL uint32_t fma_bf16x2(uint32_t a, uint32_t b, uint32_t c) { uint32_t r; asm("fma.rn.bf16x2 %0, %1, %2, %3;" : "=r"(r) : "r"(a), "r"(b), "r"(c)); return r; }
DEVINL float bf_lo(uint32_t w) { return __uint_as_float(w << 16); }
DEVINL float bf_hi(uint32_t w) { return __uint_as_float(w & 0xFFFF0000u); }
DEVINL float round_bf16(float v) { return bf_lo(pack_bf16(v, 0.f)); }
DEVINL float sigmoid_f(float v) { float r; asm("rcp.approx.ftz.f32 %0, %1;" : "=f"(r) : "f"(1.f + __expf(-v))); return r; }
DEVINL float rsqrt_f(float v) { float r; asm("rsqrt.approx.ftz.f32 %0, %1;" : "=f"(r) : "f"(v)); return r; }
DEVINL float silu_f(float v) { return v * sigmoid_f(v); }
DEVINL void stsm_x4(uint32_t addr, const uint32_t* r) {
  asm volatile("stmatrix.sync.aligned.m8n8.x4.shared.b16 [%0], {%1, %2, %3, %4};" ::"r"(addr), "r"(r[0]), "r"(r[1]), "r"(r[2]), "r"(r[3]) : "memory");
}
DEVINL void ldsm_x4(uint32_t addr, uint32_t* r) {
  asm volatile("ldmatrix.sync.aligned.m8n8.x4.shared.b16 {%0, %1, %2, %3}, [%4];" : "=r"(r[0]), "=r"(r[1]), "=r"(r[2]), "=r"(r[3]) : "r"(addr) : "memory");
}
DEVINL void ldsm_x4_t(uint32_t addr, uint32_t* r) {
  asm volatile("ldmatrix.sync.aligned.m8n8.x4.trans.shared.b16 {%0, %1, %2, %3}, [%4];" : "=r"(r[0]), "=r"(r[1]), "=r"(r[2]), "=r"(r[3]) : "r"(addr) : "memory");
}
DEVINL void mma_16816(float (&c)[4], const uint32_t* a, uint32_t b0, uint32_t b1) {
  asm("mma.sync.aligned.m16n8k16.row.col.f32.bf16.bf16.f32 {%0, %1, %2, %3}, {%4, %5, %6, %7}, {%8, %9}, {%0, %1, %2, %3};"
      : "+f"(c[0]), "+f"(c[1]), "+f"(c[2]), "+f"(c[3]) : "r"(a[0]), "r"(a[1]), "r"(a[2]), "r"(a[3]), "r"(b0), "r"(b1));
}
DEVINL void mma_1688(float (&c)[4], uint32_t a0, uint32_t a1, uint32_t b0) {
  asm("mma.sync.aligned.m16n8k8.row.col.f32.bf16.bf16.f32 {%0, %1, %2, %3}, {%4, %5}, {%6}, {%0, %1, %2, %3};"
      : "+f"(c[0]), "+f"(c[1]), "+f"(c[2]), "+f"(c[3]) : "r"(a0), "r"(a1), "r"(b0));
}
DEVINL float4 lds128(uint32_t a) { float4 v; asm volatile("ld.shared.v4.f32 {%0, %1, %2, %3}, [%4];" : "=f"(v.x), "=f"(v.y), "=f"(v.z), "=f"(v.w) : "r"(a)); return v; }
DEVINL uint4 lds128u(uint32_t a) { uint4 v; asm volatile("ld.shared.v4.u32 {%0, %1, %2, %3}, [%4];" : "=r"(v.x), "=r"(v.y), "=r"(v.z), "=r"(v.w) : "r"(a)); return v; }
DEVINL float2 lds64(uint32_t a) { float2 v; asm volatile("ld.shared.v2.f32 {%0, %1}, [%2];" : "=f"(v.x), "=f"(v.y) : "r"(a)); return v; }
DEVINL uint32_t lds32u(uint32_t a) { uint32_t v; asm volatile("ld.shared.u32 %0, [%1];" : "=r"(v) : "r"(a)); return v; }
DEVINL void sts128(uint32_t a, float x, float y, float z, float w) { asm volatile("st.shared.v4.f32 [%0], {%1, %2, %3, %4};" ::"r"(a), "f"(x), "f"(y), "f"(z), "f"(w) : "memory"); }
DEVINL void sts128u(uint32_t a, uint32_t x, uint32_t y, uint32_t z, uint32_t w) { asm volatile("st.shared.v4.u32 [%0], {%1, %2, %3, %4};" ::"r"(a), "r"(x), "r"(y), "r"(z), "r"(w) : "memory"); }
DEVINL void sts64u(uint32_t a, uint32_t x, uint32_t y) { asm volatile("st.shared.v2.u32 [%0], {%1, %2};" ::"r"(a), "r"(x), "r"(y) : "memory"); }
DEVINL void sts32v(uint32_t a, uint32_t v) { asm volatile("st.volatile.shared.u32 [%0], %1;" ::"r"(a), "r"(v) : "memory"); }
DEVINL void sts32(uint32_t a, float v) { asm volatile("st.shared.f32 [%0], %1;" ::"r"(a), "f"(v) : "memory"); }

DEVINL uint4 ld_msg(const void* p) {
  unsigned long long a, b;
  asm volatile("{\n.reg .b128 r;\nld.relaxed.gpu.global.b128 r, [%2];\nmov.b128 {%0, %1}, r;\n}" : "=l"(a), "=l"(b) : "l"(p) : "memory");
  return make_uint4((uint32_t)a, (uint32_t)(a >> 32), (uint32_t)b, (uint32_t)(b >> 32));
}
DEVINL void st_msg(void* p, uint32_t x, uint32_t y, uint32_t z, uint32_t w) {
  unsigned long long a = (unsigned long long)x | ((unsigned long long)y << 32), b = (unsigned long long)z | ((unsigned long long)w << 32);
  asm volatile("{\n.reg .b128 r;\nmov.b128 r, {%1, %2};\nst.relaxed.gpu.global.b128 [%0], r;\n}" ::"l"(p), "l"(a), "l"(b) : "memory");
}
DEVINL uint2 ld_msg8(const void* p) {
  unsigned long long a;
  asm volatile("ld.relaxed.gpu.global.b64 %0, [%1];" : "=l"(a) : "l"(p) : "memory");
  return make_uint2((uint32_t)a, (uint32_t)(a >> 32));
}
DEVINL void st_msg8(void* p, uint32_t x, uint32_t y) {
  asm volatile("st.relaxed.gpu.global.b64 [%0], %1;" ::"l"(p), "l"((unsigned long long)x | ((unsigned long long)y << 32)) : "memory");
}
DEVINL unsigned ld_rlx(const void* p) { unsigned v; asm volatile("ld.relaxed.gpu.global.u32 %0, [%1];" : "=r"(v) : "l"(p) : "memory"); return v; }
DEVINL void st_rlx(unsigned* p, unsigned v) { asm volatile("st.relaxed.gpu.global.u32 [%0], %1;" ::"l"(p), "r"(v) : "memory"); }
DEVINL void red_add(unsigned* p, unsigned v) { asm volatile("red.relaxed.gpu.global.add.u32 [%0], %1;" ::"l"(p), "r"(v) : "memory"); }
DEVINL uint4 ldg_nc(const void* p) {
  uint4 v;
  asm volatile("ld.global.nc.L1::no_allocate.v4.u32 {%0, %1, %2, %3}, [%4];" : "=r"(v.x), "=r"(v.y), "=r"(v.z), "=r"(v.w) : "l"(p));
  return v;
}
DEVINL float4 ldg_cg(const float* p) { float4 v; asm volatile("ld.global.cg.v4.f32 {%0, %1, %2, %3}, [%4];" : "=f"(v.x), "=f"(v.y), "=f"(v.z), "=f"(v.w) : "l"(p) : "memory"); return v; }
DEVINL void wait_cnt(const unsigned* p, unsigned target) {
  int it = 0;
  while ((int)(ld_rlx(p) - target) < 0) { SPIN_CHECK(it); __nanosleep(100); }
}

#define TRACE2(id)
#define TRACE3(id)
#define TRACE(id)
#define TRACE_CLK(id)

#define STAMP2(i)
#define STAMP(i)
DEVINL uint32_t fkey(float v) { const uint32_t u = __float_as_uint(v); return (u & 0x80000000u) ? ~u : (u | 0x80000000u); }
DEVINL float fkey_inv(uint32_t k) { return __uint_as_float((k & 0x80000000u) ? (k & 0x7FFFFFFFu) : ~k); }
DEVINL uint32_t redux_max(uint32_t v) { uint32_t r; asm volatile("redux.sync.max.u32 %0, %1, 0xffffffff;" : "=r"(r) : "r"(v)); return r; }
DEVINL void warp_top2(uint32_t key, uint32_t& k1, uint32_t& k2) { k1 = redux_max(key); k2 = redux_max(key == k1 ? 0u : key); }
DEVINL int key_row(uint32_t k) { return 2047 - (int)(k & 2047u); }
DEVINL int blk_src(int q, int cgrp) { const int f = q - 4, kk = (f * 37) >> 8, i = f - kk * 7; return f < 0 ? cgrp * 4 + q : (FK_SKIP ? i + (i >= cgrp) : i == cgrp ? 7 : i) * 4 + kk; }
DEVINL void split_assign(int c, int& grp, int& gi) {
  const int c7 = ((c - 36) * 37) >> 8;
  grp = c < 4 ? 0 : c < 36 ? (c - 4) & 7 : c - 35 - c7 * 7; gi = c < 4 ? c + 4 : c < 36 ? (c - 4) >> 3 : c7 + 4;
}
DEVINL uint32_t pstage(int kk) { return ((0xABA4 >> (kk * 4)) & 15) * SLOT; }
DEVINL uint32_t buf_off(int u) { return ((0x42130 >> (u * 4)) & 15) * BUF; }
DEVINL int cnt_idx(int kb) { return kb < 4 ? (8 + kb) * 32 : (kb >> 2) * 32 + (kb & 3); }

__global__ void __launch_bounds__(384, 1) __cluster_dims__(2, 1, 1)
fused_kernel(const __nv_bfloat16* __restrict__ x, Scratch* const S, __nv_bfloat16* __restrict__ out, const __nv_bfloat16* __restrict__ cvec,
             const __nv_bfloat16* __restrict__ wd_re, const __nv_bfloat16* __restrict__ wd_im, const __grid_constant__ Params prm) {
  extern __shared__ __align__(1024) uint8_t smem_raw[];
  const uint32_t sb = smem_u32(smem_raw);
  const int tid = threadIdx.x, lane = tid & 31;
  const int warp = __shfl_sync(~0u, tid >> 5, 0);
  const int bx = blockIdx.x, rank = bx & 1;
  auto BAR = [&](int i) { return sb + BAR_OFF + i * 8; };

  uint4 xr[8];
  if ((warp & ~1) == 2) {
    const uint4* src = reinterpret_cast<const uint4*>(x + (size_t)(bx * 2 + warp - 2) * D_) + lane;
#pragma unroll
    for (int i = 0; i < 4; i++) xr[i] = ldg_nc(src + 32 * i);
  }
  if (tid == 0) TRACE(0);
  if ((warp & ~1) != 2 && elect_one()) {
    const int w = warp < 2 ? warp : warp - 2;
#pragma unroll
    for (int k = 0; k < 5; k++) {
      const int i = w + 10 * k;
      if (i < B_NUM) mbar_init(BAR(i), (uint32_t)((i < 16 ? CNT0 : i < 32 ? CNT1 : CNT2) >> ((i & 15) * 4)) & 15u);
    }
    if (w < 4) mbar_expect_tx(BAR(B_FULL + w), STAGE);
    asm volatile("fence.mbarrier_init.release.cluster;" ::: "memory");
    if (w) prefetch_tmap(&prm.ws[1] + w);
  }
  if ((warp & ~1) != 2) { named_bar<4, 320>(); asm volatile("bar.arrive 3, 384;" ::: "memory"); }
  if (warp < 2 && elect_one()) {
    unsigned smid; asm volatile("mov.u32 %0, %%smid;" : "=r"(smid));
    int c = ((smid >> 1) + ((smid >> 1) >= 62 ? 2 : 4)) & 63;
    if (warp == 0) {
      int g0, i0; split_assign(c, g0, i0);
      asm volatile("cp.async.bulk.prefetch.tensor.2d.L2.global [%0, {0, %1}];" ::"l"(&prm.ws[i0 >> 2]), "r"((g0 * 2 + rank) * 128) : "memory");
    } else if (rank == 0) {
      int it = 0;
      while (atomicExch(&S->claim[c * 8], 1u)) { c = (c + 1) & 63; SPIN_CHECK(it); }
      sts32v(sb + BK_OFF, c);
      asm volatile("fence.acq_rel.cta;" ::: "memory");
    }
  }
  uint32_t tag = 0;
  if (warp == 0) tag = ld_rlx(S->epoch);
  __syncwarp();
  asm volatile("barrier.cluster.arrive.relaxed.aligned;" ::: "memory");
  const uint32_t ring = sb + SP_OFF + (warp - 2) * 16384, mf = BAR(B_MF + (warp - 2) * 4);
  const int jw = bx >> 6, e0 = (bx & 63) * 16;
  const __nv_bfloat16* src = (jw ? wd_im : wd_re) + (size_t)e0 * D_;
  int nc = 0;
  if ((warp & ~1) == 2) {
#pragma unroll 1
    for (int G = 0; G < 8; G += (G == 0 && warp == 2) + 1) {
      if (G) { mbar_wait(mf + (nc & 3) * 8, (nc >> 2) & 1); nc++; }
      const uint32_t stg = ring + (nc & 3) * 4096, sl = stg + (G ? (lane >> 4) * 2048 + (lane & 15) * 16 : lane * 16), st = G ? 256 : 512;
      if (G) {
#pragma unroll
        for (int k = 0; k < 8; k++) xr[k] = lds128u(sl + k * 256);
      }
      float s0 = 0.f, s1 = 0.f, q0 = 0.f, q1 = 0.f, s2 = 0.f, s3 = 0.f, q2 = 0.f, q3 = 0.f;
      float v[64];
#pragma unroll
      for (int h = 0; h < 2; h++)
        if (h == 0 || G) {
#pragma unroll
          for (int k = 4 * h; k < 4 * h + 4; k++) {
            float* u = v + 8 * k;
            u[0] = bf_lo(xr[k].x); u[1] = bf_hi(xr[k].x); u[2] = bf_lo(xr[k].y); u[3] = bf_hi(xr[k].y);
            u[4] = bf_lo(xr[k].z); u[5] = bf_hi(xr[k].z); u[6] = bf_lo(xr[k].w); u[7] = bf_hi(xr[k].w);
#pragma unroll
            for (int i = 0; i < 8; i += 4) {
              s0 += u[i]; s1 += u[i + 1]; s2 += u[i + 2]; s3 += u[i + 3];
              q0 = fmaf(u[i], u[i], q0); q1 = fmaf(u[i + 1], u[i + 1], q1); q2 = fmaf(u[i + 2], u[i + 2], q2); q3 = fmaf(u[i + 3], u[i + 3], q3);
            }
          }
        }
      float sum = (s0 + s1) + (s2 + s3), sq = (q0 + q1) + (q2 + q3);
#pragma unroll
      for (int o = 1; o < 32; o <<= 1)
        if (o < 16 || !G) { sum += __shfl_xor_sync(~0u, sum, o); sq += __shfl_xor_sync(~0u, sq, o); }
      const float mean = sum * (1.f / D_);
      const float rstd = rsqrt_f(fmaxf(fmaf(-mean, mean, sq * (1.f / D_)), 0.f) + 1e-5f), nmr = -mean * rstd;
#pragma unroll
      for (int h = 0; h < 2; h++)
        if (h == 0 || G) {
#pragma unroll
          for (int k = 4 * h; k < 4 * h + 4; k++) {
            const float* u = v + 8 * k;
            sts128u(sl + k * st, pack_bf16(fmaf(u[0], rstd, nmr), fmaf(u[1], rstd, nmr)), pack_bf16(fmaf(u[2], rstd, nmr), fmaf(u[3], rstd, nmr)),
                    pack_bf16(fmaf(u[4], rstd, nmr), fmaf(u[5], rstd, nmr)), pack_bf16(fmaf(u[6], rstd, nmr), fmaf(u[7], rstd, nmr)));
          }
        }
      fence_async_smem();
      const int kq = bx >> 5;
      if (elect_one()) {
        bulk_store(S->n + (size_t)(G * 256 + bx * 2 + (G ? 0 : warp - 2)) * D_, stg, G ? 4096 : 2048); bulk_commit();
        if (G == 0) { bulk_wait<0>(); rel_fence<0>(); red_add(&S->cntN[cnt_idx(kq)], 1); TRACE(42 + warp); }
      }
      if (G == 0) named_bar<3, 384>();
      if (elect_one()) {
        if (G == 0 && warp == 2) mbar_wait(BAR(B_FULL), 0);
        if (G >= 4) { bulk_wait<1>(); red_add(&S->cntN[(G - 1) * 32 + kq], 2); }
#pragma unroll 1
        for (int k = G ? nc + 1 : 0; k < (warp == 2 ? nc + 2 : 1); k++) {
          mbar_expect_tx(mf + (k & 3) * 8, 4096);
          bulk_load(ring + ((k + 1) & 3) * 4096, k < 6 ? x + (size_t)((k + 4 - warp) * 256 + bx * 2) * D_ : src + (k - 6) * 2 * D_, 4096, mf + (k & 3) * 8, k < 6 ? pol<7>() : pol<2>());
        }
        if (G == 1 || G == 2 || G == 7) { bulk_wait<0>(); rel_fence<1>(); red_add(&S->cntN[G * 32 + kq], 2); if (G > 1) TRACE(44 + (G & 3)); }
      }
      __syncwarp();
      if (warp == 3 && G) break;
    }
  }
  asm volatile("barrier.cluster.wait.acquire.aligned;" ::: "memory");
  int cl, grp, gi;
  asm volatile("{\n.reg .b32 ra;\nmapa.shared::cluster.u32 ra, %1, 0;\nld.volatile.shared::cluster.u32 %0, [ra];\n}" : "=r"(cl) : "r"(sb + BK_OFF) : "memory");
  cl = __shfl_sync(~0u, cl, 0);
  split_assign(cl, grp, gi);
  const int j = gi >> 2, m4 = gi & 3, t = grp * 2 + rank;
  const int cgrp = m4 * 2 + j;
  const int b = t * 8 + cgrp;
  const bool moe = gi < 7;
  const int eb = (j ? 64 + grp * 6 : grp * 8) + m4 * 2 + rank;

  if (warp < 4) {
    auto prefetch_piece = [&](int p) { if (!(FK_X & 1) && !((FK_X & 8) && p >= 12)) pf_bulk(prm.we[p >> 3] + (size_t)((p & 7) * 128 + b) * 7168, 7168); };
    auto weight_box = [&](int n, uint32_t bar) {
      if (moe && !(FK_X & 2) && !((FK_X & 8) && n >= 12)) {
        asm volatile("mbarrier.expect_tx.relaxed.cta.shared::cta.b64 [%0], 8192;" ::"r"(bar) : "memory");
        tma_2d(sb + SP_OFF + (n & 3) * 8192, &prm.wg + (n >> 3), eb * 32, (n & 7) * 128, bar, pol<3>());
      }
    };
    if (warp == 0) {
      const unsigned* flagAddr = &S->cntN[cnt_idx(lane)];
      const unsigned tgt = (tag + 1) * 64u;
      if (elect_one()) tma_2d(sb, &prm.ws[j], 0, t * 128, BAR(B_FULL), pol<0>());
      unsigned ready = 0;
      if (lane >= 4) sts32v(sb + POLL_OFF + lane * 4, tgt - 1);
#pragma unroll 1
      for (int g = 0; g < 32; g++) {
        const int s = g & 3;
        const uint32_t sa = sb + s * STAGE, fb = BAR(B_FULL + s);
        if (!((ready >> g) & 1)) {
          unsigned v;
          asm volatile("ld.volatile.shared.u32 %0, [%1];" : "=r"(v) : "r"(sb + POLL_OFF + lane * 4) : "memory");
          ready |= __ballot_sync(~0u, v == tgt) & ~15u;
          int it = 0;
          while (!((ready >> g) & 1)) {
            ready |= __ballot_sync(~0u, (lane >> 2) == (g >> 2) && ld_rlx(flagAddr) == tgt);
            SPIN_CHECK(it);
          }
          fence_async_global();
        }
        if (g >= 4) {
          mbar_wait(BAR(B_EMPTY + s), ((g >> 2) - 1) & 1);
          if (lane < 8 && ((~ready >> (lane * 4)) & 15))
            asm volatile("cp.async.cg.shared.global [%0], [%1], 16;" ::"r"(sb + POLL_OFF + lane * 16), "l"(&S->cntN[lane * 32]) : "memory");
          if (elect_one()) { TRACE2(128 + g); mbar_expect_tx(fb, STAGE); tma_2d(sa, &prm.ws[j], g * 64, t * 128, fb, pol<0>()); }
        }
        if (elect_one()) {
          if (g < FK_NOMC) { tma_3d(sa + SLOT, &prm.n, g * 64, m4 * 4, fb, pol<4>()); tma_3d(sa + 2 * SLOT, &prm.n, g * 64, m4 * 4 + 2, fb, pol<4>()); }
          else tma_3d_mc(sa + SLOT + rank * SLOT, &prm.n, g * 64, m4 * 4 + rank * 2, fb, pol<4>());
          if (g > 0 && g < 4) tma_2d(sa, &prm.ws[j], g * 64, t * 128, fb, pol<0>());
          TRACE2(64 + g);
        }
        if ((unsigned)(g - FK_WSPF) < 4u)
          asm volatile("prefetch.global.L2 [%0];" ::"l"(prm.wsp[j] + (size_t)(t * 128 + m4 * 32 + (g - FK_WSPF) * 8 + (lane >> 2)) * 4096 + 3584 + (lane & 3) * 128));
      }
      asm volatile("cp.async.wait_all;" ::: "memory");
    }
    asm volatile("" ::: "memory");
    if (warp == 1) {
      tag = ld_rlx(S->epoch) + 1;
      if (elect_one()) prefetch_tmap(&prm.ps);
      const uint32_t rb = sb + (m4 * 32 + lane) * 128 + ((lane & 7) << 4);
      float a0 = 0.f, a1 = 0.f, a2 = 0.f, a3 = 0.f;
#pragma unroll 1
      for (int g = 0; g < 32; g++) {
        const int s = g & 3;
        mbar_wait(BAR(B_FULL + s), (g >> 2) & 1);
        uint4 u[8];
#pragma unroll
        for (int c = 0; c < 8; c++) u[c] = lds128u((rb + s * STAGE) ^ (c << 4));
        u[7].x = __shfl_sync(~0u, u[7].x, lane);
        if (elect_one()) {
          mbar_arrive(BAR(B_EMPTY + s)); TRACE2(160 + g);
          if (FK_NP && g >= FK_G1 && (g - FK_G1) % FK_GP == 0 && (g - FK_G1) / FK_GP < FK_NP) prefetch_piece(4 + (g - FK_G1) / FK_GP);
          const int p = (g - FK_G0) >> FK_GS;
          if (g >= FK_G0 && !((g - FK_G0) & FK_GS) && (p < 8 ? moe && FK_TD == 1 : p < 12 && FK_TX)) {
            asm volatile("mbarrier.expect_tx.relaxed.cta.shared::cta.b64 [%0], 512;" ::"r"(BAR(B_RSDONE)) : "memory");
            tma_3d(sb + KEY_OFF, &prm.tch[p >> 3], p < 8 ? p : cgrp, p < 8 ? eb * 32 : t * 128 + (p - 8) * 32, BAR(B_RSDONE), POL_NORMAL);
          }
        }
#pragma unroll
        for (int c = 0; c < 8; c++) {
          a0 += bf_lo(u[c].x) + bf_lo(u[c].y); a1 += bf_hi(u[c].x) + bf_hi(u[c].y);
          a2 += bf_lo(u[c].z) + bf_lo(u[c].w); a3 += bf_hi(u[c].z) + bf_hi(u[c].w);
        }
      }
      if (lane == 0) mbar_arrive(BAR(B_RSDONE));
      mbar_wait(BAR(B_RSDONE), 0);
      st_msg8(&S->rs[j * S_ + t * 128 + m4 * 32 + lane], __float_as_uint((a0 + a1) + (a2 + a3)), tag);
    }
    asm volatile("" ::: "memory");
    if (warp >= 2) {
      tag = ld_rlx(S->epoch) + 1;
      float* const mod = S->mod[tag & 1];
      if (warp == 3) {
        const uint32_t stab = sb + TAB_OFF, stg = stab + 512;
        {
          const uint32_t cw = __ldg(reinterpret_cast<const uint32_t*>(cvec + t * 64) + lane);
          const uint32_t sp = pack_bf16(silu_f(bf_lo(cw)), silu_f(bf_hi(cw)));
          sts64u(stab + lane * 8, sp << 16, sp & 0xFFFF0000u);
        }
        float acc[8];
#pragma unroll
        for (int i = 0; i < 8; i++) acc[i] = 0.f;
#pragma unroll 1
        for (int n = -3; n < ((FK_X & 16) ? 8 : 24); n++) {
          if (n < ((FK_X & 16) ? 5 : 21) && elect_one()) {
            mbar_expect_tx(mf + (n & 3) * 8, 4096);
            tma_2d(ring + (n & 3) * 4096, &prm.wm, ((n + 3) >> 3) * 2048 + cgrp * 256, t * 64 + ((n + 3) & 7) * 8, mf + (n & 3) * 8, pol<1>());
          }
          if (n < 0) continue;
          const uint32_t sl = ring + ((n + 1) & 3) * 4096 + lane * 16;
          const float4 sv0 = lds128(stab + (n & 7) * 32), sv1 = lds128(stab + (n & 7) * 32 + 16);
          const float sc[8] = {sv0.x, sv0.y, sv0.z, sv0.w, sv1.x, sv1.y, sv1.z, sv1.w};
          mbar_wait(mf + ((n + 1) & 3) * 8, ((n + 1) >> 2) & 1);
          uint4 v[8];
#pragma unroll
          for (int u = 0; u < 8; u++) v[u] = lds128u(sl + u * 512);
#pragma unroll
          for (int u = 0; u < 8; u++) {
            acc[0] = fmaf(sc[u], bf_lo(v[u].x), acc[0]); acc[1] = fmaf(sc[u], bf_hi(v[u].x), acc[1]);
            acc[2] = fmaf(sc[u], bf_lo(v[u].y), acc[2]); acc[3] = fmaf(sc[u], bf_hi(v[u].y), acc[3]);
            acc[4] = fmaf(sc[u], bf_lo(v[u].z), acc[4]); acc[5] = fmaf(sc[u], bf_hi(v[u].z), acc[5]);
            acc[6] = fmaf(sc[u], bf_lo(v[u].w), acc[6]); acc[7] = fmaf(sc[u], bf_hi(v[u].w), acc[7]);
          }
          asm volatile("" : "+f"(acc[0]) :: "memory");
          if ((n & 7) == 7) {
            sts128(stg + lane * 32, acc[0], acc[1], acc[2], acc[3]); sts128(stg + lane * 32 + 16, acc[4], acc[5], acc[6], acc[7]);
#pragma unroll
            for (int i = 0; i < 8; i++) acc[i] = 0.f;
            fence_async_smem();
            if (elect_one()) {
              asm volatile("cp.reduce.async.bulk.global.shared::cta.bulk_group.add.f32 [%0], [%1], 1024;" ::"l"(mod + (n >> 3) * 2048 + cgrp * 256), "r"(stg) : "memory");
              bulk_commit();
              if (n != 15) { bulk_wait<0>(); rel_fence<2>(); red_add(&S->cntMod[n > 7 ? 32 : 0], 1); } else bulk_wait_read<0>();
              TRACE(n > 7 ? 34 + (n >> 3) : 9);
            }
          }
        }
      } else {
        wait_cnt(S->cntMod, tag * 128u);
        if (lane == 0) TRACE(10);
        float4 sa[8];
        {
          const float4 c0 = ldg_cg(mod + D_ + m4 * 256 + lane * 8), c1 = ldg_cg(mod + D_ + m4 * 256 + lane * 8 + 4);
#pragma unroll
          for (int i = 0; i < 8; i++) {
            const float4 sv = ldg_cg(mod + (i >> 1) * 256 + lane * 8 + (i & 1) * 4);
            const uint32_t s0 = pack_bf16(sv.x, sv.y), s1 = pack_bf16(sv.z, sv.w);
            sa[i] = make_float4(bf_lo(s0), bf_hi(s0), bf_lo(s1), bf_hi(s1));
          }
          const uint32_t cw[4] = {pack_bf16(c0.x, c0.y), pack_bf16(c0.z, c0.w), pack_bf16(c1.x, c1.y), pack_bf16(c1.z, c1.w)};
#pragma unroll
          for (int q = 0; q < 4; q++) sts32v(sb + T1_OFF + (lane >> 2) * 64 + q * 16 + (lane & 3) * 4, add_bf16x2(cw[q], 0x3F803F80u) ^ (j ? 0x80008000u : 0u));
        }
        float ul = 0.f;
#pragma unroll 1
        for (int r = 0; r < 8; r++) {
          if (r < 6 && elect_one()) {
            mbar_expect_tx(mf + ((nc + 2) & 3) * 8, 4096);
            bulk_load(ring + ((nc + 3) & 3) * 4096, src + (r + 2) * 2 * D_, 4096, mf + ((nc + 2) & 3) * 8, pol<2>());
          }
          mbar_wait(mf + (nc & 3) * 8, (nc >> 2) & 1); nc++;
          uint4 v[8];
          float u[4] = {0.f, 0.f, 0.f, 0.f};
#pragma unroll
          for (int i = 0; i < 8; i++) v[i] = lds128u(ring + (nc & 3) * 4096 + lane * 16 + i * 512);
#pragma unroll
          for (int i = 0; i < 8; i++) {
            const float4 s0 = sa[2 * (i & 3)], s1 = sa[2 * (i & 3) + 1];
            float &u0 = u[(i >> 2) * 2], &u1 = u[(i >> 2) * 2 + 1];
            u0 = fmaf(bf_lo(v[i].x), s0.x, u0); u1 = fmaf(bf_hi(v[i].x), s0.y, u1); u0 = fmaf(bf_lo(v[i].y), s0.z, u0); u1 = fmaf(bf_hi(v[i].y), s0.w, u1);
            u0 = fmaf(bf_lo(v[i].z), s1.x, u0); u1 = fmaf(bf_hi(v[i].z), s1.y, u1); u0 = fmaf(bf_lo(v[i].w), s1.z, u0); u1 = fmaf(bf_hi(v[i].w), s1.w, u1);
          }
          const float ua = u[0] + u[1], ub = u[2] + u[3];
          float us = ((lane & 1) ? ub : ua) + __shfl_xor_sync(~0u, (lane & 1) ? ua : ub, 1);
#pragma unroll
          for (int o = 16; o > 1; o >>= 1) us += __shfl_xor_sync(~0u, us, o);
          if ((lane >> 1) == r) ul = jw ? -us : us;
        }
        if (lane < 16) st_msg8(&S->u[jw * D_ + e0 + lane], __float_as_uint(ul), tag);
        if (lane == 0) TRACE(11);
#pragma unroll
        for (int i = 0; i < 4; i++) sts128u(ring + lane * 16 + i * 512, SENT, SENT, SENT, SENT);
        fence_async_smem();
        if (elect_one()) {
#pragma unroll 1
          for (int i = 0; i < 9; i++)
            bulk_store(i < 4 ? &S->part[b * 512 + i * 128] : i == 4 ? &S->stats[b * 128] : &S->rowsH[((i - 5) >> 1) * 4096 + (t * 2 + (i & 1)) * 128 + cgrp * 16], ring, i < 5 ? 2048 : 256);
          bulk_store(&S->flagP[b * 32], ring, 128);
          bulk_commit(); bulk_wait<0>();
        }
        if (lane == 12) S->claim[cl * 8] = 0;
        if (lane < 12) reinterpret_cast<float4*>(S->mod[~tag & 1] + b * 48)[lane] = make_float4(0.f, 0.f, 0.f, 0.f);
      }
      named_bar<1, 64>();
    }
    asm volatile("setmaxnreg.dec.sync.aligned.u32 40;" ::: "memory");
    if (warp == 2) {
      if (elect_one()) { rel_fence<4>(); mbar_arrive(BAR(B_RSDONE)); TRACE(30); }
      const int scl = blk_src(lane, cgrp);
      const unsigned* flagAddr = &S->flagP[(t * 8 + (scl >> 2)) * 32 + (scl & 3)];
      const unsigned* cellAddr = &S->flagP[(t * 8 + (lane & 7)) * 32];
      sts32v(sb + PFLAG_OFF + lane * 4, tag - 1);
      if (lane < 4) mbar_arrive(BAR(B_FULL2 + lane));
      mbar_wait(BAR(B_PREADY), 0);
      unsigned ready = 15;
      int u = 4, i7 = 0, kk = 0; uint32_t ph = 1;
#pragma unroll 1
      for (int q = 4; q < 32; q++) {
        const int src = FK_SKIP ? i7 + (i7 >= cgrp) : i7 == cgrp ? 7 : i7;
        if (!((ready >> q) & 1)) {
          unsigned v;
          asm volatile("ld.volatile.shared.u32 %0, [%1];" : "=r"(v) : "r"(sb + PFLAG_OFF + scl * 4) : "memory");
          ready |= __ballot_sync(~0u, v == tag);
          int it = 0;
          while (!((ready >> q) & 1)) {
            ready |= __ballot_sync(~0u, (unsigned)(lane - q) < 7u && ld_rlx(flagAddr) == tag);
            SPIN_CHECK(it);
          }
          fence_async_global();
        }
        if ((q & ~4) == 8) mbar_wait(BAR(B_PS - 2 + (q >> 2)), 0);
        mbar_wait(BAR(q >= 8 ? B_EMPTY2 + u : q == 4 ? B_EMPTY + 2 : B_FULL2 + u), ph);
        if (q >= 8) grid_wait();
        if (elect_one()) {
          TRACE3(128 + q);
          mbar_expect_tx(BAR(B_FULL2 + u), SLOT);
          tma_2d(sb + buf_off(u), &prm.p, (src >> 1) * 256 + kk * 64, (src & 1) * S_ + t * 128, BAR(B_FULL2 + u), pol<5>());
        }
        if (((~ready >> q) & 15) && lane < 8)
          asm volatile("cp.async.cg.shared.global [%0], [%1], 16;" ::"r"(sb + PFLAG_OFF + lane * 16), "l"(cellAddr) : "memory");
        if (++u == 5) { u = 0; ph ^= 1; }
        if (++i7 == 7) { i7 = 0; kk++; }
      }
      asm volatile("cp.async.wait_all;" ::: "memory");
    }
    asm volatile("" ::: "memory");
    if (warp == 0) {
      int u = 0; uint32_t ph = 1;
#pragma unroll 1
      for (int q = 0; q < 32; q++) {
        const int sc = blk_src(q, cgrp);
        mbar_wait(BAR(q >= 5 ? B_EMPTY2 + u : q < 2 ? B_ADONE : q == 4 ? B_EMPTY + 3 : B_EMPTY + 1), q >= 2 ? ph : 0);
        if (elect_one()) {
          TRACE3(160 + q);
          mbar_expect_tx(BAR(B_FULL2 + u), SLOT);
          tma_2d_mc(sb + buf_off(u) + SLOT + rank * 8192, &prm.wd[(sc >> 2) & 1], (sc >> 3) * 256 + (sc & 3) * 64, cgrp * 128 + rank * 64, BAR(B_FULL2 + u), pol<6>());
          if (q & 1) { const int p = 4 + FK_NA + FK_NP + ((q - FK_QP) >> 1); if (q >= FK_QP && p < (FK_TD ? 16 : 24)) prefetch_piece(p);
            else if (FK_TD == 3 && moe && p >= 16 && p < 24) {
              asm volatile("mbarrier.expect_tx.relaxed.cta.shared::cta.b64 [%0], 512;" ::"r"(BAR(B_B27)) : "memory");
              tma_3d(sb + KEY_OFF, &prm.tch[0], p - 16, eb * 32, BAR(B_B27), POL_NORMAL);
            } }
          else if (q >= 10 && q < 2 * FK_NL + 2) weight_box((q >> 1) - 1, BAR(B_FULL2 + (u == 4 ? 0 : u + 1)));
        }
        if (++u == 5) { u = 0; ph ^= 1; }
      }
      if (elect_one()) {
#pragma unroll 1
        for (int n = FK_NL; n < 15; n++) weight_box(n, BAR(B_WF));
        mbar_expect_tx(BAR(B_DN), moe ? 65536 : 0);
#pragma unroll 1
        for (int i = 0; i < 9; i++) {
          if ((i & 3) == 0) mbar_wait(BAR(B_EMPTY2 + 2 + (i >> 2)), 1);
          if (i == 0) { mbar_arrive(BAR(B_B27)); weight_box(15, BAR(B_WF)); mbar_arrive(BAR(B_WF)); }
          else if (moe)
            asm volatile("cp.async.bulk.tensor.5d.shared::cluster.global.mbarrier::complete_tx::bytes.L2::cache_hint [%0], [%1, {0, 0, 0, %3, %4}], [%2], %5;"
                         ::"r"(sb + RKA_OFF + (i + (i >> 3) * 4) * 8192), "l"(&prm.wdn), "r"(BAR(B_DN)), "r"(eb * 2), "r"(i * 2 - 2), "l"(pol<3>()) : "memory");
        }
      }
    }
    asm volatile("" ::: "memory");
    if (warp == 1) {
      if (elect_one()) {
#pragma unroll 1
        for (int kk = 0; kk < 4; kk++) {
          mbar_wait(BAR(B_PREADY + kk), 0);
#pragma unroll 1
          for (int i = 0; i < 4; i++) {
            tma_store_2d(&prm.ps, sb + pstage(kk) + i * 4096, m4 * 256 + kk * 64, j * S_ + t * 128 + i * 32);
            if (kk >= FK_PS0 && i < 3) { const unsigned next = clk32() + FK_PSPACE; while ((int)(clk32() - next) < 0) __nanosleep(20); }
          }
          bulk_commit(); bulk_wait<0>();
          if (kk < 2) mbar_arrive(BAR(B_PS + kk));
          rel_fence<3>();
          st_rlx(&S->flagP[b * 32 + kk], tag);
          TRACE(40 + kk); TRACE3(128 + kk);
        }
        prefetch_tmap(&prm.om);
        if (FK_XD) { const unsigned next = clk32() + FK_XD; while ((int)(clk32() - next) < 0) __nanosleep(20); }
        mbar_expect_tx(BAR(B_EFULL), (FK_X & 4) ? 0 : 32768);
#pragma unroll 1
        for (int i = 0; i < 8; i++) {
          if (!(FK_X & 4)) tma_3d(sb + E_OFF + i * 4096, &prm.xm, t * 128 + i * 16, cgrp * 2, BAR(B_EFULL), pol<8>());
          const unsigned next = clk32() + FK_SPACE;
          while ((int)(clk32() - next) < 0) __nanosleep(20);
        }
      }
      __syncwarp();
    }
    asm volatile("" ::: "memory");
    if (warp == 3) {
      if (elect_one()) {
        fence_async_smem();
        unsigned next = clk32();
#pragma unroll 1
        for (int n = 0; n < 4 + FK_NA + (FK_TD == 2) * 8; n++) {
          if (n < 4) weight_box(n, BAR(B_WF));
          else if (n < 4 + FK_NA) prefetch_piece(n + FK_NP);
          else if (moe) {
            asm volatile("mbarrier.expect_tx.relaxed.cta.shared::cta.b64 [%0], 512;" ::"r"(BAR(B_TAB)) : "memory");
            tma_3d(sb + KEY_OFF, &prm.tch[0], n - 4 - FK_NA, eb * 32, BAR(B_TAB), POL_NORMAL);
          }
          if (n == 3) mbar_arrive(BAR(B_WF));
          if (!FK_TX && (unsigned)(n - FK_XN) < 4u) pf_bulk(x + (size_t)(b * 16 + (n - FK_XN) * 4) * D_, 8192);
          next += FK_PACE;
          while ((int)(clk32() - next) < 0) __nanosleep(20);
        }
        TRACE(37);
      }
      __syncwarp();
      int it = 0;
      if (!(FK_X & 16)) wait_cnt(&S->cntMod[32], tag * 128u);
      mbar_wait(BAR(B_PREADY + 2), 0);
      {
        const float* mp = S->mod[tag & 1] + cgrp * 128 + lane * 4;
        const float4 ga = ldg_cg(mp + 2 * D_), sv = ldg_cg(mp + 3 * D_), cb = ldg_cg(mp + 4 * D_), gb = ldg_cg(mp + 5 * D_);
        const uint2 wr = __ldg(reinterpret_cast<const uint2*>(prm.w_r + cgrp * 128 + lane * 4));
        const uint32_t Aa = add_bf16x2(pack_bf16(cb.x, cb.y), 0x3F803F80u), Ab = add_bf16x2(pack_bf16(cb.z, cb.w), 0x3F803F80u);
        const uint32_t Sa = pack_bf16(sv.x, sv.y), Sb = pack_bf16(sv.z, sv.w), Ga = pack_bf16(gb.x, gb.y), Gb = pack_bf16(gb.z, gb.w);
        const float w0 = bf_lo(Aa) * bf_lo(wr.x), w1 = bf_hi(Aa) * bf_hi(wr.x), w2 = bf_lo(Ab) * bf_lo(wr.y), w3 = bf_hi(Ab) * bf_hi(wr.y);
        const uint32_t tb = sb + TAB_OFF + (lane >> 3) * 64 + (lane & 1) * 32 + ((lane >> 1) & 3) * 4, Wa = pack_bf16(w0, w1), Wb = pack_bf16(w2, w3);
        auto put = [&](int off, uint32_t a, uint32_t c) { sts32v(tb + off, a); sts32v(tb + off + 16, c); };
        put(T_WH, Wa, Wb); put(T_ONE, 0x3F803F80u, 0x3F803F80u);
        put(T_WL, pack_bf16(w0 - bf_lo(Wa), w1 - bf_hi(Wa)), pack_bf16(w2 - bf_lo(Wb), w3 - bf_hi(Wb)));
        put(T_GA, pack_bf16(ga.x, ga.y), pack_bf16(ga.z, ga.w)); put(T_A, Aa, Ab); put(T_S, Sa, Sb); put(T_G, Ga, Gb);
        float c1 = (w0 + w1) + (w2 + w3), c2 = (bf_lo(Sa) * bf_lo(wr.x) + bf_hi(Sa) * bf_hi(wr.x)) + (bf_lo(Sb) * bf_lo(wr.y) + bf_hi(Sb) * bf_hi(wr.y));
#pragma unroll 1
        for (int h = 0; h < 2; h++) {
#pragma unroll
          for (int o = 16; o; o >>= 1) { c1 += __shfl_xor_sync(~0u, c1, o); c2 += __shfl_xor_sync(~0u, c2, o); }
          if (h) break;
          if (t == 0 && lane == 0) st_msg(&S->cst[cgrp], __float_as_uint(c1), __float_as_uint(c2), tag, 0);
          uint4 cm; it = 0;
          while (true) {
            cm = ld_msg(&S->cst[lane & 7]);
            if (__all_sync(~0u, cm.z == tag)) break;
            SPIN_CHECK(it); __nanosleep(200);
          }
          c1 = 0.25f * __uint_as_float(cm.x); c2 = 0.25f * __uint_as_float(cm.y);
        }
        if (lane == 0) { sts128u(sb + CST_OFF, __float_as_uint(c1), __float_as_uint(c2), tag, b | eb << 8 | (int)moe << 16); TRACE(27); }
      }
    }
    asm volatile("" ::: "memory");
    if (warp & 1) {
      const uint2* src = (warp == 3 ? &S->u[cgrp * 128] : &S->rs[t * 128]) + lane;
      const uint2* src1 = src + (warp == 3 ? D_ : S_);
      uint2 m[8]; int it = 0;
      while (true) {
        bool ok = true;
#pragma unroll
        for (int i = 0; i < 8; i++) { m[i] = ld_msg8(((i & 1) ? src1 : src) + (i >> 1) * 32); ok &= m[i].y == tag; }
        if (__all_sync(~0u, ok)) break;
        SPIN_CHECK(it);
      }
      uint32_t rk[12];
#pragma unroll
      for (int i = 0; i < 4; i++) {
        const float r0 = __uint_as_float(m[2 * i].x) * (warp == 3 ? 0.5f : 1.f), r1 = __uint_as_float(m[2 * i + 1].x) * (warp == 3 ? 0.5f : 1.f);
        const uint32_t hi = pack_bf16(r0, r1), lo = pack_bf16(r0 - bf_lo(hi), r1 - bf_hi(hi));
        rk[3 * i] = hi; rk[3 * i + 1] = warp == 3 ? hi : lo; rk[3 * i + 2] = warp == 3 ? lo : hi;
      }
      mbar_wait(BAR(B_B27), 0);
#pragma unroll
      for (int i = 0; i < 4; i++) sts128u(sb + RKA_OFF + (warp & 2) * 1024 + (i * 32 + lane) * 16, rk[3 * i], rk[3 * i + 1], rk[3 * i + 2], 0);
      fence_async_smem();
      if (elect_one()) { mbar_arrive(BAR(B_TAB)); TRACE(26); }
    }
    asm volatile("" ::: "memory");
    if (warp == 1) {
      mbar_wait(BAR(B_PREADY), 1);
      if (lane == 0) TRACE(60);
      const int lr = lds32u(sb + BK_OFF + (lane >> 4) * 4);
      {
        const uint4 v = lds128u(sb + E_OFF + (lr >> 4) * 4096 + (lane & 8) * 256 + (lr & 15) * 128 + (((lane ^ lr) & 7) << 4));
        st_msg(&S->rowsB[(t * 2 + (lane >> 4)) * 128 + cgrp * 16 + (lane & 15)], v.x, v.y, v.z, v.w);
      }
      const unsigned cmask = __reduce_or_sync(~0u, 1u << (lr >> 4)) | FK_OMASK;
      unsigned todo = ~cmask & 255, smask = 0;
      int r1 = 0, r2 = 0;
#pragma unroll 1
      for (int h = 0; h < 2; h++) {
        if (elect_one()) {
#pragma unroll 1
          for (; todo; todo &= todo - 1) {
            const int i = __ffs(todo) - 1;
            asm volatile("cp.async.bulk.tensor.3d.global.shared::cta.bulk_group.L2::cache_hint [%0, {0, %2, %3}], [%1], %4;"
                         ::"l"(&prm.om), "r"(sb + E_OFF + i * 4096), "r"(t * 128 + i * 16), "r"(cgrp * 2), "l"(pol<9>()) : "memory");
            if (FK_OSPACE && (h == 0 || FK_OSPACE2)) spin(h ? FK_OSPACE2 : FK_OSPACE);
          }
          TRACE(61 + h);
        }
        if (h) break;
        mbar_wait(BAR(B_SEL), 0);
        r1 = lds32u(sb + SEL_OFF) - t * 128; r2 = lds32u(sb + SEL_OFF + 4) - t * 128;
        smask = ((unsigned)r1 < 128u ? 1u << (r1 >> 4) : 0) | ((unsigned)r2 < 128u ? 1u << (r2 >> 4) : 0);
        todo = cmask & ~smask;
        if (FK_ODELAY) spin(FK_ODELAY);
      }
#pragma unroll 1
      for (; smask; smask &= smask - 1) {
        const int i = __ffs(smask) - 1;
#pragma unroll 2
        for (int r = lane >> 4; r < 16; r += 2) {
          const uint4 v = lds128u(sb + E_OFF + i * 4096 + (lane & 8) * 256 + r * 128 + (((lane ^ r) & 7) << 4));
          if (i * 16 + r != r1 && i * 16 + r != r2) reinterpret_cast<uint4*>(out + (size_t)(t * 128 + i * 16 + r) * D_)[cgrp * 16 + (lane & 15)] = v;
        }
      }
      if (elect_one()) { bulk_commit(); bulk_wait_read<0>(); TRACE(29); }
    }
    asm volatile("" ::: "memory");
    if (warp == 2) {
      const uint4* cp = &S->cand[(lane >> 1) * 8];
      mbar_wait(BAR(B_B27), 0);
      uint4 m = ld_msg(cp);
      bool ok = __all_sync(~0u, m.z == tag);
      named_bar<5, 288>();
      uint32_t k1, k2;
      {
        const uint4 k4 = lds128u(sb + KEY_OFF + lane * 16);
        const uint32_t ka = max(k4.x, k4.y), kb = max(k4.z, k4.w), m1 = max(ka, kb), m2 = max(min(ka, kb), ka > kb ? min(k4.x, k4.y) : min(k4.z, k4.w));
        k1 = redux_max(m1); k2 = redux_max(m1 == k1 ? m2 : m1);
        if (lane == 0) { st_msg(&S->cand[t * 8], k1, k2, tag, 0); sts64u(sb + BK_OFF, key_row(k1) & 127, key_row(k2) & 127); mbar_arrive(BAR(B_BK)); TRACE(13); }
      }
      int it = 0;
      while (!ok) {
        m = ld_msg(cp);
        ok = __all_sync(~0u, m.z == tag);
        SPIN_CHECK(it);
      }
      warp_top2((lane & 1) ? m.y : m.x, k1, k2);
      const int r1 = key_row(k1), r2 = key_row(k2), slot1 = (r1 >> 7) * 2, slot2 = (r2 >> 7) * 2 + ((r1 >> 7) == (r2 >> 7));
      if (lane == 0) { sts64u(sb + SEL_OFF, r1, r2); sts64u(sb + SEL_OFF + 8, slot1 * 2048, slot2 * 2048); mbar_arrive(BAR(B_SEL)); TRACE(14); }
      const int fcol = (b >> 1) * 16 + (lane & 15);
      const float gb = round_bf16(__uint_as_float(ld_rlx(S->mod[tag & 1] + 5 * D_ + fcol)));
      const uint32_t* fbp = reinterpret_cast<const uint32_t*>(&S->rowsB[((b & 1) ? slot2 : slot1) * 128]) + (fcol >> 1);
      uint32_t fb;
      do { fb = ld_rlx(fbp); SPIN_CHECK(it); } while (fb == SENT);
      sts64u(sb + PFLAG_OFF + (lane & 15) * 8, (lane & 1) ? fb & 0xFFFF0000u : fb << 16, __float_as_uint(gb));
      __syncwarp();
      if (lane == 0) {
        sts32(sb + CST_OFF, round_bf16(sigmoid_f(round_bf16(fkey_inv((((b & 1) ? k2 : k1) & ~2047u) | 1024u)))));
        mbar_arrive(BAR(B_FIN));
        if (b == 0) S->epoch[0] = tag;
      }
    }
  } else {
    const int cw = (warp - 4) >> 2;
    const int cwarp = warp - 4;
    const bool elect = (tid & 127) == 0;
    uint32_t rel;
    asm volatile("mapa.shared::cluster.u32 %0, %1, %2;" : "=r"(rel) : "r"(BAR(0)), "r"(tid & 1));
    if (tid & 126) rel = 0;
    asm volatile("" : "+r"(rel));
    auto release = [&](int bar) {
      asm volatile("{\n.reg .pred p;\nsetp.ne.u32 p, %1, 0;\n@p mbarrier.arrive.shared::cluster.b64 _, [%0];\n}" ::"r"(rel + bar * 8), "r"(rel) : "memory");
    };
    const uint32_t da0 = desc_lo(sb + cw * 8192, 16), db0 = desc_lo(sb + SLOT, 8192), db2 = desc_lo(sb + SLOT, 16);

    uint32_t wf[64], uf[64], df[64];
    uint32_t pk[64];
    uint32_t xw[32];
    float lo[64];
    int ln;
    uint32_t so, wo;
    auto p_ready = [&](int kk) { fence_async_smem(); if (elect_one()) mbar_arrive(BAR(B_PREADY + kk)); };
    {
      float pa[64], pb[64];
      {
        float acc[128];
#pragma unroll 1
        for (int g = 0; g < 28; g++) {
          const int s = g & 3;
          mbar_wait(BAR(B_FULL + s), (g >> 2) & 1);
          const uint32_t da = da0 + s * (STAGE >> 4), db = db0 + s * (STAGE >> 4);
          wg_fence();
          wgmma_n256<1>(acc, da, db, g > 0);
#pragma unroll
          for (int k = 1; k < 4; k++) wgmma_n256<1>(acc, da + k * 2, db + k * 128, 1);
          wg_commit();
          wg_wait<1>();
          if (g > 0) { release(B_EMPTY + ((g - 1) & 3)); if (elect) TRACE2(191 + g + cw * 32); }
          STAMP2(g);
        }
        wg_wait<0>();
        release(B_EMPTY + 3);
#pragma unroll
        for (int i = 0; i < 64; i++) {
          asm volatile("mov.b32 %0, %1;" : "=f"(pa[i]) : "f"(acc[i]));
          asm volatile("mov.b32 %0, %1;" : "=f"(pb[i]) : "f"(acc[64 + i]));
        }
      }
      if (elect) TRACE(3 + tr);
      STAMP2(28);
#pragma unroll 1
      for (int s = 0; s < 4; s++) {
        mbar_wait(BAR(B_FULL + s), 1);
        wg_fence();
#pragma unroll
        for (int k = 0; k < 4; k++) wgmma_n128<1>(pa, da0 + s * (STAGE >> 4) + k * 2, db0 + s * (STAGE >> 4) + k * 128);
        wg_commit();
        if (s == 2) { wg_wait<1>(); if (elect) mbar_arrive(BAR(B_A29)); }
      }
      auto b_block = [&](int s) {
        wg_fence();
#pragma unroll
        for (int k = 0; k < 4; k++) wgmma_n128<1>(pb, da0 + s * (STAGE >> 4) + k * 2, db0 + s * (STAGE >> 4) + 1024 + k * 128);
        wg_commit();
      };
      uint4 t0, t1;
      auto load_t = [&](int kk) { t0 = lds128u(sb + T1_OFF + kk * 128 + (ln & 3) * 16); t1 = lds128u(sb + T1_OFF + kk * 128 + 64 + (ln & 3) * 16); };
      auto pack_p = [&](int kk, const float* a) {
        const uint32_t A[8] = {t0.x, t0.y, t0.z, t0.w, t1.x, t1.y, t1.z, t1.w};
#pragma unroll
        for (int i = 0; i < 16; i++) pk[kk * 16 + i] = mul_bf16x2(pack_bf16(a[2 * i], a[2 * i + 1]), A[i >> 1]);
      };
      auto stage_p = [&](int kk) {
#pragma unroll
        for (int k = 0; k < 4; k++) stsm_x4((so ^ (k << 5)) + pstage(kk), pk + kk * 16 + k * 4);
      };
      auto own_block = [&](int q) {
        const uint32_t db = db2 + (buf_off(q) >> 4);
        wg_fence();
        if (q == 0) wgmma_n128_rs<0>(lo, pk, db); else wgmma_n128_rs<1>(lo, pk + q * 16, db);
#pragma unroll
        for (int k = 1; k < 4; k++) wgmma_n128_rs<1>(lo, pk + q * 16 + k * 4, db + k * 2);
        wg_commit();
      };
      b_block(0);
      mbar_wait(BAR(B_RSDONE), 0);
      asm volatile("setmaxnreg.inc.sync.aligned.u32 232;" ::: "memory");
      asm volatile("mov.u32 %0, %%laneid;" : "=r"(ln));
      so = sb + (uint32_t)(cwarp * 16 + (ln & 15)) * 128 + (((ln >> 4) ^ (ln & 7)) << 4);
      wo = sb + SP_OFF + cwarp * 1024 + ((ln & 7) + (ln >> 4) * 8) * 64 + ((((ln >> 3) & 1) ^ ((ln >> 1) & 3)) << 4);
      mbar_wait(BAR(B_A29), 0);
      load_t(0);
      wg_wait<1>();
      reg_fence(pa);
      release(B_ADONE);
      if (elect) TRACE(4 + tr);
      STAMP2(29);
      pack_p(0, pa); stage_p(0);
      if (FK_TR0) { p_ready(0); b_block(1); } else { b_block(1); p_ready(0); }
      if (elect) TRACE(2 + tr);
      wg_wait<1>(); release(B_EMPTY);
      load_t(1);
      b_block(2);
      pack_p(1, pa + 32);
      wg_wait<1>(); release(B_EMPTY + 1);
      STAMP2(30);
      load_t(2);
      b_block(3);
      mbar_wait(BAR(B_FULL2), 0);
      wg_wait<1>(); release(B_EMPTY + 2);
      if (FK_S1 == 0) { mbar_wait(BAR(B_ADONE), 0); stage_p(1); }
      own_block(0);
      if (FK_S1 == 0) p_ready(1);
      mbar_wait(BAR(B_FULL2 + 1), 0);
      if (FK_S1 == 1) mbar_wait(BAR(B_ADONE), 0);
      wg_wait<1>(); release(B_EMPTY + 3);
      reg_fence(pb);
      if (elect) TRACE(1 + tr);
      STAMP2(31);
      if (FK_S1 == 1) stage_p(1);
      own_block(1);
      if (FK_S1 == 1) p_ready(1);
      pack_p(2, pb);
      mbar_wait(BAR(B_FULL2 + 2), 0);
      wg_wait<1>(); release(B_EMPTY2);
      STAMP2(32);
      load_t(3);
      own_block(2);
      pack_p(3, pb + 32);
      mbar_wait(BAR(B_EMPTY + 3), 1);
      mbar_wait(BAR(B_FULL2 + 3), 0);
      wg_wait<1>(); release(B_EMPTY2 + 1);
      STAMP2(33);
      if (FK_S1 == 3) stage_p(1);
      own_block(3);
      if (FK_S1 == 3) p_ready(1);
      mbar_wait(BAR(B_WF), 0);
      wg_wait<1>(); release(B_EMPTY2 + 2);
      STAMP2(34);
    }
    {
      mbar_wait(BAR(B_FULL2 + 4), 0);
#pragma unroll
      for (int q = 4; q < 32; q++) {
        const uint32_t da = da0 + (buf_off(q % 5) >> 4) + (q << 16), db = db2 + (buf_off(q % 5) >> 4) + (q << 16);
        wg_fence();
#pragma unroll
        for (int k = 0; k < 4; k++) wgmma_n128<0>(lo, da + k * 2, db + k * 2);
        if (q == FK_QR) wgmma_n128<0, 8>(lo, desc_lo(sb + RKA_OFF, 0) + (cwarp & 4) * 16, desc_lo(sb + RKB_OFF, 0));
        wg_commit();
        if (q == 31) break;
        if (q + 1 == FK_QR) mbar_wait(BAR(B_TAB), 0);
        if (FK_ORD == 1) { wg_wait<1>(); if (q == 28 && rel) rel = BAR(0); release(B_EMPTY2 + (q - 1) % 5); STAMP2(31 + q); }
        if (q == 8 || q == 14) p_ready(q >> 2);
        if (q == 27) mbar_wait(BAR(B_EFULL), 0);
        mbar_wait(BAR(B_FULL2 + (q + 1) % 5), ((q + 1) / 5) & 1);
        if (q >= 27) {
#pragma unroll
          for (int h = 0; h < 2; h++) ldsm_x4((so ^ ((q - 27) << 5)) + E_OFF + cwarp * 2048 + h * 2048, xw + (q - 27) * 4 + h * 16);
        } else if (!(q & 1)) {
          const int n = (q - 4) >> 1;
#pragma unroll
          for (int h = 0; h < 2; h++) ldsm_x4_t((wo ^ (h << 5)) + (n & 3) * 8192, (n < 8 ? wf + n * 8 : uf + (n - 8) * 8) + h * 4);
        } else if (q < 15 && q != 9) {
          const int i = (q - 5 - (q > 9) * 2) >> 1;
#pragma unroll
          for (int h = 0; h < 2; h++) stsm_x4((so ^ (((i & 1) * 2 + h) << 5)) + pstage(2 + (i >> 1)), pk + 32 + i * 8 + h * 4);
        }
        if (FK_ORD == 0) { wg_wait<1>(); if (q == 28 && rel) rel = BAR(0); release(B_EMPTY2 + (q - 1) % 5); STAMP2(31 + q); }
      }
    }
    if (FK_QR == 32) {
      mbar_wait(BAR(B_TAB), 0);
      wg_fence();
      wgmma_n128<0, 8>(lo, desc_lo(sb + RKA_OFF, 0) + (cwarp & 4) * 16, desc_lo(sb + RKB_OFF, 0));
      wg_commit();
    }
    const int gq = ln >> 2, q4 = ln & 3, row0 = cwarp * 16 + gq;
    const bool odd = ln & 1;
    const uint32_t role = lds32u(sb + CST_OFF + 12), bq = role & 255;
    uint32_t tq = sb + TAB_OFF + q4 * 16, tb = tq + (gq & 1) * T_ONE + (gq & 2) * (T_WL / 2);
    const uint4* src = &S->stats[((bq & ~7) + (q4 >> 1) * 4) * 128 + row0 + 8 * (q4 & 1)];
    uint4* sdst = &S->stats[bq * 128 + row0 + 8 * q4];
    asm volatile("" : "+r"(tq), "+r"(tb), "+l"(src), "+l"(sdst));
    {
      uint4 gw[4];
#pragma unroll
      for (int a = 0; a < 4; a++) gw[a] = lds128u(tq + T_GA + a * 64);
      wg_wait<0>();
      reg_fence(lo);
      STAMP(0);
      if (elect) { TRACE(7 + tr); if (cw == 0) TRACE_CLK(121); }
      float c[2][4], e0[2][4], e1[2][4];
#pragma unroll
      for (int i = 0; i < 4; i++) c[0][i] = c[1][i] = e0[0][i] = e0[1][i] = e1[0][i] = e1[1][i] = 0.f;
#pragma unroll
      for (int a = 0; a < 4; a++) {
        const uint4 bw = lds128u(tb + a * 64);
        const uint32_t g[4] = {gw[a].x, gw[a].y, gw[a].z, gw[a].w};
#pragma unroll
        for (int i = 0; i < 8; i++) xw[a * 8 + i] = fma_bf16x2(g[i >> 1], pack_bf16(lo[a * 16 + 2 * i], lo[a * 16 + 2 * i + 1]), xw[a * 8 + i]);
#pragma unroll
        for (int h = 0; h < 2; h++) {
          const uint32_t* w = xw + a * 8 + h * 4;
          mma_1688(e0[0], w[0], w[1], w[0]); mma_1688(e1[0], w[0], w[1], w[1]); mma_1688(e0[1], w[2], w[3], w[2]); mma_1688(e1[1], w[2], w[3], w[3]);
          mma_16816(c[h], w, h ? bw.z : bw.x, h ? bw.w : bw.y);
        }
      }
      const float c0 = c[0][0] + c[1][0], c2 = c[0][2] + c[1][2];
      const float q0 = (gq & 1) ? e0[0][1] + e0[1][1] : e0[0][0] + e0[1][0], q1 = (gq & 1) ? e1[0][3] + e1[1][3] : e1[0][2] + e1[1][2];
      const int dl = (ln & ~3) | (gq >> 1);
      const float da = (odd ? c2 : c0) + __shfl_xor_sync(~0u, odd ? c0 : c2, 1), s1 = __shfl_xor_sync(~0u, c[0][3] + c[1][3], 1);
      const float qa = __shfl_sync(~0u, q0, dl), qb = __shfl_sync(~0u, q1, dl);
      if (q4 < 2) st_msg(sdst, __float_as_uint(odd ? s1 : c[0][1] + c[1][1]), __float_as_uint(odd ? qb : qa), __float_as_uint(da), 0);
    }
    if (elect) TRACE(8 + tr);
    STAMP(1);
    {
      uint4 m[4], tA[4], tS[4];
      mbar_wait(BAR(B_WF), 1);
      if (FK_H1 == 0) {
#pragma unroll
        for (int i = 0; i < 4; i++) m[i] = ld_msg(src + 128 * i);
      }
      const float2 cst = lds64(sb + CST_OFF);
#pragma unroll
      for (int i = 0; i < 8; i++) ldsm_x4_t((wo ^ ((i & 1) << 5)) + (i >> 1) * 8192, uf + 32 + i * 4);
      if (FK_H1 != 1) {
#pragma unroll
        for (int a = 0; a < 4; a++) { tA[a] = lds128u(tq + T_A + a * 64); tS[a] = lds128u(tq + T_S + a * 64); }
      }
      uint32_t kaddr = sb + KEY_OFF + (row0 + 8 * (q4 & 1)) * 4, kidx = 2047 - ((bq >> 3) * 128 + row0 + 8 * (q4 & 1));
      asm volatile("" : "+r"(kaddr), "+r"(kidx));
      STAMP(2);
      if (FK_H1) {
        uint32_t one;
        asm volatile("ld.volatile.shared.u32 %0, [%1];" : "=r"(one) : "r"(sb + TAB_OFF + T_ONE) : "memory");
        src += one >> 31;
#pragma unroll
        for (int i = 0; i < 4; i++) m[i] = ld_msg(src + 128 * i);
      }
      {
        int it = 0;
        while (!__all_sync(~0u, (m[0].w | m[1].w | m[2].w | m[3].w) == 0)) {
#pragma unroll
          for (int i = 0; i < 4; i++) m[i] = ld_msg(src + 128 * i);
          SPIN_CHECK(it);
        }
      }
      STAMP(3);
      float sa = (__uint_as_float(m[0].x) + __uint_as_float(m[1].x)) + (__uint_as_float(m[2].x) + __uint_as_float(m[3].x));
      float qa = (__uint_as_float(m[0].y) + __uint_as_float(m[1].y)) + (__uint_as_float(m[2].y) + __uint_as_float(m[3].y));
      float da = (__uint_as_float(m[0].z) + __uint_as_float(m[1].z)) + (__uint_as_float(m[2].z) + __uint_as_float(m[3].z));
      sa += __shfl_xor_sync(~0u, sa, 2); qa += __shfl_xor_sync(~0u, qa, 2); da += __shfl_xor_sync(~0u, da, 2);
      const float mean = sa * (1.f / D_);
      const float rs = rsqrt_f(fmaxf(fmaf(-mean, mean, qa * (1.f / D_)), 0.f) + 1e-5f);
      sts32v(kaddr, (fkey(fmaf(rs, fmaf(-mean, cst.x, da), cst.y)) & ~2047u) | kidx);
      uint32_t one;
      asm volatile("bar.arrive 5, 288;\nld.volatile.shared.u32 %0, [%1];" : "=r"(one) : "r"(sb + TAB_OFF + T_ONE) : "memory");
      if (tid == 128) TRACE(12 + 16);
      STAMP(4);
      if (FK_H1 == 1) {
#pragma unroll
        for (int a = 0; a < 4; a++) { tA[a] = lds128u(tq + T_A + a * 64); tS[a] = lds128u(tq + T_S + a * 64); }
      }
      const uint32_t h0 = pack_bf16(rs, rs), l0 = mul_bf16x2(pack_bf16(rs - bf_lo(h0), -mean * rs), one), hx = __shfl_xor_sync(~0u, h0, 1), lx = __shfl_xor_sync(~0u, l0, 1);
      const uint32_t rh[2] = {odd ? hx : h0, odd ? h0 : hx};
      const uint32_t rl[2] = {__byte_perm(odd ? lx : l0, 0, 0x1010), __byte_perm(odd ? l0 : lx, 0, 0x1010)};
      const uint32_t nm[2] = {__byte_perm(odd ? lx : l0, 0, 0x3232), __byte_perm(odd ? l0 : lx, 0, 0x3232)};
      uint32_t h[32];
#pragma unroll
      for (int a = 0; a < 4; a++) {
        const uint32_t A[4] = {tA[a].x, tA[a].y, tA[a].z, tA[a].w}, B[4] = {tS[a].x, tS[a].y, tS[a].z, tS[a].w};
#pragma unroll
        for (int i = 0; i < 8; i++) {
          const uint32_t w = xw[a * 8 + (i & 3) * 2 + (i >> 2)];
          h[a * 8 + i] = fma_bf16x2(fma_bf16x2(w, rh[i >> 2], fma_bf16x2(w, rl[i >> 2], nm[i >> 2])), A[i & 3], B[i & 3]);
        }
      }
      uint4* cp = &S->rowsH[(bq >> 3) * 256 + (bq & 7) * 16 + q4];
#pragma unroll
      for (int i = 0; i < 32; i++) asm volatile("" : "+r"(h[i]));
      asm volatile("" : "+l"(cp));
      mbar_wait(BAR(B_BK), 0);
      STAMP(5);
      const float2 bk = lds64(sb + BK_OFF);
#pragma unroll
      for (int r = 0; r < 2; r++) {
        const bool second = row0 + 8 * r == __float_as_int(bk.y);
        if (second || row0 + 8 * r == __float_as_int(bk.x)) {
#pragma unroll
          for (int a = 0; a < 4; a++) st_msg(cp + (second ? 128 : 0) + a * 4, h[a * 8 + r * 4], h[a * 8 + r * 4 + 1], h[a * 8 + r * 4 + 2], h[a * 8 + r * 4 + 3]);
        }
      }
      mbar_wait(BAR(B_DN), 0);
#pragma unroll
      for (int a = 0; a < 4; a++) {
        const uint4 tG = lds128u(tq + T_G + a * 64);
        const uint32_t G[4] = {tG.x, tG.y, tG.z, tG.w};
#pragma unroll
        for (int i = 0; i < 8; i++) xw[a * 8 + i] = fma_bf16x2(G[i >> 1], h[a * 8 + (i & 1) * 4 + (i >> 1)], xw[a * 8 + i]);
#pragma unroll
        for (int k = 0; k < 2; k++) stsm_x4((so ^ ((((a & 1) * 2) + k) << 5)) + E_OFF + cwarp * 2048 + (a >> 1) * 2048, xw + a * 8 + k * 4);
      }
    }
    fence_async_smem();
    if (elect_one()) mbar_arrive(BAR(B_PREADY));
    STAMP(6);
    if (tid == 128) TRACE(15);
    if (role >> 16) {
      const char* hp = reinterpret_cast<const char*>(&S->rowsH[(cwarp >> 1) * 4 + q4]) + (cwarp & 1) * 8;
      uint32_t db = sb + DN_OFF + (cwarp + (cwarp == 7) * 4) * 8192 + ((ln & 7) + (ln >> 4) * 8) * 128 + ((((ln >> 3) & 1) ^ (ln & 7)) << 4), sa = sb + SEL_OFF + 8 + (gq & 1) * 4;
      asm volatile("" : "+l"(hp), "+r"(db), "+r"(sa));
      STAMP(7);
      mbar_wait(BAR(B_SEL), 0);
      STAMP(8);
      { const uint32_t off = lds32u(sa); hp += off; db += off >> 31; }
      uint2 hb[8];
#pragma unroll
      for (int i = 0; i < 8; i++) hb[i] = ld_msg8(hp + i * 256);
      STAMP(9);
#pragma unroll
      for (int i = 0; i < 16; i++) ldsm_x4_t((db ^ (((i >> 1) & 3) << 5)) + (i >> 3) * 4096 + (i & 1) * 2048, df + i * 4);
      int it = 0;
      while (!__all_sync(~0u, max(max(max(hb[0].x, hb[1].x), max(hb[2].x, hb[3].x)), max(max(hb[4].x, hb[5].x), max(hb[6].x, hb[7].x))) != SENT)) {
#pragma unroll
        for (int i = 0; i < 8; i++) hb[i] = ld_msg8(hp + i * 256);
        SPIN_CHECK(it);
      }
      if (tid == 128) TRACE(16);
      STAMP(10);
      float c[4][4];
#pragma unroll
      for (int i = 0; i < 4; i++) c[i][0] = c[i][1] = c[i][2] = c[i][3] = 0.f;
#pragma unroll
      for (int ks = 0; ks < 8; ks++) {
        const uint32_t b0 = hb[ks].x, b1 = hb[ks].y;
        mma_16816(c[0], wf + ks * 8, b0, b1); mma_16816(c[1], wf + ks * 8 + 4, b0, b1);
        mma_16816(c[2], uf + ks * 8, b0, b1); mma_16816(c[3], uf + ks * 8 + 4, b0, b1);
      }
      {
        float v[4];
#pragma unroll
        for (int i = 0; i < 4; i++) v[i] = (q4 & 2) ? (odd ? c[3][i] : c[2][i]) : (odd ? c[1][i] : c[0][i]);
        sts128(sb + RED_OFF + cwarp * 512 + (q4 * 8 + (gq ^ (q4 * 2))) * 16, v[0], v[2], v[1], v[3]);
      }
      uint2* pp = reinterpret_cast<uint2*>(&S->part[((cwarp * 16 + q4 * 2) * 128 + ((role >> 8) & 255)) * 4]) + gq;
      uint32_t ra = sb + RED_OFF + ((ln * 8) ^ ((ln & 16) * 2));
      asm volatile("" : "+l"(pp), "+r"(ra));
      STAMP(11);
      named_bar<2, 256>();
      STAMP(12);
      float g0 = 0.f, g1 = 0.f, u0 = 0.f, u1 = 0.f;
#pragma unroll
      for (int w = 0; w < 8; w++) {
        const float2 gv = lds64(ra + w * 512), uv = lds64((ra ^ 64) + w * 512 + 256);
        g0 += gv.x; g1 += gv.y; u0 += uv.x; u1 += uv.y;
      }
      const uint32_t gp = pack_bf16(g0, g1), up = pack_bf16(u0, u1), sp = pack_bf16(silu_f(bf_lo(gp)), silu_f(bf_hi(gp)));
      const uint32_t act = pack_bf16(bf_lo(sp) * bf_lo(up), bf_hi(sp) * bf_hi(up));
      uint32_t ab[4];
#pragma unroll
      for (int i = 0; i < 4; i++) ab[i] = __shfl_sync(~0u, act, i * 8 + q4 * 2 + (gq & 1));
      if (tid == 128) TRACE(31);
      STAMP(13);
#pragma unroll
      for (int T = 0; T < 2; T++) {
#pragma unroll
        for (int i = 0; i < 4; i++) {
          c[i][0] = c[i][1] = c[i][2] = c[i][3] = 0.f;
          mma_16816(c[i], df + (T * 4 + i) * 8, ab[0], ab[1]); mma_16816(c[i], df + (T * 4 + i) * 8 + 4, ab[2], ab[3]);
        }
        float v[4];
#pragma unroll
        for (int i = 0; i < 4; i++) v[i] = (q4 & 2) ? (odd ? c[3][i] : c[2][i]) : (odd ? c[1][i] : c[0][i]);
        st_msg8(pp + T * 8192, __float_as_uint(v[0]), __float_as_uint(v[2])); st_msg8(pp + T * 8192 + 1024, __float_as_uint(v[1]), __float_as_uint(v[3]));
      }
      if (tid == 128) TRACE(32);
      STAMP(14);
    }
    if (cwarp == 0) {
      const unsigned t0 = clk32();
      mbar_wait(BAR(B_FIN), 0);
      const int fc = q4 * 2 + ((ln >> 2) & 1) + (ln & 8);
      const float2 fo = lds64(sb + PFLAG_OFF + fc * 8);
      const float sg = __uint_as_float(lds32u(sb + CST_OFF));
      __nv_bfloat16* op = out + (size_t)lds32u(sb + SEL_OFF + (bq & 1) * 4) * D_ + (bq >> 1) * 16 + fc;
      const uint4* ip = &S->part[bq * 512 + ln];
      asm volatile("" : "+l"(op), "+l"(ip));
      if (role >> 16) { while (clk32() - t0 < FK_PDELAY) {} } else spin(FK_PDELAY + 600);
      int it = 0;
      uint4 m[14];
      while (true) {
        bool ok = true;
#pragma unroll
        for (int i = 0; i < 14; i++) { m[i] = ld_msg(ip + i * 32); ok &= m[i].x != SENT && m[i].z != SENT; }
        if (__all_sync(~0u, ok)) break;
        SPIN_CHECK(it);
      }
      if (lane == 0) TRACE(33);
      STAMP(15);
      float y[4] = {0.f, 0.f, 0.f, 0.f};
#pragma unroll
      for (int i = 0; i < 14; i++) { y[0] += __uint_as_float(m[i].x); y[1] += __uint_as_float(m[i].y); y[2] += __uint_as_float(m[i].z); y[3] += __uint_as_float(m[i].w); }
      const bool b2 = ln & 4;
      float y0 = (b2 ? y[2] : y[0]) + __shfl_xor_sync(~0u, b2 ? y[0] : y[2], 4), y1 = (b2 ? y[3] : y[1]) + __shfl_xor_sync(~0u, b2 ? y[1] : y[3], 4);
      y0 = ((ln & 8) ? y1 : y0) + __shfl_xor_sync(~0u, (ln & 8) ? y0 : y1, 8);
      y0 += __shfl_xor_sync(~0u, y0, 16);
      const float upd = round_bf16(round_bf16(y0) * sg);
      if (ln < 16) *op = __float2bfloat16_rn(fmaf(fo.y, upd, fo.x));
      if (lane == 0) {
        TRACE(34); TRACE_CLK(122);
      }
    }
  }
}

typedef CUresult (*PFN_encodeTiled)(CUtensorMap*, CUtensorMapDataType, cuuint32_t, void*, const cuuint64_t*, const cuuint64_t*,
                                    const cuuint32_t*, const cuuint32_t*, CUtensorMapInterleave, CUtensorMapSwizzle,
                                    CUtensorMapL2promotion, CUtensorMapFloatOOBfill);

static void mapnd(PFN_encodeTiled enc, CUtensorMap* m, const void* p, int nd, const cuuint64_t* dims, const cuuint64_t* str, const cuuint32_t* box,
                  CUtensorMapSwizzle sw, CUtensorMapL2promotion pr) {
  const cuuint32_t es[5] = {1, 1, 1, 1, 1};
  enc(m, CU_TENSOR_MAP_DATA_TYPE_BFLOAT16, nd, (void*)p, dims, str, box, es, CU_TENSOR_MAP_INTERLEAVE_NONE, sw, pr, CU_TENSOR_MAP_FLOAT_OOB_FILL_NONE);
}
static void map2d(PFN_encodeTiled enc, CUtensorMap* m, const void* p, uint64_t rows, uint64_t cols, uint32_t brows, uint32_t bcols,
                  CUtensorMapSwizzle sw = CU_TENSOR_MAP_SWIZZLE_128B, CUtensorMapL2promotion pr = CU_TENSOR_MAP_L2_PROMOTION_L2_128B) {
  const cuuint64_t dims[2] = {cols, rows}, str[1] = {cols * 2}; const cuuint32_t box[2] = {bcols, brows};
  mapnd(enc, m, p, 2, dims, str, box, sw, pr);
}
static void map3d(PFN_encodeTiled enc, CUtensorMap* m, const void* p, uint64_t rows, uint64_t cols, uint32_t brows, uint32_t bgroups) {
  const cuuint64_t dims[3] = {64, rows, cols / 64}, str[2] = {cols * 2, 128}; const cuuint32_t box[3] = {64, brows, bgroups};
  mapnd(enc, m, p, 3, dims, str, box, CU_TENSOR_MAP_SWIZZLE_128B, CU_TENSOR_MAP_L2_PROMOTION_L2_128B);
}

}

extern "C" void kernel_launch(void* const* d_in, const int* in_sizes, int n_in, void* d_out, int out_size) {
  using namespace fk;
  (void)in_sizes; (void)n_in; (void)out_size;
  static PFN_encodeTiled enc = nullptr;
  static Scratch* scr = nullptr;
  if (!enc) {
    void* fn = nullptr; cudaDriverEntryPointQueryResult qr;
    cudaGetDriverEntryPoint("cuTensorMapEncodeTiled", &fn, cudaEnableDefault, &qr);
    enc = (PFN_encodeTiled)fn;
    cudaGetSymbolAddress((void**)&scr, g_scr);
    cudaFuncSetAttribute(fused_kernel, cudaFuncAttributeMaxDynamicSharedMemorySize, SMEM_BYTES);
  }
  typedef const __nv_bfloat16* bp;
  Params prm;
  prm.w_r = (bp)d_in[6];
  prm.wsp[0] = (const char*)d_in[1]; prm.wsp[1] = (const char*)d_in[2];
  map2d(enc, &prm.ws[0], d_in[1], S_, S_, 128, 64);
  map2d(enc, &prm.ws[1], d_in[2], S_, S_, 128, 64);
  map3d(enc, &prm.n, scr->n, S_, D_, 64, 2);
  map2d(enc, &prm.wm, d_in[11], D_, 6 * D_, 8, 256, CU_TENSOR_MAP_SWIZZLE_NONE, CU_TENSOR_MAP_L2_PROMOTION_L2_256B);
  map2d(enc, &prm.p, scr->P, 2 * S_, D_, 128, 64);
  map2d(enc, &prm.wd[0], d_in[3], D_, D_, 64, 64);
  map2d(enc, &prm.wd[1], d_in[4], D_, D_, 64, 64);
  map2d(enc, &prm.wg, d_in[7], D_, F_, 128, 32, CU_TENSOR_MAP_SWIZZLE_64B);
  map2d(enc, &prm.wu, d_in[8], D_, F_, 128, 32, CU_TENSOR_MAP_SWIZZLE_64B);
  for (int i = 0; i < 3; i++) prm.we[i] = (const char*)d_in[7 + i];
  map2d(enc, &prm.ps, scr->P, 2 * S_, D_, 32, 64);
  for (int i = 0; i < 2; i++) {
    const cuuint64_t dims[3] = {128, 8, i ? 2048u : 3584u}, str[2] = {256, 2048}; const cuuint32_t box[3] = {8, 1, 32};
    mapnd(enc, &prm.tch[i], d_in[i ? 0 : 9], 3, dims, str, box, CU_TENSOR_MAP_SWIZZLE_NONE, CU_TENSOR_MAP_L2_PROMOTION_L2_256B);
  }
  map3d(enc, &prm.xm, d_in[0], S_, D_, 16, 2);
  map3d(enc, &prm.om, d_out, S_, D_, 16, 2);
  {
    const cuuint64_t dims[5] = {64, 2, 8, 224, 16}, str[4] = {8 * 2048, 2048, 16 * 2048, 128}; const cuuint32_t box[5] = {64, 2, 8, 2, 2};
    mapnd(enc, &prm.wdn, d_in[9], 5, dims, str, box, CU_TENSOR_MAP_SWIZZLE_128B, CU_TENSOR_MAP_L2_PROMOTION_L2_128B);
  }

  fused_kernel<<<NCTA, 384, SMEM_BYTES, cudaStreamPerThread>>>((bp)d_in[0], scr, (__nv_bfloat16*)d_out, (bp)d_in[10], (bp)d_in[3], (bp)d_in[4], prm);
}
```

```cpp
#include <cuda_runtime.h>
#include <cuda_bf16.h>
#include <cuda.h>
#include <stdint.h>

#define DEVINL __device__ __forceinline__

namespace fk {

constexpr int S_ = 2048, D_ = 1024, F_ = 3584;
constexpr int NCTA = 128;
constexpr int SLOT = 16384;
constexpr int STAGE = 3 * SLOT;
constexpr int BUF = 2 * SLOT;
constexpr int E_OFF = 5 * BUF;
constexpr int SP_OFF = 4 * STAGE;
constexpr int MISC_OFF = SP_OFF + 32768;
constexpr int SMEM_BYTES = MISC_OFF + 3072;
constexpr int BAR_OFF = MISC_OFF;
constexpr int SEL_OFF = MISC_OFF + 344;
constexpr int BK_OFF = MISC_OFF + 360;
constexpr int CST_OFF = MISC_OFF + 368;
constexpr int PFLAG_OFF = MISC_OFF + 384;
constexpr int TAB_OFF = MISC_OFF + 512;
enum { T_WH = 0, T_ONE = 320, T_WL = 576, T_GA = 896, T_A = 1152, T_S = 1408, T_G = 1664 };
constexpr int KEY_OFF = TAB_OFF + 2048;
constexpr int POLL_OFF = TAB_OFF + 256;
constexpr int T1_OFF = TAB_OFF + 1536;
constexpr int RKA_OFF = BUF;
constexpr int RKB_OFF = RKA_OFF + 2048;
constexpr int RED_OFF = RKB_OFF + 2048;
constexpr int H_OFF = 8192;
constexpr int DN_OFF = RED_OFF + 4096;

enum { B_FULL = 0, B_EMPTY = 4, B_PREADY = 8, B_MF = 12  , B_FULL2 = 20  , B_EMPTY2 = 25  , B_A29 = 30, B_ADONE = 31,
       B_RSDONE = 32, B_TAB = 33, B_B27 = 34, B_ROWS = 35, B_DN = 36, B_EFULL = 37, B_PS = 38  , B_WF = 40, B_BK = 41, B_FIN = 42, B_NUM = 43 };
constexpr unsigned long long CNT0 = 0x1111888855551111ull, CNT1 = 0x4244444222221111ull, CNT2 = 0x1111111111111122ull;

#define FK_SKIP 0
#define FK_X 0
#define FK_PS0 1
#define FK_XN 0
#define FK_S1 0
#define FK_NL 12
#define FK_XD 0
#define FK_GS 1
#define FK_TD 1
#define FK_TX 1
#define FK_ODELAY 0
#define FK_OMASK 255
#define FK_OSPACE2 0
#define FK_NP 0
#define FK_G1 20
#define FK_GP 2
#define FK_QR 31
#define FK_H1 3
#define FK_S 0
#define FK_NA0 1
#define FK_QUIET FK_S
#define FK_EP 0
#define FK_DRY 11
#define FK_T0D 0
#define FK_T1D 0
#define FK_A0D 200
#define FK_A1D 400
#define FK_A0N 0
#define FK_A0W 0
#define FK_REL 0x14
#define FK_WSPF 22
#define FK_SPACE 300
#define FK_OSPACE 200
#define FK_NOMC 4
#define FK_TR0 0
#define FK_G0 3
#define FK_NA 0
#define FK_PACE 800
#define FK_QP 5
#define FK_PSPACE 400
#define FK_ORD 0
#define FK_PDELAY 900
constexpr int SPIN_LIMIT = 1 << 20;
constexpr uint32_t SENT = 0xFFFFFFFFu;

struct Scratch {
  uint4 part[128 * 128 * 4];
  uint4 stats[128 * 128];
  uint4 rowsH[32 * 128];
  uint4 rowsB[32 * 128];
  uint4 cand[16 * 8];
  uint2 rs[2 * S_];
  uint4 st0[64 * 2];
  uint4 cst[8];
  float mod[2][6 * D_];
  uint2 u[2 * D_];
  unsigned flagP[128 * 4 * 8];
  unsigned cntN[12 * 32];
  unsigned cntMod[2 * 32];
  unsigned epoch[32];
  unsigned claim[64 * 8];
  alignas(1024) __nv_bfloat16 n[S_ * D_];
  __nv_bfloat16 P[2 * S_ * D_];
};
__device__ __align__(1024) Scratch g_scr;

struct Params {
  CUtensorMap ws[2];
  CUtensorMap n;
  CUtensorMap wm;
  CUtensorMap p;
  CUtensorMap wg, wu;
  CUtensorMap xm;
  CUtensorMap wdn;
  CUtensorMap wd[2];
  CUtensorMap om;
  CUtensorMap xb;
  CUtensorMap ps;
  CUtensorMap tch[2];
  const __nv_bfloat16* w_r;
  const char* wsp[2];
  const char* we[3];
};

DEVINL uint32_t smem_u32(const void* p) { return (uint32_t)__cvta_generic_to_shared(p); }
DEVINL void mbar_init(uint32_t bar, uint32_t cnt) { asm volatile("mbarrier.init.shared::cta.b64 [%0], %1;" ::"r"(bar), "r"(cnt) : "memory"); }
DEVINL void mbar_expect_tx(uint32_t bar, uint32_t bytes) { asm volatile("mbarrier.arrive.expect_tx.shared::cta.b64 _, [%0], %1;" ::"r"(bar), "r"(bytes) : "memory"); }
DEVINL void mbar_arrive(uint32_t bar) { asm volatile("mbarrier.arrive.shared::cta.b64 _, [%0];" ::"r"(bar) : "memory"); }
DEVINL void mbar_wait(uint32_t bar, uint32_t parity) {
  asm volatile("{\n.reg .pred p;\n.reg .u32 c;\nmov.u32 c, 0;\n"
               "LW:\nmbarrier.try_wait.parity.shared::cta.b64 p, [%0], %1;\n@p bra LD;\n"
               "add.u32 c, c, 1;\nsetp.lt.u32 p, c, 1048576;\n@p bra LW;\ntrap;\nLD:\n}" ::"r"(bar), "r"(parity) : "memory");
}
DEVINL void mbar_wait_cluster(uint32_t bar, uint32_t parity) {
  asm volatile("{\n.reg .pred p;\n.reg .u32 c;\nmov.u32 c, 0;\n"
               "LW:\nmbarrier.try_wait.parity.acquire.cluster.shared::cta.b64 p, [%0], %1;\n@p bra LD;\n"
               "add.u32 c, c, 1;\nsetp.lt.u32 p, c, 1048576;\n@p bra LW;\ntrap;\nLD:\n}" ::"r"(bar), "r"(parity) : "memory");
}
#define SPIN_CHECK(it) asm volatile("{\n.reg .pred p;\nsetp.gt.s32 p, %0, %1;\n@p trap;\n}" ::"r"(++(it)), "n"(SPIN_LIMIT))
DEVINL void fence_async_smem() { asm volatile("fence.proxy.async.shared::cta;" ::: "memory"); }
DEVINL void fence_async_global() { asm volatile("fence.proxy.async.global;" ::: "memory"); }
template <int BIT> DEVINL void rel_fence() { if ((FK_REL >> BIT) & 1) asm volatile("fence.acq_rel.gpu;" ::: "memory"); }
DEVINL void fence_gpu() { asm volatile("fence.acq_rel.gpu;" ::: "memory"); }
template <int ID, int N> DEVINL void named_bar() { asm volatile("bar.sync %0, %1;" ::"n"(ID), "n"(N) : "memory"); }
DEVINL bool elect_one() { uint32_t p; asm volatile("{\n.reg .pred e;\nelect.sync _|e, 0xffffffff;\nselp.u32 %0, 1, 0, e;\n}" : "=r"(p)); return p; }
DEVINL unsigned clk32() { unsigned c; asm volatile("mov.u32 %0, %%clock;" : "=r"(c)); return c; }
#define FK_GRIDW 32
#define FK_GRID 0
DEVINL void grid_wait() {
  if (FK_GRID) {
    unsigned t0, t1;
    asm volatile("mov.u32 %0, %%globaltimer_lo;" : "=r"(t0));
    do { asm volatile("mov.u32 %0, %%globaltimer_lo;" : "=r"(t1)); } while (((t0 - FK_GRIDW) ^ t1) < FK_GRID + 0u + !FK_GRID);
  }
}
DEVINL void spin(unsigned n) { const unsigned c = clk32(); while (clk32() - c < n) {} }

constexpr uint64_t POL_NORMAL = 0x1000000000000000ull, POL_FIRST = 0x12F0000000000000ull;
#define FK_HINTS 0x30B
template <int BIT> DEVINL constexpr uint64_t pol() { return ((FK_HINTS >> BIT) & 1) ? POL_FIRST : POL_NORMAL; }
DEVINL void tma_2d(uint32_t dst, const CUtensorMap* m, int x, int y, uint32_t bar, uint64_t pol) {
  asm volatile("cp.async.bulk.tensor.2d.shared::cluster.global.mbarrier::complete_tx::bytes.L2::cache_hint [%0], [%1, {%3, %4}], [%2], %5;"
               ::"r"(dst), "l"(m), "r"(bar), "r"(x), "r"(y), "l"(pol) : "memory");
}
DEVINL void tma_3d(uint32_t dst, const CUtensorMap* m, int y, int z, uint32_t bar, uint64_t pol) {
  asm volatile("cp.async.bulk.tensor.3d.shared::cluster.global.mbarrier::complete_tx::bytes.L2::cache_hint [%0], [%1, {0, %3, %4}], [%2], %5;"
               ::"r"(dst), "l"(m), "r"(bar), "r"(y), "r"(z), "l"(pol) : "memory");
}
DEVINL void tma_3d_mc(uint32_t dst, const CUtensorMap* m, int y, int z, uint32_t bar, uint64_t pol) {
  asm volatile("cp.async.bulk.tensor.3d.shared::cluster.global.mbarrier::complete_tx::bytes.multicast::cluster.L2::cache_hint [%0], [%1, {0, %3, %4}], [%2], %5, %6;"
               ::"r"(dst), "l"(m), "r"(bar), "r"(y), "r"(z), "h"((unsigned short)3), "l"(pol) : "memory");
}
DEVINL void tma_2d_mc(uint32_t dst, const CUtensorMap* m, int x, int y, uint32_t bar, uint64_t pol) {
  asm volatile("cp.async.bulk.tensor.2d.shared::cluster.global.mbarrier::complete_tx::bytes.multicast::cluster.L2::cache_hint [%0], [%1, {%3, %4}], [%2], %5, %6;"
               ::"r"(dst), "l"(m), "r"(bar), "r"(x), "r"(y), "h"((unsigned short)3), "l"(pol) : "memory");
}
DEVINL void tma_store_2d(const CUtensorMap* m, uint32_t src, int x, int y) {
  asm volatile("cp.async.bulk.tensor.2d.global.shared::cta.bulk_group [%0, {%2, %3}], [%1];" ::"l"(m), "r"(src), "r"(x), "r"(y) : "memory");
}
DEVINL void bulk_store(void* dst, uint32_t src, uint32_t bytes) {
  asm volatile("cp.async.bulk.global.shared::cta.bulk_group [%0], [%1], %2;" ::"l"(dst), "r"(src), "r"(bytes) : "memory");
}
DEVINL void bulk_load(uint32_t dst, const void* src, uint32_t bytes, uint32_t bar, uint64_t pol) {
  asm volatile("cp.async.bulk.shared::cluster.global.mbarrier::complete_tx::bytes.L2::cache_hint [%0], [%1], %2, [%3], %4;" ::"r"(dst), "l"(src), "r"(bytes), "r"(bar), "l"(pol) : "memory");
}
template <int N> DEVINL void bulk_wait_read() { asm volatile("cp.async.bulk.wait_group.read %0;" ::"n"(N) : "memory"); }
DEVINL void pf_bulk(const void* p, uint32_t bytes) { asm volatile("cp.async.bulk.prefetch.L2.global [%0], %1;" ::"l"(p), "r"(bytes) : "memory"); }
DEVINL void bulk_commit() { asm volatile("cp.async.bulk.commit_group;" ::: "memory"); }
template <int N> DEVINL void bulk_wait() { asm volatile("cp.async.bulk.wait_group %0;" ::"n"(N) : "memory"); }
DEVINL void prefetch_tmap(const CUtensorMap* m) { asm volatile("prefetch.tensormap [%0];" ::"l"(m) : "memory"); }

DEVINL void wg_fence() { asm volatile("wgmma.fence.sync.aligned;" ::: "memory"); }
DEVINL void wg_commit() { asm volatile("wgmma.commit_group.sync.aligned;" ::: "memory"); }
template <int N> DEVINL void wg_wait() { asm volatile("wgmma.wait_group.sync.aligned %0;" ::"n"(N) : "memory"); }
DEVINL uint32_t desc_lo(uint32_t addr, uint32_t lbo) { return ((addr & 0x3FFFF) >> 4) | ((lbo >> 4) << 16); }

#define R8(a, o) "+f"(a[o]), "+f"(a[o + 1]), "+f"(a[o + 2]), "+f"(a[o + 3]), "+f"(a[o + 4]), "+f"(a[o + 5]), "+f"(a[o + 6]), "+f"(a[o + 7])
#define R64(a, o) R8(a, o), R8(a, o + 8), R8(a, o + 16), R8(a, o + 24), R8(a, o + 32), R8(a, o + 40), R8(a, o + 48), R8(a, o + 56)
#define ACC64 "{%0, %1, %2, %3, %4, %5, %6, %7, %8, %9, %10, %11, %12, %13, %14, %15, "              \
              "%16, %17, %18, %19, %20, %21, %22, %23, %24, %25, %26, %27, %28, %29, %30, %31, "    \
              "%32, %33, %34, %35, %36, %37, %38, %39, %40, %41, %42, %43, %44, %45, %46, %47, "    \
              "%48, %49, %50, %51, %52, %53, %54, %55, %56, %57, %58, %59, %60, %61, %62, %63"
#define ACC128 ACC64 ", %64, %65, %66, %67, %68, %69, %70, %71, %72, %73, %74, %75, %76, %77, %78, %79, "      \
              "%80, %81, %82, %83, %84, %85, %86, %87, %88, %89, %90, %91, %92, %93, %94, %95, "               \
              "%96, %97, %98, %99, %100, %101, %102, %103, %104, %105, %106, %107, %108, %109, %110, %111, "   \
              "%112, %113, %114, %115, %116, %117, %118, %119, %120, %121, %122, %123, %124, %125, %126, %127"
template <int TB> DEVINL void wgmma_n256(float (&d)[128], uint32_t da, uint32_t db, int scale_d) {
  asm volatile("{\n.reg .pred p;\n.reg .b64 a, b;\nsetp.ne.b32 p, %130, 0;\nmov.b64 a, {%128, 0x40000040};\nmov.b64 b, {%129, 0x40000040};\n"
               "wgmma.mma_async.sync.aligned.m64n256k16.f32.bf16.bf16 " ACC128 "}, a, b, p, 1, 1, 0, %131;\n}\n"
               : R64(d, 0), R64(d, 64) : "r"(da), "r"(db), "r"(scale_d), "n"(TB));
}
template <int TB, int HI = 0x40000040> DEVINL void wgmma_n128(float (&d)[64], uint32_t da, uint32_t db) {
  asm volatile("{\n.reg .b64 a, b;\nmov.b64 a, {%64, %67};\nmov.b64 b, {%65, %67};\n"
               "wgmma.mma_async.sync.aligned.m64n128k16.f32.bf16.bf16 " ACC64 "}, a, b, 1, 1, 1, 0, %66;\n}\n" : R64(d, 0) : "r"(da), "r"(db), "n"(TB), "n"(HI));
}
template <int SC> DEVINL void wgmma_n128_rs(float (&d)[64], const uint32_t* a, uint32_t db) {
  asm volatile("{\n.reg .pred p;\n.reg .b64 b;\nsetp.ne.b32 p, %69, 0;\nmov.b64 b, {%68, 0x40000040};\n"
               "wgmma.mma_async.sync.aligned.m64n128k16.f32.bf16.bf16 " ACC64 "}, {%64, %65, %66, %67}, b, p, 1, 1, 0;\n}\n"
               : R64(d, 0) : "r"(a[0]), "r"(a[1]), "r"(a[2]), "r"(a[3]), "r"(db), "n"(SC));
}
template <int N> DEVINL void reg_fence(float (&a)[N]) {
#pragma unroll
  for (int i = 0; i < N; i++) asm volatile("" : "+f"(a[i])::"memory");
}

DEVINL uint32_t pack_bf16(float lo, float hi) { uint32_t r; asm("cvt.rn.bf16x2.f32 %0, %1, %2;" : "=r"(r) : "f"(hi), "f"(lo)); return r; }
DEVINL uint32_t add_bf16x2(uint32_t a, uint32_t b) { uint32_t r; asm("add.rn.bf16x2 %0, %1, %2;" : "=r"(r) : "r"(a), "r"(b)); return r; }
DEVINL uint32_t mul_bf16x2(uint32_t a, uint32_t b) { uint32_t r; asm("mul.rn.bf16x2 %0, %1, %2;" : "=r"(r) : "r"(a), "r"(b)); return r; }
DEVINL uint32_t fma_bf16x2(uint32_t a, uint32_t b, uint32_t c) { uint32_t r; asm("fma.rn.bf16x2 %0, %1, %2, %3;" : "=r"(r) : "r"(a), "r"(b), "r"(c)); return r; }
DEVINL float bf_lo(uint32_t w) { return __uint_as_float(w << 16); }
DEVINL float bf_hi(uint32_t w) { return __uint_as_float(w & 0xFFFF0000u); }
DEVINL float round_bf16(float v) { return bf_lo(pack_bf16(v, 0.f)); }
DEVINL float sigmoid_f(float v) { float r; asm("rcp.approx.ftz.f32 %0, %1;" : "=f"(r) : "f"(1.f + __expf(-v))); return r; }
DEVINL float rsqrt_f(float v) { float r; asm("rsqrt.approx.ftz.f32 %0, %1;" : "=f"(r) : "f"(v)); return r; }
DEVINL float silu_f(float v) { return v * sigmoid_f(v); }
DEVINL void stsm_x4(uint32_t addr, const uint32_t* r) {
  asm volatile("stmatrix.sync.aligned.m8n8.x4.shared.b16 [%0], {%1, %2, %3, %4};" ::"r"(addr), "r"(r[0]), "r"(r[1]), "r"(r[2]), "r"(r[3]) : "memory");
}
DEVINL void ldsm_x4(uint32_t addr, uint32_t* r) {
  asm volatile("ldmatrix.sync.aligned.m8n8.x4.shared.b16 {%0, %1, %2, %3}, [%4];" : "=r"(r[0]), "=r"(r[1]), "=r"(r[2]), "=r"(r[3]) : "r"(addr) : "memory");
}
DEVINL void ldsm_x4_t(uint32_t addr, uint32_t* r) {
  asm volatile("ldmatrix.sync.aligned.m8n8.x4.trans.shared.b16 {%0, %1, %2, %3}, [%4];" : "=r"(r[0]), "=r"(r[1]), "=r"(r[2]), "=r"(r[3]) : "r"(addr) : "memory");
}
DEVINL void mma_16816(float (&c)[4], const uint32_t* a, uint32_t b0, uint32_t b1) {
  asm("mma.sync.aligned.m16n8k16.row.col.f32.bf16.bf16.f32 {%0, %1, %2, %3}, {%4, %5, %6, %7}, {%8, %9}, {%0, %1, %2, %3};"
      : "+f"(c[0]), "+f"(c[1]), "+f"(c[2]), "+f"(c[3]) : "r"(a[0]), "r"(a[1]), "r"(a[2]), "r"(a[3]), "r"(b0), "r"(b1));
}
DEVINL void mma_1688(float (&c)[4], uint32_t a0, uint32_t a1, uint32_t b0) {
  asm("mma.sync.aligned.m16n8k8.row.col.f32.bf16.bf16.f32 {%0, %1, %2, %3}, {%4, %5}, {%6}, {%0, %1, %2, %3};"
      : "+f"(c[0]), "+f"(c[1]), "+f"(c[2]), "+f"(c[3]) : "r"(a0), "r"(a1), "r"(b0));
}
DEVINL float4 lds128(uint32_t a) { float4 v; asm volatile("ld.shared.v4.f32 {%0, %1, %2, %3}, [%4];" : "=f"(v.x), "=f"(v.y), "=f"(v.z), "=f"(v.w) : "r"(a)); return v; }
DEVINL uint4 lds128u(uint32_t a) { uint4 v; asm volatile("ld.shared.v4.u32 {%0, %1, %2, %3}, [%4];" : "=r"(v.x), "=r"(v.y), "=r"(v.z), "=r"(v.w) : "r"(a)); return v; }
DEVINL float2 lds64(uint32_t a) { float2 v; asm volatile("ld.shared.v2.f32 {%0, %1}, [%2];" : "=f"(v.x), "=f"(v.y) : "r"(a)); return v; }
DEVINL uint32_t lds32u(uint32_t a) { uint32_t v; asm volatile("ld.shared.u32 %0, [%1];" : "=r"(v) : "r"(a)); return v; }
DEVINL void sts128(uint32_t a, float x, float y, float z, float w) { asm volatile("st.shared.v4.f32 [%0], {%1, %2, %3, %4};" ::"r"(a), "f"(x), "f"(y), "f"(z), "f"(w) : "memory"); }
DEVINL void sts128u(uint32_t a, uint32_t x, uint32_t y, uint32_t z, uint32_t w) { asm volatile("st.shared.v4.u32 [%0], {%1, %2, %3, %4};" ::"r"(a), "r"(x), "r"(y), "r"(z), "r"(w) : "memory"); }
DEVINL void sts64u(uint32_t a, uint32_t x, uint32_t y) { asm volatile("st.shared.v2.u32 [%0], {%1, %2};" ::"r"(a), "r"(x), "r"(y) : "memory"); }
DEVINL void sts32v(uint32_t a, uint32_t v) { asm volatile("st.volatile.shared.u32 [%0], %1;" ::"r"(a), "r"(v) : "memory"); }
DEVINL void sts32(uint32_t a, float v) { asm volatile("st.shared.f32 [%0], %1;" ::"r"(a), "f"(v) : "memory"); }

DEVINL uint4 ld_msg(const void* p) {
  unsigned long long a, b;
  asm volatile("{\n.reg .b128 r;\nld.relaxed.gpu.global.b128 r, [%2];\nmov.b128 {%0, %1}, r;\n}" : "=l"(a), "=l"(b) : "l"(p) : "memory");
  return make_uint4((uint32_t)a, (uint32_t)(a >> 32), (uint32_t)b, (uint32_t)(b >> 32));
}
DEVINL void st_msg(void* p, uint32_t x, uint32_t y, uint32_t z, uint32_t w) {
  unsigned long long a = (unsigned long long)x | ((unsigned long long)y << 32), b = (unsigned long long)z | ((unsigned long long)w << 32);
  asm volatile("{\n.reg .b128 r;\nmov.b128 r, {%1, %2};\nst.relaxed.gpu.global.b128 [%0], r;\n}" ::"l"(p), "l"(a), "l"(b) : "memory");
}
DEVINL uint2 ld_msg8(const void* p) {
  unsigned long long a;
  asm volatile("ld.relaxed.gpu.global.b64 %0, [%1];" : "=l"(a) : "l"(p) : "memory");
  return make_uint2((uint32_t)a, (uint32_t)(a >> 32));
}
DEVINL void st_msg8(void* p, uint32_t x, uint32_t y) {
  asm volatile("st.relaxed.gpu.global.b64 [%0], %1;" ::"l"(p), "l"((unsigned long long)x | ((unsigned long long)y << 32)) : "memory");
}
DEVINL unsigned ld_rlx(const void* p) { unsigned v; asm volatile("ld.relaxed.gpu.global.u32 %0, [%1];" : "=r"(v) : "l"(p) : "memory"); return v; }
DEVINL void st_rlx(unsigned* p, unsigned v) { asm volatile("st.relaxed.gpu.global.u32 [%0], %1;" ::"l"(p), "r"(v) : "memory"); }
DEVINL void red_add(unsigned* p, unsigned v) { asm volatile("red.relaxed.gpu.global.add.u32 [%0], %1;" ::"l"(p), "r"(v) : "memory"); }
DEVINL uint4 ldg_nc(const void* p) {
  uint4 v;
  asm volatile("ld.global.nc.L1::no_allocate.v4.u32 {%0, %1, %2, %3}, [%4];" : "=r"(v.x), "=r"(v.y), "=r"(v.z), "=r"(v.w) : "l"(p));
  return v;
}
DEVINL float4 ldg_cg(const float* p) { float4 v; asm volatile("ld.global.cg.v4.f32 {%0, %1, %2, %3}, [%4];" : "=f"(v.x), "=f"(v.y), "=f"(v.z), "=f"(v.w) : "l"(p) : "memory"); return v; }
DEVINL void wait_cnt(const unsigned* p, unsigned target) {
  int it = 0;
  while ((int)(ld_rlx(p) - target) < 0) { SPIN_CHECK(it); __nanosleep(100); }
}

#define TRACE2(id)
#define TRACE3(id)
#define TRACE(id)
#define TRACE_CLK(id)

#define STAMP2(i)
#define STAMP(i)
DEVINL uint32_t fkey(float v) { const uint32_t u = __float_as_uint(v); return (u & 0x80000000u) ? ~u : (u | 0x80000000u); }
DEVINL float fkey_inv(uint32_t k) { return __uint_as_float((k & 0x80000000u) ? (k & 0x7FFFFFFFu) : ~k); }
DEVINL uint32_t redux_max(uint32_t v) { uint32_t r; asm volatile("redux.sync.max.u32 %0, %1, 0xffffffff;" : "=r"(r) : "r"(v)); return r; }
DEVINL void warp_top2(uint32_t key, uint32_t& k1, uint32_t& k2) { k1 = redux_max(key); k2 = redux_max(key == k1 ? 0u : key); }
DEVINL int key_row(uint32_t k) { return 2047 - (int)(k & 2047u); }
DEVINL int blk_src(int q, int cgrp) { const int f = q - 4, kk = (f * 37) >> 8, i = f - kk * 7; return f < 0 ? cgrp * 4 + q : (FK_SKIP ? i + (i >= cgrp) : i == cgrp ? 7 : i) * 4 + kk; }
DEVINL void split_assign(int c, int& grp, int& gi) {
  const int c7 = ((c - 36) * 37) >> 8;
  grp = c < 4 ? 0 : c < 36 ? (c - 4) & 7 : c - 35 - c7 * 7; gi = c < 4 ? c + 4 : c < 36 ? (c - 4) >> 3 : c7 + 4;
}
DEVINL int first_choice() {
  unsigned smid; asm volatile("mov.u32 %0, %%smid;" : "=r"(smid));
  return (smid >> 1) >= 62 ? (62 - (smid >> 1)) & 3 : ((smid >> 1) + 4) & 63;
}
DEVINL uint32_t pstage(int kk) { return ((0xABA4 >> (kk * 4)) & 15) * SLOT; }
DEVINL uint32_t buf_off(int u) { return ((0x42130 >> (u * 4)) & 15) * BUF; }
DEVINL int cnt_idx(int kb) { return kb < 4 ? (8 + kb) * 32 : (kb >> 2) * 32 + (kb & 3); }

__global__ void __launch_bounds__(384, 1) __cluster_dims__(2, 1, 1)
fused_kernel(const __nv_bfloat16* __restrict__ x, Scratch* const S, __nv_bfloat16* __restrict__ out, const __nv_bfloat16* __restrict__ cvec,
             const __nv_bfloat16* __restrict__ wd_re, const __nv_bfloat16* __restrict__ wd_im, const __grid_constant__ Params prm) {
  extern __shared__ __align__(1024) uint8_t smem_raw[];
  const uint32_t sb = smem_u32(smem_raw);
  const int tid = threadIdx.x, lane = tid & 31;
  const int warp = __shfl_sync(~0u, tid >> 5, 0);
  const int bx = blockIdx.x, rank = bx & 1;
  auto BAR = [&](int i) { return sb + BAR_OFF + i * 8; };

  uint4 xr[8] = {};
  if ((warp & ~1) == 2) {
    const uint4* src = reinterpret_cast<const uint4*>(x + (size_t)(bx * 2 + warp - 2) * D_) + lane;
#pragma unroll
    for (int i = 0; i < 4; i++) xr[i] = ldg_nc(src + 32 * i);
  }
  if (warp < 2) spin(FK_T0D);
  unsigned cnt0 = 0;
  if (FK_EP && tid < 8) cnt0 = ld_rlx(&S->cntN[cnt_idx(tid)]);
  if (warp >= 4 && warp < 11 && elect_one()) {
    const int w = warp - 4;
#pragma unroll 1
    for (int i = w; i < B_NUM; i += 7) {
      mbar_init(BAR(i), (uint32_t)((i < 16 ? CNT0 : i < 32 ? CNT1 : CNT2) >> ((i & 15) * 4)) & 15u);
    }
    if (w < 4) mbar_expect_tx(BAR(B_FULL + w), STAGE);
    asm volatile("fence.mbarrier_init.release.cluster;" ::: "memory");
    if (w < 3) { spin(FK_T1D); prefetch_tmap(&prm.ws[0] + w); }
  }
  if (warp == 1 && rank == 0 && elect_one()) {
    int c = first_choice(), it = 0;
    while (atomicExch(&S->claim[c * 8], 1u)) { c = (c + 1) & 63; SPIN_CHECK(it); }
    sts32v(sb + BK_OFF, c);
    asm volatile("fence.acq_rel.cta;" ::: "memory");
  }
  __syncwarp();
  if (warp >= 4 && warp != FK_DRY) asm volatile("bar.arrive 3, 320;" ::: "memory");
  asm volatile("barrier.cluster.arrive.relaxed.aligned;" ::: "memory");
  if (warp >= 11 - FK_A0N && warp < 11) {
    int g0, i0; split_assign(first_choice(), g0, i0);
    spin(FK_A0D + (10 - warp) * FK_A1D);
    asm volatile("prefetch.global.L2 [%0];" ::"l"(prm.wsp[i0 >> 2] + (size_t)((g0 * 2 + rank) * 128 + (i0 & 3) * 32 + lane) * 4096 + (10 - warp) * 128));
  }
  uint32_t epoch = 0;
  if (FK_S || warp == 1 || (FK_DRY && warp == 0)) epoch = ld_rlx(S->epoch);
  const uint32_t ring = sb + SP_OFF + (warp == FK_DRY ? 8192 : (warp - 2) * 16384), mf = BAR(B_MF + (warp - 2) * 4);
  const int jw = bx >> 6, e0 = (bx & 63) * 16;
  const __nv_bfloat16* src = (jw ? wd_im : wd_re) + (size_t)e0 * D_;
  int nc = 0;
  if ((warp & ~1) == 2 || warp == FK_DRY) {
#pragma unroll 1
    for (int G = 0; G < 8; G += (G == 0 && warp == 2) + 1) {
      if (G) { mbar_wait(mf + (nc & 3) * 8, (nc >> 2) & 1); nc++; }
      const uint32_t stg = ring + (nc & 3) * 4096, sl = stg + (G ? (lane >> 4) * 2048 + (lane & 15) * 16 : lane * 16), st = G ? 256 : 512;
      if (G) {
#pragma unroll
        for (int k = 0; k < 8; k++) xr[k] = lds128u(sl + k * 256);
      }
      float s0 = 0.f, s1 = 0.f, q0 = 0.f, q1 = 0.f, s2 = 0.f, s3 = 0.f, q2 = 0.f, q3 = 0.f;
      float v[64];
#pragma unroll
      for (int h = 0; h < 2; h++)
        if (h == 0 || G) {
#pragma unroll
          for (int k = 4 * h; k < 4 * h + 4; k++) {
            float* u = v + 8 * k;
            u[0] = bf_lo(xr[k].x); u[1] = bf_hi(xr[k].x); u[2] = bf_lo(xr[k].y); u[3] = bf_hi(xr[k].y);
            u[4] = bf_lo(xr[k].z); u[5] = bf_hi(xr[k].z); u[6] = bf_lo(xr[k].w); u[7] = bf_hi(xr[k].w);
#pragma unroll
            for (int i = 0; i < 8; i += 4) {
              s0 += u[i]; s1 += u[i + 1]; s2 += u[i + 2]; s3 += u[i + 3];
              q0 = fmaf(u[i], u[i], q0); q1 = fmaf(u[i + 1], u[i + 1], q1); q2 = fmaf(u[i + 2], u[i + 2], q2); q3 = fmaf(u[i + 3], u[i + 3], q3);
            }
          }
        }
      float sum = (s0 + s1) + (s2 + s3), sq = (q0 + q1) + (q2 + q3);
#pragma unroll
      for (int o = 1; o < 32; o <<= 1)
        if (o < 16 || !G) { sum += __shfl_xor_sync(~0u, sum, o); sq += __shfl_xor_sync(~0u, sq, o); }
      const float mean = sum * (1.f / D_);
      const float rstd = rsqrt_f(fmaxf(fmaf(-mean, mean, sq * (1.f / D_)), 0.f) + 1e-5f), nmr = -mean * rstd;
      if (FK_S && G == 0 && bx < 32 && lane < 2) st_msg(&S->st0[(bx * 2 + warp - 2) * 2 + lane], __float_as_uint(rstd), __float_as_uint(nmr), epoch + 1, 0);
#pragma unroll
      for (int h = 0; h < 2; h++)
        if (h == 0 || G) {
#pragma unroll
          for (int k = 4 * h; k < 4 * h + 4; k++) {
            const float* u = v + 8 * k;
            sts128u(sl + k * st, pack_bf16(fmaf(u[0], rstd, nmr), fmaf(u[1], rstd, nmr)), pack_bf16(fmaf(u[2], rstd, nmr), fmaf(u[3], rstd, nmr)),
                    pack_bf16(fmaf(u[4], rstd, nmr), fmaf(u[5], rstd, nmr)), pack_bf16(fmaf(u[6], rstd, nmr), fmaf(u[7], rstd, nmr)));
          }
        }
      fence_async_smem();
      if (warp == FK_DRY) { if (FK_DRY >= 4) asm volatile("bar.arrive 3, 320;" ::: "memory"); break; }
      const int kq = bx >> 5;
      if (elect_one()) {
        bulk_store(S->n + (size_t)(G * 256 + bx * 2 + (G ? 0 : warp - 2)) * D_, stg, G ? 4096 : 2048); bulk_commit();
        if (G == 0) { bulk_wait<0>(); rel_fence<0>(); red_add(&S->cntN[cnt_idx(kq)], 1);
          TRACE(42 + warp);
        }
      }
      if (G == 0) named_bar<3, 320>();
      if (elect_one()) {
        if (G == 0 && warp == 2) mbar_wait(BAR(B_FULL + FK_QUIET), 0);
        if (G >= 4) { bulk_wait<1>(); red_add(&S->cntN[(G - 1) * 32 + kq], 2); }
#pragma unroll 1
        for (int k = G ? nc + 1 : 0; k < (warp == 2 ? nc + 2 : 1); k++) {
          mbar_expect_tx(mf + (k & 3) * 8, 4096);
          bulk_load(ring + ((k + 1) & 3) * 4096, k < 6 ? x + (size_t)((k + 4 - warp) * 256 + bx * 2) * D_ : src + (k - 6) * 2 * D_, 4096, mf + (k & 3) * 8, k < 6 ? pol<7>() : pol<2>());
        }
        if (G == 1 || G == 2 || G == 7) { bulk_wait<0>(); rel_fence<1>(); red_add(&S->cntN[G * 32 + kq], 2); if (G > 1) TRACE(44 + (G & 3)); }
      }
      __syncwarp();
      if (warp == 3 && G) break;
    }
    if (!FK_S) epoch = ld_rlx(S->epoch);
  }
  asm volatile("barrier.cluster.wait.acquire.aligned;" ::: "memory");
  int cl, grp, gi;
  asm volatile("{\n.reg .b32 ra;\nmapa.shared::cluster.u32 ra, %1, 0;\nld.volatile.shared::cluster.u32 %0, [ra];\n}" : "=r"(cl) : "r"(sb + BK_OFF) : "memory");
  cl = __shfl_sync(~0u, cl, 0);
  split_assign(cl, grp, gi);
  const uint32_t tag = epoch + 1;
  const int j = gi >> 2, m4 = gi & 3, t = grp * 2 + rank;
  const int cgrp = m4 * 2 + j;
  const int b = t * 8 + cgrp;
  const bool moe = gi < 7;
  const int eb = (j ? 64 + grp * 6 : grp * 8) + m4 * 2 + rank;

  if (warp < 4) {
    auto prefetch_piece = [&](int p) { if (!(FK_X & 1) && !((FK_X & 8) && p >= 12)) pf_bulk(prm.we[p >> 3] + (size_t)((p & 7) * 128 + b) * 7168, 7168); };
    auto weight_box = [&](int n, uint32_t bar) {
      if (moe && !(FK_X & 2) && !((FK_X & 8) && n >= 12)) {
        asm volatile("mbarrier.expect_tx.relaxed.cta.shared::cta.b64 [%0], 8192;" ::"r"(bar) : "memory");
        tma_2d(sb + SP_OFF + (n & 3) * 8192, &prm.wg + (n >> 3), eb * 32, (n & 7) * 128, bar, pol<3>());
      }
    };
    if (warp == 0) {
      const unsigned* flagAddr = &S->cntN[cnt_idx(lane)];
      const unsigned tgt = tag * 64u;
      if (elect_one()) {
        if (FK_A0W) spin(FK_A0W);
        if (FK_S) { tma_3d(sb + SLOT, &prm.xb, 0, m4 * 4, BAR(B_FULL), POL_NORMAL); tma_3d(sb + 2 * SLOT, &prm.xb, 0, m4 * 4 + 2, BAR(B_FULL), POL_NORMAL); }
#pragma unroll 1
        for (int g = 0; g < FK_NA0; g++) tma_2d(sb + g * STAGE, &prm.ws[j], g * 64, t * 128, BAR(B_FULL + g), pol<0>());
      }
      if (lane == 0) TRACE(59);
      unsigned ready = FK_S | __ballot_sync(~0u, lane < 8 && cnt0 == tgt);
      fence_async_global();
      if (lane >= 4) sts32v(sb + POLL_OFF + lane * 4, tgt - 1);
      auto ensure = [&](int g) {
        int it = 0;
        while (!((ready >> g) & 1)) {
          ready |= __ballot_sync(~0u, (lane >> 2) == (g >> 2) && ld_rlx(flagAddr) == tgt);
          SPIN_CHECK(it);
        }
        fence_async_global();
      };
#pragma unroll 1
      for (int g = FK_S; g < 32; g++) {
        const int s = g & 3;
        const uint32_t sa = sb + s * STAGE, fb = BAR(B_FULL + s);
        if (g >= 4) {
          if (g == 4) ensure(4);
          mbar_wait(BAR(B_EMPTY + s), ((g >> 2) - 1) & 1);
          if (lane < 8 && ((~ready >> (lane * 4)) & 15))
            asm volatile("cp.async.cg.shared.global [%0], [%1], 16;" ::"r"(sb + POLL_OFF + lane * 16), "l"(&S->cntN[lane * 32]) : "memory");
          if (elect_one()) { TRACE2(128 + g); mbar_expect_tx(fb, STAGE); tma_2d(sa, &prm.ws[j], g * 64, t * 128, fb, pol<0>()); }
        }
        if (!((ready >> g) & 1)) {
          unsigned v;
          asm volatile("ld.volatile.shared.u32 %0, [%1];" : "=r"(v) : "r"(sb + POLL_OFF + lane * 4) : "memory");
          ready |= __ballot_sync(~0u, v == tgt) & ~15u;
          ensure(g);
        }
        if (elect_one()) {
          if (g < FK_NOMC) { tma_3d(sa + SLOT, &prm.n, g * 64, m4 * 4, fb, pol<4>()); tma_3d(sa + 2 * SLOT, &prm.n, g * 64, m4 * 4 + 2, fb, pol<4>()); }
          else tma_3d_mc(sa + SLOT + rank * SLOT, &prm.n, g * 64, m4 * 4 + rank * 2, fb, pol<4>());
          if (g >= FK_NA0 && g < 4) tma_2d(sa, &prm.ws[j], g * 64, t * 128, fb, pol<0>());
          TRACE2(64 + g);
        }
        if ((unsigned)(g - FK_WSPF) < 4u)
          asm volatile("prefetch.global.L2 [%0];" ::"l"(prm.wsp[j] + (size_t)(t * 128 + m4 * 32 + (g - FK_WSPF) * 8 + (lane >> 2)) * 4096 + 3584 + (lane & 3) * 128));
      }
      asm volatile("cp.async.wait_all;" ::: "memory");
    }
    asm volatile("" ::: "memory");
    if (warp == 1) {
      const uint32_t rb = sb + (m4 * 32 + lane) * 128 + ((lane & 7) << 4);
      float a0 = 0.f, a1 = 0.f, a2 = 0.f, a3 = 0.f;
#pragma unroll 1
      for (int g = 0; g < 32; g++) {
        const int s = g & 3;
        mbar_wait(BAR(B_FULL + s), (g >> 2) & 1);
        uint4 u[8];
#pragma unroll
        for (int c = 0; c < 8; c++) u[c] = lds128u((rb + s * STAGE) ^ (c << 4));
        u[7].x = __shfl_sync(~0u, u[7].x, lane);
        if (elect_one()) {
          mbar_arrive(BAR(B_EMPTY + s)); TRACE2(160 + g);
          if (g >= 8 && g < 18) prefetch_tmap(&prm.p + g - 8);
          if (FK_NP && g >= FK_G1 && (g - FK_G1) % FK_GP == 0 && (g - FK_G1) / FK_GP < FK_NP) prefetch_piece(4 + (g - FK_G1) / FK_GP);
          const int p = (g - FK_G0) >> FK_GS;
          if (g >= FK_G0 && !((g - FK_G0) & FK_GS) && (p < 8 ? moe && FK_TD == 1 : p < 12 && FK_TX)) {
            asm volatile("mbarrier.expect_tx.relaxed.cta.shared::cta.b64 [%0], 512;" ::"r"(BAR(B_RSDONE)) : "memory");
            tma_3d(sb + KEY_OFF, &prm.tch[p >> 3], p < 8 ? p : cgrp, p < 8 ? eb * 32 : t * 128 + (p - 8) * 32, BAR(B_RSDONE), POL_NORMAL);
          }
        }
#pragma unroll
        for (int c = 0; c < 8; c++) {
          a0 += bf_lo(u[c].x) + bf_lo(u[c].y); a1 += bf_hi(u[c].x) + bf_hi(u[c].y);
          a2 += bf_lo(u[c].z) + bf_lo(u[c].w); a3 += bf_hi(u[c].z) + bf_hi(u[c].w);
        }
      }
      if (lane == 0) mbar_arrive(BAR(B_RSDONE));
      mbar_wait(BAR(B_RSDONE), 0);
      st_msg8(&S->rs[j * S_ + t * 128 + m4 * 32 + lane], __float_as_uint((a0 + a1) + (a2 + a3)), tag);
    }
    asm volatile("" ::: "memory");
    if (warp >= 2) {
      float* const mod = S->mod[tag & 1];
      if (warp == 3) {
        const uint32_t stab = sb + TAB_OFF, stg = stab + 512;
        {
          const uint32_t cw = __ldg(reinterpret_cast<const uint32_t*>(cvec + t * 64) + lane);
          const uint32_t sp = pack_bf16(silu_f(bf_lo(cw)), silu_f(bf_hi(cw)));
          sts64u(stab + lane * 8, sp << 16, sp & 0xFFFF0000u);
        }
        float acc[8];
#pragma unroll
        for (int i = 0; i < 8; i++) acc[i] = 0.f;
#pragma unroll 1
        for (int n = -3; n < ((FK_X & 16) ? 8 : 24); n++) {
          if (n < ((FK_X & 16) ? 5 : 21) && elect_one()) {
            mbar_expect_tx(mf + (n & 3) * 8, 4096);
            tma_2d(ring + (n & 3) * 4096, &prm.wm, ((n + 3) >> 3) * 2048 + cgrp * 256, t * 64 + ((n + 3) & 7) * 8, mf + (n & 3) * 8, pol<1>());
          }
          if (n < 0) continue;
          const uint32_t sl = ring + ((n + 1) & 3) * 4096 + lane * 16;
          const float4 sv0 = lds128(stab + (n & 7) * 32), sv1 = lds128(stab + (n & 7) * 32 + 16);
          const float sc[8] = {sv0.x, sv0.y, sv0.z, sv0.w, sv1.x, sv1.y, sv1.z, sv1.w};
          mbar_wait(mf + ((n + 1) & 3) * 8, ((n + 1) >> 2) & 1);
          uint4 v[8];
#pragma unroll
          for (int u = 0; u < 8; u++) v[u] = lds128u(sl + u * 512);
#pragma unroll
          for (int u = 0; u < 8; u++) {
            acc[0] = fmaf(sc[u], bf_lo(v[u].x), acc[0]); acc[1] = fmaf(sc[u], bf_hi(v[u].x), acc[1]);
            acc[2] = fmaf(sc[u], bf_lo(v[u].y), acc[2]); acc[3] = fmaf(sc[u], bf_hi(v[u].y), acc[3]);
            acc[4] = fmaf(sc[u], bf_lo(v[u].z), acc[4]); acc[5] = fmaf(sc[u], bf_hi(v[u].z), acc[5]);
            acc[6] = fmaf(sc[u], bf_lo(v[u].w), acc[6]); acc[7] = fmaf(sc[u], bf_hi(v[u].w), acc[7]);
          }
          asm volatile("" : "+f"(acc[0]) :: "memory");
          if ((n & 7) == 7) {
            sts128(stg + lane * 32, acc[0], acc[1], acc[2], acc[3]); sts128(stg + lane * 32 + 16, acc[4], acc[5], acc[6], acc[7]);
#pragma unroll
            for (int i = 0; i < 8; i++) acc[i] = 0.f;
            fence_async_smem();
            if (elect_one()) {
              asm volatile("cp.reduce.async.bulk.global.shared::cta.bulk_group.add.f32 [%0], [%1], 1024;" ::"l"(mod + (n >> 3) * 2048 + cgrp * 256), "r"(stg) : "memory");
              bulk_commit();
              if (n != 15) { bulk_wait<0>(); rel_fence<2>(); red_add(&S->cntMod[n > 7 ? 32 : 0], 1); } else bulk_wait_read<0>();
              TRACE(n > 7 ? 34 + (n >> 3) : 9);
            }
          }
        }
      } else {
        wait_cnt(S->cntMod, tag * 128u);
        if (lane == 0) TRACE(10);
        float4 sa[8];
        {
          const float4 c0 = ldg_cg(mod + D_ + m4 * 256 + lane * 8), c1 = ldg_cg(mod + D_ + m4 * 256 + lane * 8 + 4);
#pragma unroll
          for (int i = 0; i < 8; i++) {
            const float4 sv = ldg_cg(mod + (i >> 1) * 256 + lane * 8 + (i & 1) * 4);
            const uint32_t s0 = pack_bf16(sv.x, sv.y), s1 = pack_bf16(sv.z, sv.w);
            sa[i] = make_float4(bf_lo(s0), bf_hi(s0), bf_lo(s1), bf_hi(s1));
          }
          const uint32_t cw[4] = {pack_bf16(c0.x, c0.y), pack_bf16(c0.z, c0.w), pack_bf16(c1.x, c1.y), pack_bf16(c1.z, c1.w)};
#pragma unroll
          for (int q = 0; q < 4; q++) sts32v(sb + T1_OFF + (lane >> 2) * 64 + q * 16 + (lane & 3) * 4, add_bf16x2(cw[q], 0x3F803F80u) ^ (j ? 0x80008000u : 0u));
        }
        float ul = 0.f;
#pragma unroll 1
        for (int r = 0; r < 8; r++) {
          if (r < 6 && elect_one()) {
            mbar_expect_tx(mf + ((nc + 2) & 3) * 8, 4096);
            bulk_load(ring + ((nc + 3) & 3) * 4096, src + (r + 2) * 2 * D_, 4096, mf + ((nc + 2) & 3) * 8, pol<2>());
          }
          mbar_wait(mf + (nc & 3) * 8, (nc >> 2) & 1); nc++;
          uint4 v[8];
          float u[4] = {0.f, 0.f, 0.f, 0.f};
#pragma unroll
          for (int i = 0; i < 8; i++) v[i] = lds128u(ring + (nc & 3) * 4096 + lane * 16 + i * 512);
#pragma unroll
          for (int i = 0; i < 8; i++) {
            const float4 s0 = sa[2 * (i & 3)], s1 = sa[2 * (i & 3) + 1];
            float &u0 = u[(i >> 2) * 2], &u1 = u[(i >> 2) * 2 + 1];
            u0 = fmaf(bf_lo(v[i].x), s0.x, u0); u1 = fmaf(bf_hi(v[i].x), s0.y, u1); u0 = fmaf(bf_lo(v[i].y), s0.z, u0); u1 = fmaf(bf_hi(v[i].y), s0.w, u1);
            u0 = fmaf(bf_lo(v[i].z), s1.x, u0); u1 = fmaf(bf_hi(v[i].z), s1.y, u1); u0 = fmaf(bf_lo(v[i].w), s1.z, u0); u1 = fmaf(bf_hi(v[i].w), s1.w, u1);
          }
          const float ua = u[0] + u[1], ub = u[2] + u[3];
          float us = ((lane & 1) ? ub : ua) + __shfl_xor_sync(~0u, (lane & 1) ? ua : ub, 1);
#pragma unroll
          for (int o = 16; o > 1; o >>= 1) us += __shfl_xor_sync(~0u, us, o);
          if ((lane >> 1) == r) ul = jw ? -us : us;
        }
        if (lane < 16) st_msg8(&S->u[jw * D_ + e0 + lane], __float_as_uint(ul), tag);
        if (lane == 0) TRACE(11);
#pragma unroll
        for (int i = 0; i < 4; i++) sts128u(ring + lane * 16 + i * 512, SENT, SENT, SENT, SENT);
        fence_async_smem();
        if (elect_one()) {
#pragma unroll 1
          for (int i = 0; i < 9; i++)
            bulk_store(i < 4 ? &S->part[b * 512 + i * 128] : i == 4 ? &S->stats[b * 128] : &S->rowsH[((i - 5) >> 1) * 4096 + (t * 2 + (i & 1)) * 128 + cgrp * 16], ring, i < 5 ? 2048 : 256);
          bulk_store(&S->flagP[b * 32], ring, 128);
          bulk_commit(); bulk_wait<0>();
        }
        if (lane == 12) S->claim[cl * 8] = 0;
        if (lane < 12) reinterpret_cast<float4*>(S->mod[~tag & 1] + b * 48)[lane] = make_float4(0.f, 0.f, 0.f, 0.f);
      }
      named_bar<1, 64>();
    }
    asm volatile("setmaxnreg.dec.sync.aligned.u32 40;" ::: "memory");
    if (warp == 2) {
      if (elect_one()) { rel_fence<4>(); mbar_arrive(BAR(B_RSDONE)); TRACE(30); }
      const int scl = blk_src(lane, cgrp);
      const unsigned* flagAddr = &S->flagP[(t * 8 + (scl >> 2)) * 32 + (scl & 3)];
      const unsigned* cellAddr = &S->flagP[(t * 8 + (lane & 7)) * 32];
      sts32v(sb + PFLAG_OFF + lane * 4, tag - 1);
      if (lane < 4) mbar_arrive(BAR(B_FULL2 + lane));
      mbar_wait(BAR(B_PREADY), 0);
      unsigned ready = 15;
      int u = 4, i7 = 0, kk = 0; uint32_t ph = 1;
#pragma unroll 1
      for (int q = 4; q < 32; q++) {
        const int src = FK_SKIP ? i7 + (i7 >= cgrp) : i7 == cgrp ? 7 : i7;
        if (!((ready >> q) & 1)) {
          unsigned v;
          asm volatile("ld.volatile.shared.u32 %0, [%1];" : "=r"(v) : "r"(sb + PFLAG_OFF + scl * 4) : "memory");
          ready |= __ballot_sync(~0u, v == tag);
          int it = 0;
          while (!((ready >> q) & 1)) {
            ready |= __ballot_sync(~0u, (unsigned)(lane - q) < 7u && ld_rlx(flagAddr) == tag);
            SPIN_CHECK(it);
          }
          fence_async_global();
        }
        if ((q & ~4) == 8) mbar_wait(BAR(B_PS - 2 + (q >> 2)), 0);
        mbar_wait(BAR(q >= 8 ? B_EMPTY2 + u : q == 4 ? B_EMPTY + 2 : B_FULL2 + u), ph);
        if (q >= 8) grid_wait();
        if (elect_one()) {
          TRACE3(128 + q);
          mbar_expect_tx(BAR(B_FULL2 + u), SLOT);
          tma_2d(sb + buf_off(u), &prm.p, (src >> 1) * 256 + kk * 64, (src & 1) * S_ + t * 128, BAR(B_FULL2 + u), pol<5>());
        }
        if (((~ready >> q) & 15) && lane < 8)
          asm volatile("cp.async.cg.shared.global [%0], [%1], 16;" ::"r"(sb + PFLAG_OFF + lane * 16), "l"(cellAddr) : "memory");
        if (++u == 5) { u = 0; ph ^= 1; }
        if (++i7 == 7) { i7 = 0; kk++; }
      }
      asm volatile("cp.async.wait_all;" ::: "memory");
    }
    asm volatile("" ::: "memory");
    if (warp == 0) {
      int u = 0; uint32_t ph = 1;
#pragma unroll 1
      for (int q = 0; q < 32; q++) {
        const int sc = blk_src(q, cgrp);
        mbar_wait(BAR(q >= 5 ? B_EMPTY2 + u : q < 2 ? B_ADONE : q == 4 ? B_EMPTY + 3 : B_EMPTY + 1), q >= 2 ? ph : 0);
        if (elect_one()) {
          TRACE3(160 + q);
          mbar_expect_tx(BAR(B_FULL2 + u), SLOT);
          tma_2d_mc(sb + buf_off(u) + SLOT + rank * 8192, &prm.wd[(sc >> 2) & 1], (sc >> 3) * 256 + (sc & 3) * 64, cgrp * 128 + rank * 64, BAR(B_FULL2 + u), pol<6>());
          if (q & 1) { const int p = 4 + FK_NA + FK_NP + ((q - FK_QP) >> 1); if (q >= FK_QP && p < (FK_TD ? 16 : 24)) prefetch_piece(p);
            else if (FK_TD == 3 && moe && p >= 16 && p < 24) {
              asm volatile("mbarrier.expect_tx.relaxed.cta.shared::cta.b64 [%0], 512;" ::"r"(BAR(B_B27)) : "memory");
              tma_3d(sb + KEY_OFF, &prm.tch[0], p - 16, eb * 32, BAR(B_B27), POL_NORMAL);
            } }
          else if (q >= 10 && q < 2 * FK_NL + 2) weight_box((q >> 1) - 1, BAR(B_FULL2 + (u == 4 ? 0 : u + 1)));
        }
        if (++u == 5) { u = 0; ph ^= 1; }
      }
      if (elect_one()) {
#pragma unroll 1
        for (int n = FK_NL; n < 15; n++) weight_box(n, BAR(B_WF));
        mbar_expect_tx(BAR(B_DN), moe ? 65536 : 0);
#pragma unroll 1
        for (int i = 0; i < 9; i++) {
          if ((i & 3) == 0) mbar_wait(BAR(B_EMPTY2 + 2 + (i >> 2)), 1);
          if (i == 0) { mbar_arrive(BAR(B_B27)); weight_box(15, BAR(B_WF)); mbar_arrive(BAR(B_WF)); }
          else if (moe)
            asm volatile("cp.async.bulk.tensor.5d.shared::cluster.global.mbarrier::complete_tx::bytes.L2::cache_hint [%0], [%1, {0, 0, 0, %3, %4}], [%2], %5;"
                         ::"r"(sb + RKA_OFF + (i + (i >> 3) * 4) * 8192), "l"(&prm.wdn), "r"(BAR(B_DN)), "r"(eb * 2), "r"(i * 2 - 2), "l"(pol<3>()) : "memory");
        }
      }
    }
    asm volatile("" ::: "memory");
    if (warp == 1) {
      if (elect_one()) {
#pragma unroll 1
        for (int kk = 0; kk < 4; kk++) {
          mbar_wait(BAR(B_PREADY + kk), 0);
#pragma unroll 1
          for (int i = 0; i < 4; i++) {
            tma_store_2d(&prm.ps, sb + pstage(kk) + i * 4096, m4 * 256 + kk * 64, j * S_ + t * 128 + i * 32);
            if (kk >= FK_PS0 && i < 3) { const unsigned next = clk32() + FK_PSPACE; while ((int)(clk32() - next) < 0) __nanosleep(20); }
          }
          bulk_commit(); bulk_wait<0>();
          if (kk < 2) mbar_arrive(BAR(B_PS + kk));
          rel_fence<3>();
          st_rlx(&S->flagP[b * 32 + kk], tag);
          TRACE(40 + kk); TRACE3(128 + kk);
        }
        if (FK_XD) { const unsigned next = clk32() + FK_XD; while ((int)(clk32() - next) < 0) __nanosleep(20); }
        mbar_expect_tx(BAR(B_EFULL), (FK_X & 4) ? 0 : 32768);
#pragma unroll 1
        for (int i = 0; i < 8; i++) {
          if (!(FK_X & 4)) tma_3d(sb + E_OFF + i * 4096, &prm.xm, t * 128 + i * 16, cgrp * 2, BAR(B_EFULL), pol<8>());
          const unsigned next = clk32() + FK_SPACE;
          while ((int)(clk32() - next) < 0) __nanosleep(20);
        }
      }
      __syncwarp();
    }
    asm volatile("" ::: "memory");
    if (warp == 3) {
      if (elect_one()) {
        fence_async_smem();
        unsigned next = clk32();
#pragma unroll 1
        for (int n = 0; n < 4 + FK_NA + (FK_TD == 2) * 8; n++) {
          if (n < 4) weight_box(n, BAR(B_WF));
          else if (n < 4 + FK_NA) prefetch_piece(n + FK_NP);
          else if (moe) {
            asm volatile("mbarrier.expect_tx.relaxed.cta.shared::cta.b64 [%0], 512;" ::"r"(BAR(B_TAB)) : "memory");
            tma_3d(sb + KEY_OFF, &prm.tch[0], n - 4 - FK_NA, eb * 32, BAR(B_TAB), POL_NORMAL);
          }
          if (n == 3) mbar_arrive(BAR(B_WF));
          if (!FK_TX && (unsigned)(n - FK_XN) < 4u) pf_bulk(x + (size_t)(b * 16 + (n - FK_XN) * 4) * D_, 8192);
          next += FK_PACE;
          while ((int)(clk32() - next) < 0) __nanosleep(20);
        }
        TRACE(37);
      }
      __syncwarp();
      int it = 0;
      if (!(FK_X & 16)) wait_cnt(&S->cntMod[32], tag * 128u);
      mbar_wait(BAR(B_PREADY + 2), 0);
      {
        const float* mp = S->mod[tag & 1] + cgrp * 128 + lane * 4;
        const float4 ga = ldg_cg(mp + 2 * D_), sv = ldg_cg(mp + 3 * D_), cb = ldg_cg(mp + 4 * D_), gb = ldg_cg(mp + 5 * D_);
        const uint2 wr = __ldg(reinterpret_cast<const uint2*>(prm.w_r + cgrp * 128 + lane * 4));
        const uint32_t Aa = add_bf16x2(pack_bf16(cb.x, cb.y), 0x3F803F80u), Ab = add_bf16x2(pack_bf16(cb.z, cb.w), 0x3F803F80u);
        const uint32_t Sa = pack_bf16(sv.x, sv.y), Sb = pack_bf16(sv.z, sv.w), Ga = pack_bf16(gb.x, gb.y), Gb = pack_bf16(gb.z, gb.w);
        const float w0 = bf_lo(Aa) * bf_lo(wr.x), w1 = bf_hi(Aa) * bf_hi(wr.x), w2 = bf_lo(Ab) * bf_lo(wr.y), w3 = bf_hi(Ab) * bf_hi(wr.y);
        const uint32_t tb = sb + TAB_OFF + (lane >> 3) * 64 + (lane & 1) * 32 + ((lane >> 1) & 3) * 4, Wa = pack_bf16(w0, w1), Wb = pack_bf16(w2, w3);
        auto put = [&](int off, uint32_t a, uint32_t c) { sts32v(tb + off, a); sts32v(tb + off + 16, c); };
        put(T_WH, Wa, Wb); put(T_ONE, 0x3F803F80u, 0x3F803F80u);
        put(T_WL, pack_bf16(w0 - bf_lo(Wa), w1 - bf_hi(Wa)), pack_bf16(w2 - bf_lo(Wb), w3 - bf_hi(Wb)));
        put(T_GA, pack_bf16(ga.x, ga.y), pack_bf16(ga.z, ga.w)); put(T_A, Aa, Ab); put(T_S, Sa, Sb); put(T_G, Ga, Gb);
        float c1 = (w0 + w1) + (w2 + w3), c2 = (bf_lo(Sa) * bf_lo(wr.x) + bf_hi(Sa) * bf_hi(wr.x)) + (bf_lo(Sb) * bf_lo(wr.y) + bf_hi(Sb) * bf_hi(wr.y));
#pragma unroll 1
        for (int h = 0; h < 2; h++) {
#pragma unroll
          for (int o = 16; o; o >>= 1) { c1 += __shfl_xor_sync(~0u, c1, o); c2 += __shfl_xor_sync(~0u, c2, o); }
          if (h) break;
          if (t == 0 && lane == 0) st_msg(&S->cst[cgrp], __float_as_uint(c1), __float_as_uint(c2), tag, 0);
          uint4 cm; it = 0;
          while (true) {
            cm = ld_msg(&S->cst[lane & 7]);
            if (__all_sync(~0u, cm.z == tag)) break;
            SPIN_CHECK(it); __nanosleep(200);
          }
          c1 = 0.25f * __uint_as_float(cm.x); c2 = 0.25f * __uint_as_float(cm.y);
        }
        if (lane == 0) { sts128u(sb + CST_OFF, __float_as_uint(c1), __float_as_uint(c2), tag, b | eb << 8 | (int)moe << 16); TRACE(27); }
      }
    }
    asm volatile("" ::: "memory");
    if (warp & 1) {
      const uint2* src = (warp == 3 ? &S->u[cgrp * 128] : &S->rs[t * 128]) + lane;
      const uint2* src1 = src + (warp == 3 ? D_ : S_);
      uint2 m[8]; int it = 0;
      while (true) {
        bool ok = true;
#pragma unroll
        for (int i = 0; i < 8; i++) { m[i] = ld_msg8(((i & 1) ? src1 : src) + (i >> 1) * 32); ok &= m[i].y == tag; }
        if (__all_sync(~0u, ok)) break;
        SPIN_CHECK(it);
      }
      uint32_t rk[12];
#pragma unroll
      for (int i = 0; i < 4; i++) {
        const float r0 = __uint_as_float(m[2 * i].x) * (warp == 3 ? 0.5f : 1.f), r1 = __uint_as_float(m[2 * i + 1].x) * (warp == 3 ? 0.5f : 1.f);
        const uint32_t hi = pack_bf16(r0, r1), lo = pack_bf16(r0 - bf_lo(hi), r1 - bf_hi(hi));
        rk[3 * i] = hi; rk[3 * i + 1] = warp == 3 ? hi : lo; rk[3 * i + 2] = warp == 3 ? lo : hi;
      }
      mbar_wait(BAR(B_B27), 0);
#pragma unroll
      for (int i = 0; i < 4; i++) sts128u(sb + RKA_OFF + (warp & 2) * 1024 + (i * 32 + lane) * 16, rk[3 * i], rk[3 * i + 1], rk[3 * i + 2], 0);
      fence_async_smem();
      if (elect_one()) { mbar_arrive(BAR(B_TAB)); TRACE(26); }
    }
    asm volatile("" ::: "memory");
    if (warp == 1) {
      mbar_wait(BAR(B_PREADY), 1);
      if (lane == 0) TRACE(60);
      const int lr = lds32u(sb + BK_OFF + (lane >> 4) * 4);
      {
        const uint4 v = lds128u(sb + E_OFF + (lr >> 4) * 4096 + (lane & 8) * 256 + (lr & 15) * 128 + (((lane ^ lr) & 7) << 4));
        st_msg(&S->rowsB[(t * 2 + (lane >> 4)) * 128 + cgrp * 16 + (lane & 15)], v.x, v.y, v.z, v.w);
      }
      const unsigned cmask = __reduce_or_sync(~0u, 1u << (lr >> 4)) | FK_OMASK;
      unsigned todo = ~cmask & 255, smask = 0;
      int r1 = 0, r2 = 0;
#pragma unroll 1
      for (int h = 0; h < 2; h++) {
        if (elect_one()) {
#pragma unroll 1
          for (; todo; todo &= todo - 1) {
            const int i = __ffs(todo) - 1;
            asm volatile("cp.async.bulk.tensor.3d.global.shared::cta.bulk_group.L2::cache_hint [%0, {0, %2, %3}], [%1], %4;"
                         ::"l"(&prm.om), "r"(sb + E_OFF + i * 4096), "r"(t * 128 + i * 16), "r"(cgrp * 2), "l"(pol<9>()) : "memory");
            if (h == 0) {
              const unsigned c0 = clk32();
              uint32_t sel;
              do {
                asm volatile("{\n.reg .pred p;\nmbarrier.test_wait.parity.shared::cta.b64 p, [%1], 1;\nselp.u32 %0, 1, 0, p;\n}" : "=r"(sel) : "r"(BAR(B_B27)) : "memory");
              } while (!sel && clk32() - c0 < FK_OSPACE);
            }
          }
          TRACE(61 + h);
        }
        if (h) break;
        mbar_wait(BAR(B_B27), 1);
        r1 = lds32u(sb + SEL_OFF) - t * 128; r2 = lds32u(sb + SEL_OFF + 4) - t * 128;
        smask = ((unsigned)r1 < 128u ? 1u << (r1 >> 4) : 0) | ((unsigned)r2 < 128u ? 1u << (r2 >> 4) : 0);
        todo = cmask & ~smask;
        if (FK_ODELAY) spin(FK_ODELAY);
      }
#pragma unroll 1
      for (; smask; smask &= smask - 1) {
        const int i = __ffs(smask) - 1;
#pragma unroll 2
        for (int r = lane >> 4; r < 16; r += 2) {
          const uint4 v = lds128u(sb + E_OFF + i * 4096 + (lane & 8) * 256 + r * 128 + (((lane ^ r) & 7) << 4));
          if (i * 16 + r != r1 && i * 16 + r != r2) reinterpret_cast<uint4*>(out + (size_t)(t * 128 + i * 16 + r) * D_)[cgrp * 16 + (lane & 15)] = v;
        }
      }
      if (elect_one()) { bulk_commit(); bulk_wait_read<0>(); TRACE(29); }
    }
    asm volatile("" ::: "memory");
    if (warp == 2) {
      const uint4* cp = &S->cand[(lane >> 1) * 8];
      mbar_wait(BAR(B_B27), 0);
      uint4 m = ld_msg(cp);
      bool ok = __all_sync(~0u, m.z == tag);
      named_bar<5, 288>();
      uint32_t k1, k2;
      {
        const uint4 k4 = lds128u(sb + KEY_OFF + lane * 16);
        const uint32_t ka = max(k4.x, k4.y), kb = max(k4.z, k4.w), m1 = max(ka, kb), m2 = max(min(ka, kb), ka > kb ? min(k4.x, k4.y) : min(k4.z, k4.w));
        k1 = redux_max(m1); k2 = redux_max(m1 == k1 ? m2 : m1);
        if (lane == 0) { st_msg(&S->cand[t * 8], k1, k2, tag, 0); sts64u(sb + BK_OFF, key_row(k1) & 127, key_row(k2) & 127); mbar_arrive(BAR(B_BK)); TRACE(13); }
      }
      int it = 0;
      while (!ok) {
        m = ld_msg(cp);
        ok = __all_sync(~0u, m.z == tag);
        SPIN_CHECK(it);
      }
      warp_top2((lane & 1) ? m.y : m.x, k1, k2);
      const int r1 = key_row(k1), r2 = key_row(k2), slot1 = (r1 >> 7) * 2, slot2 = (r2 >> 7) * 2 + ((r1 >> 7) == (r2 >> 7));
      if (elect_one()) {
        if (moe) {
          fence_async_global();
          bulk_load(sb + H_OFF, &S->rowsH[slot1 * 128], 2048, BAR(B_ROWS), POL_NORMAL);
          bulk_load(sb + H_OFF + 2112, &S->rowsH[slot2 * 128], 2048, BAR(B_ROWS), POL_NORMAL);
        }
        sts64u(sb + SEL_OFF, r1, r2); sts64u(sb + SEL_OFF + 8, slot1 * 2048, slot2 * 2048);
        mbar_expect_tx(BAR(B_ROWS), moe ? 4096 : 0);
        mbar_arrive(BAR(B_B27));
        TRACE(14);
      }
      const int fcol = (b >> 1) * 16 + (lane & 15);
      const float gb = round_bf16(__uint_as_float(ld_rlx(S->mod[tag & 1] + 5 * D_ + fcol)));
      const uint32_t* fbp = reinterpret_cast<const uint32_t*>(&S->rowsB[((b & 1) ? slot2 : slot1) * 128]) + (fcol >> 1);
      uint32_t fb;
      do { fb = ld_rlx(fbp); SPIN_CHECK(it); } while (fb == SENT);
      sts64u(sb + PFLAG_OFF + (lane & 15) * 8, (lane & 1) ? fb & 0xFFFF0000u : fb << 16, __float_as_uint(gb));
      __syncwarp();
      if (lane == 0) {
        sts32(sb + CST_OFF, round_bf16(sigmoid_f(round_bf16(fkey_inv((((b & 1) ? k2 : k1) & ~2047u) | 1024u)))));
        mbar_arrive(BAR(B_FIN));
        if (b == 0) S->epoch[0] = tag;
      }
    }
  } else {
    const int cw = (warp - 4) >> 2;
    const int cwarp = warp - 4;
    const bool elect = (tid & 127) == 0;
    uint32_t rel;
    asm volatile("mapa.shared::cluster.u32 %0, %1, %2;" : "=r"(rel) : "r"(BAR(0)), "r"(tid & 1));
    if (tid & 126) rel = 0;
    asm volatile("" : "+r"(rel));
    auto release = [&](int bar) {
      asm volatile("{\n.reg .pred p;\nsetp.ne.u32 p, %1, 0;\n@p mbarrier.arrive.shared::cluster.b64 _, [%0];\n}" ::"r"(rel + bar * 8), "r"(rel) : "memory");
    };
    const uint32_t da0 = desc_lo(sb + cw * 8192, 16), db0 = desc_lo(sb + SLOT, 8192), db2 = desc_lo(sb + SLOT, 16);

    if (FK_S) {
      const int r = (tid - 128) >> 2;
      const uint32_t base = sb + SLOT + (tid & 3) * 8192 + r * 128 + ((((tid & 3) * 2) | (r & 1)) << 4);
      mbar_wait(BAR(B_FULL), 0);
      uint4 v[8];
#pragma unroll
      for (int c = 0; c < 8; c++) v[c] = lds128u(base ^ (c << 4));
      uint4 m = ld_msg(&S->st0[r * 2]);
      int it = 0;
      while (!__all_sync(~0u, m.z == tag)) { m = ld_msg(&S->st0[r * 2]); SPIN_CHECK(it); }
      if (tid == 128) TRACE(63);
      const float rs = __uint_as_float(m.x), nm = __uint_as_float(m.y);
#pragma unroll
      for (int c = 0; c < 8; c++)
        sts128u(base ^ (c << 4), pack_bf16(fmaf(bf_lo(v[c].x), rs, nm), fmaf(bf_hi(v[c].x), rs, nm)), pack_bf16(fmaf(bf_lo(v[c].y), rs, nm), fmaf(bf_hi(v[c].y), rs, nm)),
                pack_bf16(fmaf(bf_lo(v[c].z), rs, nm), fmaf(bf_hi(v[c].z), rs, nm)), pack_bf16(fmaf(bf_lo(v[c].w), rs, nm), fmaf(bf_hi(v[c].w), rs, nm)));
      fence_async_smem();
      named_bar<2, 256>();
    }
    uint32_t wf[64], uf[64], df[64];
    uint32_t pk[64];
    uint32_t xw[32];
    float lo[64];
    int ln;
    uint32_t so, wo;
    auto p_ready = [&](int kk) { fence_async_smem(); if (elect_one()) mbar_arrive(BAR(B_PREADY + kk)); };
    {
      float pa[64], pb[64];
      {
        float acc[128];
#pragma unroll 1
        for (int g = 0; g < 28; g++) {
          const int s = g & 3;
          mbar_wait(BAR(B_FULL + s), (g >> 2) & 1);
          const uint32_t da = da0 + s * (STAGE >> 4), db = db0 + s * (STAGE >> 4);
          wg_fence();
          wgmma_n256<1>(acc, da, db, g > 0);
#pragma unroll
          for (int k = 1; k < 4; k++) wgmma_n256<1>(acc, da + k * 2, db + k * 128, 1);
          wg_commit();
          wg_wait<1>();
          if (g > 0) { release(B_EMPTY + ((g - 1) & 3)); if (elect) TRACE2(191 + g + cw * 32); }
          STAMP2(g);
        }
        wg_wait<0>();
        release(B_EMPTY + 3);
#pragma unroll
        for (int i = 0; i < 64; i++) {
          asm volatile("mov.b32 %0, %1;" : "=f"(pa[i]) : "f"(acc[i]));
          asm volatile("mov.b32 %0, %1;" : "=f"(pb[i]) : "f"(acc[64 + i]));
        }
      }
      if (elect) TRACE(3 + tr);
      STAMP2(28);
#pragma unroll 1
      for (int s = 0; s < 4; s++) {
        mbar_wait(BAR(B_FULL + s), 1);
        wg_fence();
#pragma unroll
        for (int k = 0; k < 4; k++) wgmma_n128<1>(pa, da0 + s * (STAGE >> 4) + k * 2, db0 + s * (STAGE >> 4) + k * 128);
        wg_commit();
        if (s == 2) { wg_wait<1>(); if (elect) mbar_arrive(BAR(B_A29)); }
      }
      auto b_block = [&](int s) {
        wg_fence();
#pragma unroll
        for (int k = 0; k < 4; k++) wgmma_n128<1>(pb, da0 + s * (STAGE >> 4) + k * 2, db0 + s * (STAGE >> 4) + 1024 + k * 128);
        wg_commit();
      };
      uint4 t0, t1;
      auto load_t = [&](int kk) { t0 = lds128u(sb + T1_OFF + kk * 128 + (ln & 3) * 16); t1 = lds128u(sb + T1_OFF + kk * 128 + 64 + (ln & 3) * 16); };
      auto pack_p = [&](int kk, const float* a) {
        const uint32_t A[8] = {t0.x, t0.y, t0.z, t0.w, t1.x, t1.y, t1.z, t1.w};
#pragma unroll
        for (int i = 0; i < 16; i++) pk[kk * 16 + i] = mul_bf16x2(pack_bf16(a[2 * i], a[2 * i + 1]), A[i >> 1]);
      };
      auto stage_p = [&](int kk) {
#pragma unroll
        for (int k = 0; k < 4; k++) stsm_x4((so ^ (k << 5)) + pstage(kk), pk + kk * 16 + k * 4);
      };
      auto own_block = [&](int q) {
        const uint32_t db = db2 + (buf_off(q) >> 4);
        wg_fence();
        if (q == 0) wgmma_n128_rs<0>(lo, pk, db); else wgmma_n128_rs<1>(lo, pk + q * 16, db);
#pragma unroll
        for (int k = 1; k < 4; k++) wgmma_n128_rs<1>(lo, pk + q * 16 + k * 4, db + k * 2);
        wg_commit();
      };
      b_block(0);
      mbar_wait(BAR(B_RSDONE), 0);
      asm volatile("setmaxnreg.inc.sync.aligned.u32 232;" ::: "memory");
      asm volatile("mov.u32 %0, %%laneid;" : "=r"(ln));
      so = sb + (uint32_t)(cwarp * 16 + (ln & 15)) * 128 + (((ln >> 4) ^ (ln & 7)) << 4);
      wo = sb + SP_OFF + cwarp * 1024 + ((ln & 7) + (ln >> 4) * 8) * 64 + ((((ln >> 3) & 1) ^ ((ln >> 1) & 3)) << 4);
      mbar_wait(BAR(B_A29), 0);
      load_t(0);
      wg_wait<1>();
      reg_fence(pa);
      release(B_ADONE);
      if (elect) TRACE(4 + tr);
      STAMP2(29);
      pack_p(0, pa); stage_p(0);
      if (FK_TR0) { p_ready(0); b_block(1); } else { b_block(1); p_ready(0); }
      if (elect) TRACE(2 + tr);
      wg_wait<1>(); release(B_EMPTY);
      load_t(1);
      b_block(2);
      pack_p(1, pa + 32);
      wg_wait<1>(); release(B_EMPTY + 1);
      STAMP2(30);
      load_t(2);
      b_block(3);
      mbar_wait(BAR(B_FULL2), 0);
      wg_wait<1>(); release(B_EMPTY + 2);
      if (FK_S1 == 0) { mbar_wait(BAR(B_ADONE), 0); stage_p(1); }
      own_block(0);
      if (FK_S1 == 0) p_ready(1);
      mbar_wait(BAR(B_FULL2 + 1), 0);
      if (FK_S1 == 1) mbar_wait(BAR(B_ADONE), 0);
      wg_wait<1>(); release(B_EMPTY + 3);
      reg_fence(pb);
      if (elect) TRACE(1 + tr);
      STAMP2(31);
      if (FK_S1 == 1) stage_p(1);
      own_block(1);
      if (FK_S1 == 1) p_ready(1);
      pack_p(2, pb);
      mbar_wait(BAR(B_FULL2 + 2), 0);
      wg_wait<1>(); release(B_EMPTY2);
      STAMP2(32);
      load_t(3);
      own_block(2);
      pack_p(3, pb + 32);
      mbar_wait(BAR(B_EMPTY + 3), 1);
      mbar_wait(BAR(B_FULL2 + 3), 0);
      wg_wait<1>(); release(B_EMPTY2 + 1);
      STAMP2(33);
      if (FK_S1 == 3) stage_p(1);
      own_block(3);
      if (FK_S1 == 3) p_ready(1);
      mbar_wait(BAR(B_WF), 0);
      wg_wait<1>(); release(B_EMPTY2 + 2);
      STAMP2(34);
    }
    {
      mbar_wait(BAR(B_FULL2 + 4), 0);
#pragma unroll
      for (int q = 4; q < 32; q++) {
        const uint32_t da = da0 + (buf_off(q % 5) >> 4) + (q << 16), db = db2 + (buf_off(q % 5) >> 4) + (q << 16);
        wg_fence();
#pragma unroll
        for (int k = 0; k < 4; k++) wgmma_n128<0>(lo, da + k * 2, db + k * 2);
        if (q == FK_QR) wgmma_n128<0, 8>(lo, desc_lo(sb + RKA_OFF, 0) + (cwarp & 4) * 16, desc_lo(sb + RKB_OFF, 0));
        wg_commit();
        if (q == 31) break;
        if (q + 1 == FK_QR) mbar_wait(BAR(B_TAB), 0);
        if (FK_ORD == 1) { wg_wait<1>(); if (q == 28 && rel) rel = BAR(0); release(B_EMPTY2 + (q - 1) % 5); STAMP2(31 + q); }
        if (q == 8 || q == 14) p_ready(q >> 2);
        if (q == 27) mbar_wait(BAR(B_EFULL), 0);
        mbar_wait(BAR(B_FULL2 + (q + 1) % 5), ((q + 1) / 5) & 1);
        if (q >= 27) {
#pragma unroll
          for (int h = 0; h < 2; h++) ldsm_x4((so ^ ((q - 27) << 5)) + E_OFF + cwarp * 2048 + h * 2048, xw + (q - 27) * 4 + h * 16);
        } else if (!(q & 1)) {
          const int n = (q - 4) >> 1;
#pragma unroll
          for (int h = 0; h < 2; h++) ldsm_x4_t((wo ^ (h << 5)) + (n & 3) * 8192, (n < 8 ? wf + n * 8 : uf + (n - 8) * 8) + h * 4);
        } else if (q < 15 && q != 9) {
          const int i = (q - 5 - (q > 9) * 2) >> 1;
#pragma unroll
          for (int h = 0; h < 2; h++) stsm_x4((so ^ (((i & 1) * 2 + h) << 5)) + pstage(2 + (i >> 1)), pk + 32 + i * 8 + h * 4);
        }
        if (FK_ORD == 0) { wg_wait<1>(); if (q == 28 && rel) rel = BAR(0); release(B_EMPTY2 + (q - 1) % 5); STAMP2(31 + q); }
      }
    }
    if (FK_QR == 32) {
      mbar_wait(BAR(B_TAB), 0);
      wg_fence();
      wgmma_n128<0, 8>(lo, desc_lo(sb + RKA_OFF, 0) + (cwarp & 4) * 16, desc_lo(sb + RKB_OFF, 0));
      wg_commit();
    }
    const int gq = ln >> 2, q4 = ln & 3, row0 = cwarp * 16 + gq;
    const bool odd = ln & 1;
    const uint32_t role = lds32u(sb + CST_OFF + 12), bq = role & 255;
    uint32_t tq = sb + TAB_OFF + q4 * 16, tb = tq + (gq & 1) * T_ONE + (gq & 2) * (T_WL / 2);
    const uint4* src = &S->stats[((bq & ~7) + (q4 >> 1) * 4) * 128 + row0 + 8 * (q4 & 1)];
    uint4* sdst = &S->stats[bq * 128 + row0 + 8 * q4];
    asm volatile("" : "+r"(tq), "+r"(tb), "+l"(src), "+l"(sdst));
    {
      uint4 gw[4];
#pragma unroll
      for (int a = 0; a < 4; a++) gw[a] = lds128u(tq + T_GA + a * 64);
      wg_wait<0>();
      reg_fence(lo);
      STAMP(0);
      if (elect) { TRACE(7 + tr); if (cw == 0) TRACE_CLK(121); }
      float c[2][4], e0[2][4], e1[2][4];
#pragma unroll
      for (int i = 0; i < 4; i++) c[0][i] = c[1][i] = e0[0][i] = e0[1][i] = e1[0][i] = e1[1][i] = 0.f;
#pragma unroll
      for (int a = 0; a < 4; a++) {
        const uint4 bw = lds128u(tb + a * 64);
        const uint32_t g[4] = {gw[a].x, gw[a].y, gw[a].z, gw[a].w};
#pragma unroll
        for (int i = 0; i < 8; i++) xw[a * 8 + i] = fma_bf16x2(g[i >> 1], pack_bf16(lo[a * 16 + 2 * i], lo[a * 16 + 2 * i + 1]), xw[a * 8 + i]);
#pragma unroll
        for (int h = 0; h < 2; h++) {
          const uint32_t* w = xw + a * 8 + h * 4;
          mma_1688(e0[0], w[0], w[1], w[0]); mma_1688(e1[0], w[0], w[1], w[1]); mma_1688(e0[1], w[2], w[3], w[2]); mma_1688(e1[1], w[2], w[3], w[3]);
          mma_16816(c[h], w, h ? bw.z : bw.x, h ? bw.w : bw.y);
        }
      }
      const float c0 = c[0][0] + c[1][0], c2 = c[0][2] + c[1][2];
      const float q0 = (gq & 1) ? e0[0][1] + e0[1][1] : e0[0][0] + e0[1][0], q1 = (gq & 1) ? e1[0][3] + e1[1][3] : e1[0][2] + e1[1][2];
      const int dl = (ln & ~3) | (gq >> 1);
      const float da = (odd ? c2 : c0) + __shfl_xor_sync(~0u, odd ? c0 : c2, 1), s1 = __shfl_xor_sync(~0u, c[0][3] + c[1][3], 1);
      const float qa = __shfl_sync(~0u, q0, dl), qb = __shfl_sync(~0u, q1, dl);
      if (q4 < 2) st_msg(sdst, __float_as_uint(odd ? s1 : c[0][1] + c[1][1]), __float_as_uint(odd ? qb : qa), __float_as_uint(da), 0);
    }
    if (elect) TRACE(8 + tr);
    STAMP(1);
    {
      uint4 m[4], tA[4], tS[4];
      if (FK_H1 < 3) mbar_wait(BAR(B_WF), 1); else mbar_wait(BAR(B_TAB), 0);
      if (FK_H1 == 0) {
#pragma unroll
        for (int i = 0; i < 4; i++) m[i] = ld_msg(src + 128 * i);
      }
      const float2 cst = lds64(sb + CST_OFF);
      if (FK_H1 < 3) {
#pragma unroll
        for (int i = 0; i < 8; i++) ldsm_x4_t((wo ^ ((i & 1) << 5)) + (i >> 1) * 8192, uf + 32 + i * 4);
      }
      if (FK_H1 != 1) {
#pragma unroll
        for (int a = 0; a < 4; a++) { tA[a] = lds128u(tq + T_A + a * 64); tS[a] = lds128u(tq + T_S + a * 64); }
      }
      uint32_t kaddr = sb + KEY_OFF + (row0 + 8 * (q4 & 1)) * 4, kidx = 2047 - ((bq >> 3) * 128 + row0 + 8 * (q4 & 1));
      asm volatile("" : "+r"(kaddr), "+r"(kidx));
      STAMP(2);
      if (FK_H1) {
        uint32_t one;
        asm volatile("ld.volatile.shared.u32 %0, [%1];" : "=r"(one) : "r"(sb + TAB_OFF + T_ONE) : "memory");
        src += one >> 31;
#pragma unroll
        for (int i = 0; i < 4; i++) m[i] = ld_msg(src + 128 * i);
      }
      {
        int it = 0;
        while (!__all_sync(~0u, (m[0].w | m[1].w | m[2].w | m[3].w) == 0)) {
#pragma unroll
          for (int i = 0; i < 4; i++) m[i] = ld_msg(src + 128 * i);
          SPIN_CHECK(it);
        }
      }
      STAMP(3);
      float sa = (__uint_as_float(m[0].x) + __uint_as_float(m[1].x)) + (__uint_as_float(m[2].x) + __uint_as_float(m[3].x));
      float qa = (__uint_as_float(m[0].y) + __uint_as_float(m[1].y)) + (__uint_as_float(m[2].y) + __uint_as_float(m[3].y));
      float da = (__uint_as_float(m[0].z) + __uint_as_float(m[1].z)) + (__uint_as_float(m[2].z) + __uint_as_float(m[3].z));
      sa += __shfl_xor_sync(~0u, sa, 2); qa += __shfl_xor_sync(~0u, qa, 2); da += __shfl_xor_sync(~0u, da, 2);
      const float mean = sa * (1.f / D_);
      const float rs = rsqrt_f(fmaxf(fmaf(-mean, mean, qa * (1.f / D_)), 0.f) + 1e-5f);
      sts32v(kaddr, (fkey(fmaf(rs, fmaf(-mean, cst.x, da), cst.y)) & ~2047u) | kidx);
      uint32_t one;
      asm volatile("bar.arrive 5, 288;\nld.volatile.shared.u32 %0, [%1];" : "=r"(one) : "r"(sb + TAB_OFF + T_ONE) : "memory");
      if (tid == 128) TRACE(12 + 16);
      STAMP(4);
      if (FK_H1 == 1) {
#pragma unroll
        for (int a = 0; a < 4; a++) { tA[a] = lds128u(tq + T_A + a * 64); tS[a] = lds128u(tq + T_S + a * 64); }
      }
      const uint32_t h0 = pack_bf16(rs, rs), l0 = mul_bf16x2(pack_bf16(rs - bf_lo(h0), -mean * rs), one), hx = __shfl_xor_sync(~0u, h0, 1), lx = __shfl_xor_sync(~0u, l0, 1);
      const uint32_t rh[2] = {odd ? hx : h0, odd ? h0 : hx};
      const uint32_t rl[2] = {__byte_perm(odd ? lx : l0, 0, 0x1010), __byte_perm(odd ? l0 : lx, 0, 0x1010)};
      const uint32_t nm[2] = {__byte_perm(odd ? lx : l0, 0, 0x3232), __byte_perm(odd ? l0 : lx, 0, 0x3232)};
      uint32_t h[32];
#pragma unroll
      for (int a = 0; a < 4; a++) {
        const uint32_t A[4] = {tA[a].x, tA[a].y, tA[a].z, tA[a].w}, B[4] = {tS[a].x, tS[a].y, tS[a].z, tS[a].w};
#pragma unroll
        for (int i = 0; i < 8; i++) {
          const uint32_t w = xw[a * 8 + (i & 3) * 2 + (i >> 2)];
          h[a * 8 + i] = fma_bf16x2(fma_bf16x2(w, rh[i >> 2], fma_bf16x2(w, rl[i >> 2], nm[i >> 2])), A[i & 3], B[i & 3]);
        }
      }
      uint4* cp = &S->rowsH[(bq >> 3) * 256 + (bq & 7) * 16 + q4];
#pragma unroll
      for (int i = 0; i < 32; i++) asm volatile("" : "+r"(h[i]));
      asm volatile("" : "+l"(cp));
      mbar_wait(BAR(B_BK), 0);
      STAMP(5);
      const float2 bk = lds64(sb + BK_OFF);
#pragma unroll
      for (int r = 0; r < 2; r++) {
        const bool second = row0 + 8 * r == __float_as_int(bk.y);
        if (second || row0 + 8 * r == __float_as_int(bk.x)) {
#pragma unroll
          for (int a = 0; a < 4; a++) st_msg(cp + (second ? 128 : 0) + a * 4, h[a * 8 + r * 4], h[a * 8 + r * 4 + 1], h[a * 8 + r * 4 + 2], h[a * 8 + r * 4 + 3]);
        }
      }
      mbar_wait(BAR(B_DN), 0);
      if (FK_H1 == 3) {
        mbar_wait(BAR(B_WF), 1);
#pragma unroll
        for (int i = 0; i < 8; i++) ldsm_x4_t((wo ^ ((i & 1) << 5)) + (i >> 1) * 8192, uf + 32 + i * 4);
      }
#pragma unroll
      for (int a = 0; a < 4; a++) {
        const uint4 tG = lds128u(tq + T_G + a * 64);
        const uint32_t G[4] = {tG.x, tG.y, tG.z, tG.w};
#pragma unroll
        for (int i = 0; i < 8; i++) xw[a * 8 + i] = fma_bf16x2(G[i >> 1], h[a * 8 + (i & 1) * 4 + (i >> 1)], xw[a * 8 + i]);
#pragma unroll
        for (int k = 0; k < 2; k++) stsm_x4((so ^ ((((a & 1) * 2) + k) << 5)) + E_OFF + cwarp * 2048 + (a >> 1) * 2048, xw + a * 8 + k * 4);
      }
    }
    fence_async_smem();
    if (elect_one()) mbar_arrive(BAR(B_PREADY));
    STAMP(6);
    if (tid == 128) TRACE(15);
    if (role >> 16) {
      const char* hp = reinterpret_cast<const char*>(&S->rowsH[(cwarp >> 1) * 4 + q4]) + (cwarp & 1) * 8;
      uint32_t db = sb + DN_OFF + (cwarp + (cwarp == 7) * 4) * 8192 + ((ln & 7) + (ln >> 4) * 8) * 128 + ((((ln >> 3) & 1) ^ (ln & 7)) << 4), sa = sb + SEL_OFF + 8 + (gq & 1) * 4;
      const uint32_t ha = sb + H_OFF + (gq & 1) * 2112 + ((cwarp >> 1) * 4 + q4) * 16 + (cwarp & 1) * 8;
#pragma unroll
      for (int i = 0; i < 16; i++) ldsm_x4_t((db ^ (((i >> 1) & 3) << 5)) + (i >> 3) * 4096 + (i & 1) * 2048, df + i * 4);
      STAMP(7);
      mbar_wait(BAR(B_ROWS), 0);
      STAMP(8);
      uint2 hb[8];
#pragma unroll
      for (int i = 0; i < 8; i++) { const float2 v = lds64(ha + i * 256); hb[i] = make_uint2(__float_as_uint(v.x), __float_as_uint(v.y)); }
      STAMP(9);
      int it = 0;
      while (!__all_sync(~0u, max(max(max(hb[0].x, hb[1].x), max(hb[2].x, hb[3].x)), max(max(hb[4].x, hb[5].x), max(hb[6].x, hb[7].x))) != SENT)) {
#pragma unroll
        for (int i = 0; i < 8; i++) hb[i] = ld_msg8(hp + lds32u(sa) + i * 256);
        SPIN_CHECK(it);
      }
      if (tid == 128) TRACE(16);
      STAMP(10);
      float c[4][4];
#pragma unroll
      for (int i = 0; i < 4; i++) c[i][0] = c[i][1] = c[i][2] = c[i][3] = 0.f;
#pragma unroll
      for (int ks = 0; ks < 8; ks++) {
        const uint32_t b0 = hb[ks].x, b1 = hb[ks].y;
        mma_16816(c[0], wf + ks * 8, b0, b1); mma_16816(c[1], wf + ks * 8 + 4, b0, b1);
        mma_16816(c[2], uf + ks * 8, b0, b1); mma_16816(c[3], uf + ks * 8 + 4, b0, b1);
      }
      {
        float v[4];
#pragma unroll
        for (int i = 0; i < 4; i++) v[i] = (q4 & 2) ? (odd ? c[3][i] : c[2][i]) : (odd ? c[1][i] : c[0][i]);
        sts128(sb + RED_OFF + cwarp * 512 + (q4 * 8 + (gq ^ (q4 * 2))) * 16, v[0], v[2], v[1], v[3]);
      }
      uint2* pp = reinterpret_cast<uint2*>(&S->part[((cwarp * 16 + q4 * 2) * 128 + ((role >> 8) & 255)) * 4]) + gq;
      uint32_t ra = sb + RED_OFF + ((ln * 8) ^ ((ln & 16) * 2));
      asm volatile("" : "+l"(pp), "+r"(ra));
      STAMP(11);
      named_bar<2, 256>();
      STAMP(12);
      float g0 = 0.f, g1 = 0.f, u0 = 0.f, u1 = 0.f;
#pragma unroll
      for (int w = 0; w < 8; w++) {
        const float2 gv = lds64(ra + w * 512), uv = lds64((ra ^ 64) + w * 512 + 256);
        g0 += gv.x; g1 += gv.y; u0 += uv.x; u1 += uv.y;
      }
      const uint32_t gp = pack_bf16(g0, g1), up = pack_bf16(u0, u1), sp = pack_bf16(silu_f(bf_lo(gp)), silu_f(bf_hi(gp)));
      const uint32_t act = pack_bf16(bf_lo(sp) * bf_lo(up), bf_hi(sp) * bf_hi(up));
      uint32_t ab[4];
#pragma unroll
      for (int i = 0; i < 4; i++) ab[i] = __shfl_sync(~0u, act, i * 8 + q4 * 2 + (gq & 1));
      if (tid == 128) TRACE(31);
      STAMP(13);
#pragma unroll
      for (int T = 0; T < 2; T++) {
#pragma unroll
        for (int i = 0; i < 4; i++) {
          c[i][0] = c[i][1] = c[i][2] = c[i][3] = 0.f;
          mma_16816(c[i], df + (T * 4 + i) * 8, ab[0], ab[1]); mma_16816(c[i], df + (T * 4 + i) * 8 + 4, ab[2], ab[3]);
        }
        float v[4];
#pragma unroll
        for (int i = 0; i < 4; i++) v[i] = (q4 & 2) ? (odd ? c[3][i] : c[2][i]) : (odd ? c[1][i] : c[0][i]);
        st_msg8(pp + T * 8192, __float_as_uint(v[0]), __float_as_uint(v[2])); st_msg8(pp + T * 8192 + 1024, __float_as_uint(v[1]), __float_as_uint(v[3]));
      }
      if (tid == 128) TRACE(32);
      STAMP(14);
    }
    if (cwarp == 0) {
      const unsigned t0 = clk32();
      mbar_wait(BAR(B_FIN), 0);
      const int fc = q4 * 2 + ((ln >> 2) & 1) + (ln & 8);
      const float2 fo = lds64(sb + PFLAG_OFF + fc * 8);
      const float sg = __uint_as_float(lds32u(sb + CST_OFF));
      __nv_bfloat16* op = out + (size_t)lds32u(sb + SEL_OFF + (bq & 1) * 4) * D_ + (bq >> 1) * 16 + fc;
      const uint4* ip = &S->part[bq * 512 + ln];
      asm volatile("" : "+l"(op), "+l"(ip));
      if (role >> 16) { while (clk32() - t0 < FK_PDELAY) {} } else spin(FK_PDELAY + 600);
      int it = 0;
      uint4 m[14];
      while (true) {
        bool ok = true;
#pragma unroll
        for (int i = 0; i < 14; i++) { m[i] = ld_msg(ip + i * 32); ok &= m[i].x != SENT && m[i].z != SENT; }
        if (__all_sync(~0u, ok)) break;
        SPIN_CHECK(it);
      }
      if (lane == 0) TRACE(33);
      STAMP(15);
      float y[4] = {0.f, 0.f, 0.f, 0.f};
#pragma unroll
      for (int i = 0; i < 14; i++) { y[0] += __uint_as_float(m[i].x); y[1] += __uint_as_float(m[i].y); y[2] += __uint_as_float(m[i].z); y[3] += __uint_as_float(m[i].w); }
      const bool b2 = ln & 4;
      float y0 = (b2 ? y[2] : y[0]) + __shfl_xor_sync(~0u, b2 ? y[0] : y[2], 4), y1 = (b2 ? y[3] : y[1]) + __shfl_xor_sync(~0u, b2 ? y[1] : y[3], 4);
      y0 = ((ln & 8) ? y1 : y0) + __shfl_xor_sync(~0u, (ln & 8) ? y0 : y1, 8);
      y0 += __shfl_xor_sync(~0u, y0, 16);
      const float upd = round_bf16(round_bf16(y0) * sg);
      if (ln < 16) *op = __float2bfloat16_rn(fmaf(fo.y, upd, fo.x));
      if (lane == 0) {
        TRACE(34); TRACE_CLK(122);
      }
    }
  }
}

typedef CUresult (*PFN_encodeTiled)(CUtensorMap*, CUtensorMapDataType, cuuint32_t, void*, const cuuint64_t*, const cuuint64_t*,
                                    const cuuint32_t*, const cuuint32_t*, CUtensorMapInterleave, CUtensorMapSwizzle,
                                    CUtensorMapL2promotion, CUtensorMapFloatOOBfill);

static void mapnd(PFN_encodeTiled enc, CUtensorMap* m, const void* p, int nd, const cuuint64_t* dims, const cuuint64_t* str, const cuuint32_t* box,
                  CUtensorMapSwizzle sw, CUtensorMapL2promotion pr) {
  const cuuint32_t es[5] = {1, 1, 1, 1, 1};
  enc(m, CU_TENSOR_MAP_DATA_TYPE_BFLOAT16, nd, (void*)p, dims, str, box, es, CU_TENSOR_MAP_INTERLEAVE_NONE, sw, pr, CU_TENSOR_MAP_FLOAT_OOB_FILL_NONE);
}
static void map2d(PFN_encodeTiled enc, CUtensorMap* m, const void* p, uint64_t rows, uint64_t cols, uint32_t brows, uint32_t bcols,
                  CUtensorMapSwizzle sw = CU_TENSOR_MAP_SWIZZLE_128B, CUtensorMapL2promotion pr = CU_TENSOR_MAP_L2_PROMOTION_L2_128B) {
  const cuuint64_t dims[2] = {cols, rows}, str[1] = {cols * 2}; const cuuint32_t box[2] = {bcols, brows};
  mapnd(enc, m, p, 2, dims, str, box, sw, pr);
}
static void map3d(PFN_encodeTiled enc, CUtensorMap* m, const void* p, uint64_t rows, uint64_t cols, uint32_t brows, uint32_t bgroups) {
  const cuuint64_t dims[3] = {64, rows, cols / 64}, str[2] = {cols * 2, 128}; const cuuint32_t box[3] = {64, brows, bgroups};
  mapnd(enc, m, p, 3, dims, str, box, CU_TENSOR_MAP_SWIZZLE_128B, CU_TENSOR_MAP_L2_PROMOTION_L2_128B);
}

}

extern "C" void kernel_launch(void* const* d_in, const int* in_sizes, int n_in, void* d_out, int out_size) {
  using namespace fk;
  (void)in_sizes; (void)n_in; (void)out_size;
  static PFN_encodeTiled enc = nullptr;
  static Scratch* scr = nullptr;
  if (!enc) {
    void* fn = nullptr; cudaDriverEntryPointQueryResult qr;
    cudaGetDriverEntryPoint("cuTensorMapEncodeTiled", &fn, cudaEnableDefault, &qr);
    enc = (PFN_encodeTiled)fn;
    cudaGetSymbolAddress((void**)&scr, g_scr);
    cudaFuncSetAttribute(fused_kernel, cudaFuncAttributeMaxDynamicSharedMemorySize, SMEM_BYTES);
  }
  typedef const __nv_bfloat16* bp;
  Params prm;
  prm.w_r = (bp)d_in[6];
  prm.wsp[0] = (const char*)d_in[1]; prm.wsp[1] = (const char*)d_in[2];
  map2d(enc, &prm.ws[0], d_in[1], S_, S_, 128, 64);
  map2d(enc, &prm.ws[1], d_in[2], S_, S_, 128, 64);
  map3d(enc, &prm.n, scr->n, S_, D_, 64, 2);
  map2d(enc, &prm.wm, d_in[11], D_, 6 * D_, 8, 256, CU_TENSOR_MAP_SWIZZLE_NONE, CU_TENSOR_MAP_L2_PROMOTION_L2_256B);
  map2d(enc, &prm.p, scr->P, 2 * S_, D_, 128, 64);
  map2d(enc, &prm.wd[0], d_in[3], D_, D_, 64, 64);
  map2d(enc, &prm.wd[1], d_in[4], D_, D_, 64, 64);
  map2d(enc, &prm.wg, d_in[7], D_, F_, 128, 32, CU_TENSOR_MAP_SWIZZLE_64B);
  map2d(enc, &prm.wu, d_in[8], D_, F_, 128, 32, CU_TENSOR_MAP_SWIZZLE_64B);
  for (int i = 0; i < 3; i++) prm.we[i] = (const char*)d_in[7 + i];
  map2d(enc, &prm.ps, scr->P, 2 * S_, D_, 32, 64);
  for (int i = 0; i < 2; i++) {
    const cuuint64_t dims[3] = {128, 8, i ? 2048u : 3584u}, str[2] = {256, 2048}; const cuuint32_t box[3] = {8, 1, 32};
    mapnd(enc, &prm.tch[i], d_in[i ? 0 : 9], 3, dims, str, box, CU_TENSOR_MAP_SWIZZLE_NONE, CU_TENSOR_MAP_L2_PROMOTION_L2_256B);
  }
  map3d(enc, &prm.xb, d_in[0], S_, D_, 64, 2);
  map3d(enc, &prm.xm, d_in[0], S_, D_, 16, 2);
  map3d(enc, &prm.om, d_out, S_, D_, 16, 2);
  {
    const cuuint64_t dims[5] = {64, 2, 8, 224, 16}, str[4] = {8 * 2048, 2048, 16 * 2048, 128}; const cuuint32_t box[5] = {64, 2, 8, 2, 2};
    mapnd(enc, &prm.wdn, d_in[9], 5, dims, str, box, CU_TENSOR_MAP_SWIZZLE_128B, CU_TENSOR_MAP_L2_PROMOTION_L2_128B);
  }

  fused_kernel<<<NCTA, 384, SMEM_BYTES, cudaStreamPerThread>>>((bp)d_in[0], scr, (__nv_bfloat16*)d_out, (bp)d_in[10], (bp)d_in[3], (bp)d_in[4], prm);
}
```

```cpp
#include <cuda_runtime.h>
#include <cuda_bf16.h>
#include <cuda.h>
#include <stdint.h>

#define DEVINL __device__ __forceinline__

namespace fk {

constexpr int S_ = 2048, D_ = 1024, F_ = 3584;
constexpr int NCTA = 128;
constexpr int SLOT = 16384;
constexpr int STAGE = 3 * SLOT;
constexpr int BUF = 2 * SLOT;
constexpr int E_OFF = 5 * BUF;
constexpr int SP_OFF = 4 * STAGE;
constexpr int MISC_OFF = SP_OFF + 32768;
constexpr int SMEM_BYTES = MISC_OFF + 3072;
constexpr int BAR_OFF = MISC_OFF;
constexpr int SEL_OFF = MISC_OFF + 344;
constexpr int BK_OFF = MISC_OFF + 360;
constexpr int CST_OFF = MISC_OFF + 368;
constexpr int PFLAG_OFF = MISC_OFF + 384;
constexpr int TAB_OFF = MISC_OFF + 512;
enum { T_WH = 0, T_ONE = 320, T_WL = 576, T_GA = 896, T_A = 1152, T_S = 1408, T_G = 1664 };
constexpr int KEY_OFF = TAB_OFF + 2048;
constexpr int SINK_OFF = KEY_OFF;
constexpr int POLL_OFF = TAB_OFF + 256;
constexpr int T1_OFF = TAB_OFF + 1536;
constexpr int RKA_OFF = BUF;
constexpr int RKB_OFF = RKA_OFF + 2048;
constexpr int RED_OFF = RKB_OFF + 2048;
constexpr int H_OFF = 8192;
constexpr int DN_OFF = RED_OFF + 4096;

enum { B_FULL = 0, B_EMPTY = 4, B_PREADY = 8, B_MF = 12  , B_FULL2 = 20  , B_EMPTY2 = 25  , B_A29 = 30, B_ADONE = 31,
       B_RSDONE = 32, B_TAB = 33, B_B27 = 34, B_ROWS = 35, B_DN = 36, B_EFULL = 37, B_PS = 38  , B_WF = 40, B_BK = 41, B_FIN = 42, B_NUM = 43 };
constexpr unsigned long long CNT0 = 0x1111888855551111ull, CNT1 = 0x4244444222221111ull, CNT2 = 0x1111111111111122ull;

#define FK_SKIP 0
#define FK_X 0
#define FK_PS0 1
#define FK_XN 0
#define FK_S1 0
#define FK_NL 12
#define FK_XD 0
#define FK_GS 1
#define FK_TD 1
#define FK_TX 1
#define FK_ODELAY 0
#define FK_OMASK 255
#define FK_OSPACE2 0
#define FK_NP 0
#define FK_G1 20
#define FK_GP 2
#define FK_QR 31
#define FK_H1 3
#define FK_S 0
#define FK_NA0 1
#define FK_QUIET FK_S
#define FK_EP 0
#define FK_DRY 11
#define FK_T0D 0
#define FK_T1D 0
#define FK_A0D 200
#define FK_A1D 400
#define FK_A0N 0
#define FK_A0W 0
#define FK_P0D 0
#define FK_E4 0
#define FK_QW 0
#define FK_REL 0x14
#define FK_WSPF 22
#define FK_SPACE 300
#define FK_OSPACE 200
#define FK_NOMC 4
#define FK_TR0 0
#define FK_G0 3
#define FK_NA 0
#define FK_PACE 800
#define FK_QP 5
#define FK_PSPACE 400
#define FK_ORD 0
#define FK_PDELAY 900
constexpr int SPIN_LIMIT = 1 << 20;
constexpr uint32_t SENT = 0xFFFFFFFFu;

struct Scratch {
  uint4 part[128 * 128 * 4];
  uint4 stats[128 * 128];
  uint4 rowsH[32 * 128];
  uint4 rowsB[32 * 128];
  uint4 cand[16 * 8];
  uint2 rs[2 * S_];
  uint4 st0[64 * 2];
  uint4 cst[8];
  float mod[2][6 * D_];
  uint2 u[2 * D_];
  unsigned flagP[128 * 4 * 8];
  unsigned cntN[12 * 32];
  unsigned cntMod[2 * 32];
  unsigned epoch[32];
  unsigned claim[64 * 8];
  alignas(1024) __nv_bfloat16 n[S_ * D_];
  __nv_bfloat16 P[2 * S_ * D_];
};
__device__ __align__(1024) Scratch g_scr;

struct Params {
  CUtensorMap ws[2];
  CUtensorMap n;
  CUtensorMap wm;
  CUtensorMap p;
  CUtensorMap wg, wu;
  CUtensorMap xm;
  CUtensorMap wdn;
  CUtensorMap wd[2];
  CUtensorMap om;
  CUtensorMap xb;
  CUtensorMap ps;
  CUtensorMap tch[2];
  const __nv_bfloat16* w_r;
  const char* wsp[2];
  const char* we[3];
};

DEVINL uint32_t smem_u32(const void* p) { return (uint32_t)__cvta_generic_to_shared(p); }
DEVINL void mbar_init(uint32_t bar, uint32_t cnt) { asm volatile("mbarrier.init.shared::cta.b64 [%0], %1;" ::"r"(bar), "r"(cnt) : "memory"); }
DEVINL void mbar_expect_tx(uint32_t bar, uint32_t bytes) { asm volatile("mbarrier.arrive.expect_tx.shared::cta.b64 _, [%0], %1;" ::"r"(bar), "r"(bytes) : "memory"); }
DEVINL void mbar_arrive(uint32_t bar) { asm volatile("mbarrier.arrive.shared::cta.b64 _, [%0];" ::"r"(bar) : "memory"); }
DEVINL void mbar_wait(uint32_t bar, uint32_t parity) {
  asm volatile("{\n.reg .pred p;\n.reg .u32 c;\nmov.u32 c, 0;\n"
               "LW:\nmbarrier.try_wait.parity.shared::cta.b64 p, [%0], %1;\n@p bra LD;\n"
               "add.u32 c, c, 1;\nsetp.lt.u32 p, c, 1048576;\n@p bra LW;\ntrap;\nLD:\n}" ::"r"(bar), "r"(parity) : "memory");
}
DEVINL void mbar_wait_cluster(uint32_t bar, uint32_t parity) {
  asm volatile("{\n.reg .pred p;\n.reg .u32 c;\nmov.u32 c, 0;\n"
               "LW:\nmbarrier.try_wait.parity.acquire.cluster.shared::cta.b64 p, [%0], %1;\n@p bra LD;\n"
               "add.u32 c, c, 1;\nsetp.lt.u32 p, c, 1048576;\n@p bra LW;\ntrap;\nLD:\n}" ::"r"(bar), "r"(parity) : "memory");
}
#define SPIN_CHECK(it) asm volatile("{\n.reg .pred p;\nsetp.gt.s32 p, %0, %1;\n@p trap;\n}" ::"r"(++(it)), "n"(SPIN_LIMIT))
DEVINL void fence_async_smem() { asm volatile("fence.proxy.async.shared::cta;" ::: "memory"); }
DEVINL void fence_async_global() { asm volatile("fence.proxy.async.global;" ::: "memory"); }
template <int BIT> DEVINL void rel_fence() { if ((FK_REL >> BIT) & 1) asm volatile("fence.acq_rel.gpu;" ::: "memory"); }
DEVINL void fence_gpu() { asm volatile("fence.acq_rel.gpu;" ::: "memory"); }
template <int ID, int N> DEVINL void named_bar() { asm volatile("bar.sync %0, %1;" ::"n"(ID), "n"(N) : "memory"); }
DEVINL bool elect_one() { uint32_t p; asm volatile("{\n.reg .pred e;\nelect.sync _|e, 0xffffffff;\nselp.u32 %0, 1, 0, e;\n}" : "=r"(p)); return p; }
DEVINL unsigned clk32() { unsigned c; asm volatile("mov.u32 %0, %%clock;" : "=r"(c)); return c; }
#define FK_GRIDW 32
#define FK_GRID 0
DEVINL void grid_wait() {
  if (FK_GRID) {
    unsigned t0, t1;
    asm volatile("mov.u32 %0, %%globaltimer_lo;" : "=r"(t0));
    do { asm volatile("mov.u32 %0, %%globaltimer_lo;" : "=r"(t1)); } while (((t0 - FK_GRIDW) ^ t1) < FK_GRID + 0u + !FK_GRID);
  }
}
DEVINL void spin(unsigned n) { const unsigned c = clk32(); while (clk32() - c < n) {} }

constexpr uint64_t POL_NORMAL = 0x1000000000000000ull, POL_FIRST = 0x12F0000000000000ull;
#define FK_HINTS 0x30B
template <int BIT> DEVINL constexpr uint64_t pol() { return ((FK_HINTS >> BIT) & 1) ? POL_FIRST : POL_NORMAL; }
DEVINL void tma_2d(uint32_t dst, const CUtensorMap* m, int x, int y, uint32_t bar, uint64_t pol) {
  asm volatile("cp.async.bulk.tensor.2d.shared::cluster.global.mbarrier::complete_tx::bytes.L2::cache_hint [%0], [%1, {%3, %4}], [%2], %5;"
               ::"r"(dst), "l"(m), "r"(bar), "r"(x), "r"(y), "l"(pol) : "memory");
}
DEVINL void tma_3d(uint32_t dst, const CUtensorMap* m, int y, int z, uint32_t bar, uint64_t pol) {
  asm volatile("cp.async.bulk.tensor.3d.shared::cluster.global.mbarrier::complete_tx::bytes.L2::cache_hint [%0], [%1, {0, %3, %4}], [%2], %5;"
               ::"r"(dst), "l"(m), "r"(bar), "r"(y), "r"(z), "l"(pol) : "memory");
}
DEVINL void tma_3d_mc(uint32_t dst, const CUtensorMap* m, int y, int z, uint32_t bar, uint64_t pol) {
  asm volatile("cp.async.bulk.tensor.3d.shared::cluster.global.mbarrier::complete_tx::bytes.multicast::cluster.L2::cache_hint [%0], [%1, {0, %3, %4}], [%2], %5, %6;"
               ::"r"(dst), "l"(m), "r"(bar), "r"(y), "r"(z), "h"((unsigned short)3), "l"(pol) : "memory");
}
DEVINL void tma_2d_mc(uint32_t dst, const CUtensorMap* m, int x, int y, uint32_t bar, uint64_t pol) {
  asm volatile("cp.async.bulk.tensor.2d.shared::cluster.global.mbarrier::complete_tx::bytes.multicast::cluster.L2::cache_hint [%0], [%1, {%3, %4}], [%2], %5, %6;"
               ::"r"(dst), "l"(m), "r"(bar), "r"(x), "r"(y), "h"((unsigned short)3), "l"(pol) : "memory");
}
DEVINL void tma_store_2d(const CUtensorMap* m, uint32_t src, int x, int y) {
  asm volatile("cp.async.bulk.tensor.2d.global.shared::cta.bulk_group [%0, {%2, %3}], [%1];" ::"l"(m), "r"(src), "r"(x), "r"(y) : "memory");
}
DEVINL void bulk_store(void* dst, uint32_t src, uint32_t bytes) {
  asm volatile("cp.async.bulk.global.shared::cta.bulk_group [%0], [%1], %2;" ::"l"(dst), "r"(src), "r"(bytes) : "memory");
}
DEVINL void bulk_load(uint32_t dst, const void* src, uint32_t bytes, uint32_t bar, uint64_t pol) {
  asm volatile("cp.async.bulk.shared::cluster.global.mbarrier::complete_tx::bytes.L2::cache_hint [%0], [%1], %2, [%3], %4;" ::"r"(dst), "l"(src), "r"(bytes), "r"(bar), "l"(pol) : "memory");
}
template <int N> DEVINL void bulk_wait_read() { asm volatile("cp.async.bulk.wait_group.read %0;" ::"n"(N) : "memory"); }
DEVINL void pf_bulk(const void* p, uint32_t bytes) { asm volatile("cp.async.bulk.prefetch.L2.global [%0], %1;" ::"l"(p), "r"(bytes) : "memory"); }
DEVINL void bulk_commit() { asm volatile("cp.async.bulk.commit_group;" ::: "memory"); }
template <int N> DEVINL void bulk_wait() { asm volatile("cp.async.bulk.wait_group %0;" ::"n"(N) : "memory"); }
DEVINL void prefetch_tmap(const CUtensorMap* m) { asm volatile("prefetch.tensormap [%0];" ::"l"(m) : "memory"); }

DEVINL void wg_fence() { asm volatile("wgmma.fence.sync.aligned;" ::: "memory"); }
DEVINL void wg_commit() { asm volatile("wgmma.commit_group.sync.aligned;" ::: "memory"); }
template <int N> DEVINL void wg_wait() { asm volatile("wgmma.wait_group.sync.aligned %0;" ::"n"(N) : "memory"); }
DEVINL uint32_t desc_lo(uint32_t addr, uint32_t lbo) { return ((addr & 0x3FFFF) >> 4) | ((lbo >> 4) << 16); }

#define R8(a, o) "+f"(a[o]), "+f"(a[o + 1]), "+f"(a[o + 2]), "+f"(a[o + 3]), "+f"(a[o + 4]), "+f"(a[o + 5]), "+f"(a[o + 6]), "+f"(a[o + 7])
#define R64(a, o) R8(a, o), R8(a, o + 8), R8(a, o + 16), R8(a, o + 24), R8(a, o + 32), R8(a, o + 40), R8(a, o + 48), R8(a, o + 56)
#define ACC64 "{%0, %1, %2, %3, %4, %5, %6, %7, %8, %9, %10, %11, %12, %13, %14, %15, "              \
              "%16, %17, %18, %19, %20, %21, %22, %23, %24, %25, %26, %27, %28, %29, %30, %31, "    \
              "%32, %33, %34, %35, %36, %37, %38, %39, %40, %41, %42, %43, %44, %45, %46, %47, "    \
              "%48, %49, %50, %51, %52, %53, %54, %55, %56, %57, %58, %59, %60, %61, %62, %63"
#define ACC128 ACC64 ", %64, %65, %66, %67, %68, %69, %70, %71, %72, %73, %74, %75, %76, %77, %78, %79, "      \
              "%80, %81, %82, %83, %84, %85, %86, %87, %88, %89, %90, %91, %92, %93, %94, %95, "               \
              "%96, %97, %98, %99, %100, %101, %102, %103, %104, %105, %106, %107, %108, %109, %110, %111, "   \
              "%112, %113, %114, %115, %116, %117, %118, %119, %120, %121, %122, %123, %124, %125, %126, %127"
template <int TB> DEVINL void wgmma_n256(float (&d)[128], uint32_t da, uint32_t db, int scale_d) {
  asm volatile("{\n.reg .pred p;\n.reg .b64 a, b;\nsetp.ne.b32 p, %130, 0;\nmov.b64 a, {%128, 0x40000040};\nmov.b64 b, {%129, 0x40000040};\n"
               "wgmma.mma_async.sync.aligned.m64n256k16.f32.bf16.bf16 " ACC128 "}, a, b, p, 1, 1, 0, %131;\n}\n"
               : R64(d, 0), R64(d, 64) : "r"(da), "r"(db), "r"(scale_d), "n"(TB));
}
template <int TB, int HI = 0x40000040> DEVINL void wgmma_n128(float (&d)[64], uint32_t da, uint32_t db) {
  asm volatile("{\n.reg .b64 a, b;\nmov.b64 a, {%64, %67};\nmov.b64 b, {%65, %67};\n"
               "wgmma.mma_async.sync.aligned.m64n128k16.f32.bf16.bf16 " ACC64 "}, a, b, 1, 1, 1, 0, %66;\n}\n" : R64(d, 0) : "r"(da), "r"(db), "n"(TB), "n"(HI));
}
template <int SC> DEVINL void wgmma_n128_rs(float (&d)[64], const uint32_t* a, uint32_t db) {
  asm volatile("{\n.reg .pred p;\n.reg .b64 b;\nsetp.ne.b32 p, %69, 0;\nmov.b64 b, {%68, 0x40000040};\n"
               "wgmma.mma_async.sync.aligned.m64n128k16.f32.bf16.bf16 " ACC64 "}, {%64, %65, %66, %67}, b, p, 1, 1, 0;\n}\n"
               : R64(d, 0) : "r"(a[0]), "r"(a[1]), "r"(a[2]), "r"(a[3]), "r"(db), "n"(SC));
}
template <int N> DEVINL void reg_fence(float (&a)[N]) {
#pragma unroll
  for (int i = 0; i < N; i++) asm volatile("" : "+f"(a[i])::"memory");
}

DEVINL uint32_t pack_bf16(float lo, float hi) { uint32_t r; asm("cvt.rn.bf16x2.f32 %0, %1, %2;" : "=r"(r) : "f"(hi), "f"(lo)); return r; }
DEVINL uint32_t add_bf16x2(uint32_t a, uint32_t b) { uint32_t r; asm("add.rn.bf16x2 %0, %1, %2;" : "=r"(r) : "r"(a), "r"(b)); return r; }
DEVINL uint32_t mul_bf16x2(uint32_t a, uint32_t b) { uint32_t r; asm("mul.rn.bf16x2 %0, %1, %2;" : "=r"(r) : "r"(a), "r"(b)); return r; }
DEVINL uint32_t fma_bf16x2(uint32_t a, uint32_t b, uint32_t c) { uint32_t r; asm("fma.rn.bf16x2 %0, %1, %2, %3;" : "=r"(r) : "r"(a), "r"(b), "r"(c)); return r; }
DEVINL float bf_lo(uint32_t w) { return __uint_as_float(w << 16); }
DEVINL float bf_hi(uint32_t w) { return __uint_as_float(w & 0xFFFF0000u); }
DEVINL float round_bf16(float v) { return bf_lo(pack_bf16(v, 0.f)); }
DEVINL float sigmoid_f(float v) { float r; asm("rcp.approx.ftz.f32 %0, %1;" : "=f"(r) : "f"(1.f + __expf(-v))); return r; }
DEVINL float rsqrt_f(float v) { float r; asm("rsqrt.approx.ftz.f32 %0, %1;" : "=f"(r) : "f"(v)); return r; }
DEVINL float silu_f(float v) { return v * sigmoid_f(v); }
DEVINL void stsm_x4(uint32_t addr, const uint32_t* r) {
  asm volatile("stmatrix.sync.aligned.m8n8.x4.shared.b16 [%0], {%1, %2, %3, %4};" ::"r"(addr), "r"(r[0]), "r"(r[1]), "r"(r[2]), "r"(r[3]) : "memory");
}
DEVINL void ldsm_x4(uint32_t addr, uint32_t* r) {
  asm volatile("ldmatrix.sync.aligned.m8n8.x4.shared.b16 {%0, %1, %2, %3}, [%4];" : "=r"(r[0]), "=r"(r[1]), "=r"(r[2]), "=r"(r[3]) : "r"(addr) : "memory");
}
DEVINL void ldsm_x4_t(uint32_t addr, uint32_t* r) {
  asm volatile("ldmatrix.sync.aligned.m8n8.x4.trans.shared.b16 {%0, %1, %2, %3}, [%4];" : "=r"(r[0]), "=r"(r[1]), "=r"(r[2]), "=r"(r[3]) : "r"(addr) : "memory");
}
DEVINL void mma_16816(float (&c)[4], const uint32_t* a, uint32_t b0, uint32_t b1) {
  asm("mma.sync.aligned.m16n8k16.row.col.f32.bf16.bf16.f32 {%0, %1, %2, %3}, {%4, %5, %6, %7}, {%8, %9}, {%0, %1, %2, %3};"
      : "+f"(c[0]), "+f"(c[1]), "+f"(c[2]), "+f"(c[3]) : "r"(a[0]), "r"(a[1]), "r"(a[2]), "r"(a[3]), "r"(b0), "r"(b1));
}
DEVINL void mma_1688(float (&c)[4], uint32_t a0, uint32_t a1, uint32_t b0) {
  asm("mma.sync.aligned.m16n8k8.row.col.f32.bf16.bf16.f32 {%0, %1, %2, %3}, {%4, %5}, {%6}, {%0, %1, %2, %3};"
      : "+f"(c[0]), "+f"(c[1]), "+f"(c[2]), "+f"(c[3]) : "r"(a0), "r"(a1), "r"(b0));
}
DEVINL float4 lds128(uint32_t a) { float4 v; asm volatile("ld.shared.v4.f32 {%0, %1, %2, %3}, [%4];" : "=f"(v.x), "=f"(v.y), "=f"(v.z), "=f"(v.w) : "r"(a)); return v; }
DEVINL uint4 lds128u(uint32_t a) { uint4 v; asm volatile("ld.shared.v4.u32 {%0, %1, %2, %3}, [%4];" : "=r"(v.x), "=r"(v.y), "=r"(v.z), "=r"(v.w) : "r"(a)); return v; }
DEVINL float2 lds64(uint32_t a) { float2 v; asm volatile("ld.shared.v2.f32 {%0, %1}, [%2];" : "=f"(v.x), "=f"(v.y) : "r"(a)); return v; }
DEVINL uint32_t lds32u(uint32_t a) { uint32_t v; asm volatile("ld.shared.u32 %0, [%1];" : "=r"(v) : "r"(a)); return v; }
DEVINL void sts128(uint32_t a, float x, float y, float z, float w) { asm volatile("st.shared.v4.f32 [%0], {%1, %2, %3, %4};" ::"r"(a), "f"(x), "f"(y), "f"(z), "f"(w) : "memory"); }
DEVINL void sts128u(uint32_t a, uint32_t x, uint32_t y, uint32_t z, uint32_t w) { asm volatile("st.shared.v4.u32 [%0], {%1, %2, %3, %4};" ::"r"(a), "r"(x), "r"(y), "r"(z), "r"(w) : "memory"); }
DEVINL void sts64u(uint32_t a, uint32_t x, uint32_t y) { asm volatile("st.shared.v2.u32 [%0], {%1, %2};" ::"r"(a), "r"(x), "r"(y) : "memory"); }
DEVINL void sts32v(uint32_t a, uint32_t v) { asm volatile("st.volatile.shared.u32 [%0], %1;" ::"r"(a), "r"(v) : "memory"); }
DEVINL void sts32(uint32_t a, float v) { asm volatile("st.shared.f32 [%0], %1;" ::"r"(a), "f"(v) : "memory"); }

DEVINL uint4 ld_msg(const void* p) {
  unsigned long long a, b;
  asm volatile("{\n.reg .b128 r;\nld.relaxed.gpu.global.b128 r, [%2];\nmov.b128 {%0, %1}, r;\n}" : "=l"(a), "=l"(b) : "l"(p) : "memory");
  return make_uint4((uint32_t)a, (uint32_t)(a >> 32), (uint32_t)b, (uint32_t)(b >> 32));
}
DEVINL void st_msg(void* p, uint32_t x, uint32_t y, uint32_t z, uint32_t w) {
  unsigned long long a = (unsigned long long)x | ((unsigned long long)y << 32), b = (unsigned long long)z | ((unsigned long long)w << 32);
  asm volatile("{\n.reg .b128 r;\nmov.b128 r, {%1, %2};\nst.relaxed.gpu.global.b128 [%0], r;\n}" ::"l"(p), "l"(a), "l"(b) : "memory");
}
DEVINL uint2 ld_msg8(const void* p) {
  unsigned long long a;
  asm volatile("ld.relaxed.gpu.global.b64 %0, [%1];" : "=l"(a) : "l"(p) : "memory");
  return make_uint2((uint32_t)a, (uint32_t)(a >> 32));
}
DEVINL void st_msg8(void* p, uint32_t x, uint32_t y) {
  asm volatile("st.relaxed.gpu.global.b64 [%0], %1;" ::"l"(p), "l"((unsigned long long)x | ((unsigned long long)y << 32)) : "memory");
}
DEVINL unsigned ld_rlx(const void* p) { unsigned v; asm volatile("ld.relaxed.gpu.global.u32 %0, [%1];" : "=r"(v) : "l"(p) : "memory"); return v; }
DEVINL void st_rlx(unsigned* p, unsigned v) { asm volatile("st.relaxed.gpu.global.u32 [%0], %1;" ::"l"(p), "r"(v) : "memory"); }
DEVINL void red_add(unsigned* p, unsigned v) { asm volatile("red.relaxed.gpu.global.add.u32 [%0], %1;" ::"l"(p), "r"(v) : "memory"); }
DEVINL uint4 ldg_nc(const void* p) {
  uint4 v;
  asm volatile("ld.global.nc.L1::no_allocate.v4.u32 {%0, %1, %2, %3}, [%4];" : "=r"(v.x), "=r"(v.y), "=r"(v.z), "=r"(v.w) : "l"(p));
  return v;
}
DEVINL float4 ldg_cg(const float* p) { float4 v; asm volatile("ld.global.cg.v4.f32 {%0, %1, %2, %3}, [%4];" : "=f"(v.x), "=f"(v.y), "=f"(v.z), "=f"(v.w) : "l"(p) : "memory"); return v; }
DEVINL void wait_cnt(const unsigned* p, unsigned target) {
  int it = 0;
  while ((int)(ld_rlx(p) - target) < 0) { SPIN_CHECK(it); __nanosleep(100); }
}

#define TRACE2(id)
#define TRACE3(id)
#define TRACE(id)
#define TRACE_CLK(id)

#define STAMP2(i)
#define STAMP(i)
DEVINL uint32_t fkey(float v) { const uint32_t u = __float_as_uint(v); return (u & 0x80000000u) ? ~u : (u | 0x80000000u); }
DEVINL float fkey_inv(uint32_t k) { return __uint_as_float((k & 0x80000000u) ? (k & 0x7FFFFFFFu) : ~k); }
DEVINL uint32_t redux_max(uint32_t v) { uint32_t r; asm volatile("redux.sync.max.u32 %0, %1, 0xffffffff;" : "=r"(r) : "r"(v)); return r; }
DEVINL void warp_top2(uint32_t key, uint32_t& k1, uint32_t& k2) { k1 = redux_max(key); k2 = redux_max(key == k1 ? 0u : key); }
DEVINL int key_row(uint32_t k) { return 2047 - (int)(k & 2047u); }
DEVINL int blk_src(int q, int cgrp) { const int f = q - 4, kk = (f * 37) >> 8, i = f - kk * 7; return f < 0 ? cgrp * 4 + q : (FK_SKIP ? i + (i >= cgrp) : i == cgrp ? 7 : i) * 4 + kk; }
DEVINL void split_assign(int c, int& grp, int& gi) {
  const int c7 = ((c - 36) * 37) >> 8;
  grp = c < 4 ? 0 : c < 36 ? (c - 4) & 7 : c - 35 - c7 * 7; gi = c < 4 ? c + 4 : c < 36 ? (c - 4) >> 3 : c7 + 4;
}
DEVINL int first_choice() {
  unsigned smid; asm volatile("mov.u32 %0, %%smid;" : "=r"(smid));
  return (smid >> 1) >= 62 ? (62 - (smid >> 1)) & 3 : ((smid >> 1) + 4) & 63;
}
DEVINL uint32_t pstage(int kk) { return ((0xABA4 >> (kk * 4)) & 15) * SLOT; }
DEVINL uint32_t buf_off(int u) { return ((0x42130 >> (u * 4)) & 15) * BUF; }
DEVINL int cnt_idx(int kb) { return kb < 4 ? (8 + kb) * 32 : (kb >> 2) * 32 + (kb & 3); }

__global__ void __launch_bounds__(384, 1) __cluster_dims__(2, 1, 1)
fused_kernel(const __nv_bfloat16* __restrict__ x, Scratch* const S, __nv_bfloat16* __restrict__ out, const __nv_bfloat16* __restrict__ cvec,
             const __nv_bfloat16* __restrict__ wd_re, const __nv_bfloat16* __restrict__ wd_im, const __grid_constant__ Params prm) {
  extern __shared__ __align__(1024) uint8_t smem_raw[];
  const uint32_t sb = smem_u32(smem_raw);
  const int tid = threadIdx.x, lane = tid & 31;
  const int warp = __shfl_sync(~0u, tid >> 5, 0);
  const int bx = blockIdx.x, rank = bx & 1;
  auto BAR = [&](int i) { return sb + BAR_OFF + i * 8; };

  uint4 xr[8] = {};
  if ((warp & ~1) == 2) {
    const uint4* src = reinterpret_cast<const uint4*>(x + (size_t)(bx * 2 + warp - 2) * D_) + lane;
#pragma unroll
    for (int i = 0; i < 4; i++) xr[i] = ldg_nc(src + 32 * i);
  }
  if (warp < 2) spin(FK_T0D);
  unsigned cnt0 = 0;
  if (FK_EP && tid < 8) cnt0 = ld_rlx(&S->cntN[cnt_idx(tid)]);
  if (warp >= 4 && warp < 11 && elect_one()) {
    const int w = warp - 4;
#pragma unroll 1
    for (int i = w; i < B_NUM; i += 7) {
      mbar_init(BAR(i), (uint32_t)((i < 16 ? CNT0 : i < 32 ? CNT1 : CNT2) >> ((i & 15) * 4)) & 15u);
    }
    if (w < 4) mbar_expect_tx(BAR(B_FULL + w), STAGE);
    asm volatile("fence.mbarrier_init.release.cluster;" ::: "memory");
    if (w < 3) { spin(FK_T1D); prefetch_tmap(&prm.ws[0] + w); }
  }
  if (warp == 1 && rank == 0 && elect_one()) {
    int c = first_choice(), it = 0;
    while (atomicExch(&S->claim[c * 8], 1u)) { c = (c + 1) & 63; SPIN_CHECK(it); }
    sts32v(sb + BK_OFF, c);
    asm volatile("fence.acq_rel.cta;" ::: "memory");
  }
  __syncwarp();
  if (warp >= 4 && warp != FK_DRY) asm volatile("bar.arrive 3, 320;" ::: "memory");
  asm volatile("barrier.cluster.arrive.relaxed.aligned;" ::: "memory");
  if (warp >= 11 - FK_A0N && warp < 11) {
    int g0, i0; split_assign(first_choice(), g0, i0);
    spin(FK_A0D + (10 - warp) * FK_A1D);
    asm volatile("prefetch.global.L2 [%0];" ::"l"(prm.wsp[i0 >> 2] + (size_t)((g0 * 2 + rank) * 128 + (i0 & 3) * 32 + lane) * 4096 + (10 - warp) * 128));
  }
  uint32_t epoch = 0;
  if (FK_S || warp == 1 || (FK_DRY && warp == 0)) epoch = ld_rlx(S->epoch);
  const uint32_t ring = sb + SP_OFF + (warp == FK_DRY ? 8192 : (warp - 2) * 16384), mf = BAR(B_MF + (warp - 2) * 4);
  const int jw = bx >> 6, e0 = (bx & 63) * 16;
  const __nv_bfloat16* src = (jw ? wd_im : wd_re) + (size_t)e0 * D_;
  int nc = 0;
  if ((warp & ~1) == 2 || warp == FK_DRY) {
#pragma unroll 1
    for (int G = 0; G < 8; G += (G == 0 && warp == 2) + 1) {
      if (G) { mbar_wait(mf + (nc & 3) * 8, (nc >> 2) & 1); nc++; }
      const uint32_t stg = ring + (nc & 3) * 4096, sl = stg + (G ? (lane >> 4) * 2048 + (lane & 15) * 16 : lane * 16), st = G ? 256 : 512;
      if (G) {
#pragma unroll
        for (int k = 0; k < 8; k++) xr[k] = lds128u(sl + k * 256);
      }
      float s0 = 0.f, s1 = 0.f, q0 = 0.f, q1 = 0.f, s2 = 0.f, s3 = 0.f, q2 = 0.f, q3 = 0.f;
      float v[64];
#pragma unroll
      for (int h = 0; h < 2; h++)
        if (h == 0 || G) {
#pragma unroll
          for (int k = 4 * h; k < 4 * h + 4; k++) {
            float* u = v + 8 * k;
            u[0] = bf_lo(xr[k].x); u[1] = bf_hi(xr[k].x); u[2] = bf_lo(xr[k].y); u[3] = bf_hi(xr[k].y);
            u[4] = bf_lo(xr[k].z); u[5] = bf_hi(xr[k].z); u[6] = bf_lo(xr[k].w); u[7] = bf_hi(xr[k].w);
#pragma unroll
            for (int i = 0; i < 8; i += 4) {
              s0 += u[i]; s1 += u[i + 1]; s2 += u[i + 2]; s3 += u[i + 3];
              q0 = fmaf(u[i], u[i], q0); q1 = fmaf(u[i + 1], u[i + 1], q1); q2 = fmaf(u[i + 2], u[i + 2], q2); q3 = fmaf(u[i + 3], u[i + 3], q3);
            }
          }
        }
      float sum = (s0 + s1) + (s2 + s3), sq = (q0 + q1) + (q2 + q3);
#pragma unroll
      for (int o = 1; o < 32; o <<= 1)
        if (o < 16 || !G) { sum += __shfl_xor_sync(~0u, sum, o); sq += __shfl_xor_sync(~0u, sq, o); }
      const float mean = sum * (1.f / D_);
      const float rstd = rsqrt_f(fmaxf(fmaf(-mean, mean, sq * (1.f / D_)), 0.f) + 1e-5f), nmr = -mean * rstd;
      if (FK_S && G == 0 && bx < 32 && lane < 2) st_msg(&S->st0[(bx * 2 + warp - 2) * 2 + lane], __float_as_uint(rstd), __float_as_uint(nmr), epoch + 1, 0);
#pragma unroll
      for (int h = 0; h < 2; h++)
        if (h == 0 || G) {
#pragma unroll
          for (int k = 4 * h; k < 4 * h + 4; k++) {
            const float* u = v + 8 * k;
            sts128u(sl + k * st, pack_bf16(fmaf(u[0], rstd, nmr), fmaf(u[1], rstd, nmr)), pack_bf16(fmaf(u[2], rstd, nmr), fmaf(u[3], rstd, nmr)),
                    pack_bf16(fmaf(u[4], rstd, nmr), fmaf(u[5], rstd, nmr)), pack_bf16(fmaf(u[6], rstd, nmr), fmaf(u[7], rstd, nmr)));
          }
        }
      fence_async_smem();
      if (warp == FK_DRY) { if (FK_DRY >= 4) asm volatile("bar.arrive 3, 320;" ::: "memory"); break; }
      const int kq = bx >> 5;
      if (elect_one()) {
        bulk_store(S->n + (size_t)(G * 256 + bx * 2 + (G ? 0 : warp - 2)) * D_, stg, G ? 4096 : 2048); bulk_commit();
        if (G == 0) { bulk_wait<0>(); rel_fence<0>(); red_add(&S->cntN[cnt_idx(kq)], 1);
          TRACE(42 + warp);
        }
      }
      if (G == 0) named_bar<3, 320>();
      if (elect_one()) {
        if (G == 0 && warp == 2) { if (FK_QW) spin(FK_QW); else mbar_wait(BAR(B_FULL + FK_QUIET), 0); }
        if (G >= 4) { bulk_wait<1>(); red_add(&S->cntN[(G - 1) * 32 + kq], 2); }
#pragma unroll 1
        for (int k = G ? nc + 1 : 0; k < (warp == 2 ? nc + 2 : 1); k++) {
          mbar_expect_tx(mf + (k & 3) * 8, 4096);
          bulk_load(ring + ((k + 1) & 3) * 4096, k < 6 ? x + (size_t)((k + 4 - warp) * 256 + bx * 2) * D_ : src + (k - 6) * 2 * D_, 4096, mf + (k & 3) * 8, k < 6 ? pol<7>() : pol<2>());
        }
        if (G == 1 || G == 2 || G == 7) { bulk_wait<0>(); rel_fence<1>(); red_add(&S->cntN[G * 32 + kq], 2); if (G > 1) TRACE(44 + (G & 3)); }
      }
      __syncwarp();
      if (warp == 3 && G) break;
    }
    if (!FK_S) epoch = ld_rlx(S->epoch);
  }
  asm volatile("barrier.cluster.wait.acquire.aligned;" ::: "memory");
  int cl, grp, gi;
  asm volatile("{\n.reg .b32 ra;\nmapa.shared::cluster.u32 ra, %1, 0;\nld.volatile.shared::cluster.u32 %0, [ra];\n}" : "=r"(cl) : "r"(sb + BK_OFF) : "memory");
  cl = __shfl_sync(~0u, cl, 0);
  split_assign(cl, grp, gi);
  const uint32_t tag = epoch + 1;
  const int j = gi >> 2, m4 = gi & 3, t = grp * 2 + rank;
  const int cgrp = m4 * 2 + j;
  const int b = t * 8 + cgrp;
  const bool moe = gi < 7;
  const int eb = (j ? 64 + grp * 6 : grp * 8) + m4 * 2 + rank;

  if (warp < 4) {
    auto prefetch_piece = [&](int p) { if (!(FK_X & 1) && !((FK_X & 8) && p >= 12)) pf_bulk(prm.we[p >> 3] + (size_t)((p & 7) * 128 + b) * 7168, 7168); };
    auto weight_box = [&](int n, uint32_t bar) {
      if (moe && !(FK_X & 2) && !((FK_X & 8) && n >= 12)) {
        asm volatile("mbarrier.expect_tx.relaxed.cta.shared::cta.b64 [%0], 8192;" ::"r"(bar) : "memory");
        tma_2d(sb + SP_OFF + (n & 3) * 8192, &prm.wg + (n >> 3), eb * 32, (n & 7) * 128, bar, pol<3>());
      }
    };
    if (warp == 0) {
      const unsigned* flagAddr = &S->cntN[cnt_idx(lane)];
      const unsigned tgt = tag * 64u;
      if (elect_one()) {
        if (FK_A0W) spin(FK_A0W);
        if (FK_S) { tma_3d(sb + SLOT, &prm.xb, 0, m4 * 4, BAR(B_FULL), POL_NORMAL); tma_3d(sb + 2 * SLOT, &prm.xb, 0, m4 * 4 + 2, BAR(B_FULL), POL_NORMAL); }
#pragma unroll 1
        for (int g = 0; g < FK_NA0; g++) tma_2d(sb + g * STAGE, &prm.ws[j], g * 64, t * 128, BAR(B_FULL + g), pol<0>());
      }
      if (lane == 0) TRACE(59);
      unsigned ready = FK_S | __ballot_sync(~0u, lane < 8 && cnt0 == tgt);
      fence_async_global();
      if (lane >= 4) sts32v(sb + POLL_OFF + lane * 4, tgt - 1);
      if (FK_P0D) spin(FK_P0D);
      auto ensure = [&](int g) {
        int it = 0;
        while (!((ready >> g) & 1)) {
          ready |= __ballot_sync(~0u, (lane >> 2) == (g >> 2) && ld_rlx(flagAddr) == tgt);
          SPIN_CHECK(it);
        }
        fence_async_global();
      };
#pragma unroll 1
      for (int g = FK_S; g < 32; g++) {
        const int s = g & 3;
        const uint32_t sa = sb + s * STAGE, fb = BAR(B_FULL + s);
        if (g >= 4) {
          if (FK_E4 && g == 4) ensure(4);
          mbar_wait(BAR(B_EMPTY + s), ((g >> 2) - 1) & 1);
          if (lane < 8 && ((~ready >> (lane * 4)) & 15))
            asm volatile("cp.async.cg.shared.global [%0], [%1], 16;" ::"r"(sb + POLL_OFF + lane * 16), "l"(&S->cntN[lane * 32]) : "memory");
          if (elect_one()) { TRACE2(128 + g); mbar_expect_tx(fb, STAGE); tma_2d(sa, &prm.ws[j], g * 64, t * 128, fb, pol<0>()); }
        }
        if (!((ready >> g) & 1)) {
          unsigned v;
          asm volatile("ld.volatile.shared.u32 %0, [%1];" : "=r"(v) : "r"(sb + POLL_OFF + lane * 4) : "memory");
          ready |= __ballot_sync(~0u, v == tgt) & ~15u;
          ensure(g);
        }
        if (elect_one()) {
          if (g < FK_NOMC) { tma_3d(sa + SLOT, &prm.n, g * 64, m4 * 4, fb, pol<4>()); tma_3d(sa + 2 * SLOT, &prm.n, g * 64, m4 * 4 + 2, fb, pol<4>()); }
          else tma_3d_mc(sa + SLOT + rank * SLOT, &prm.n, g * 64, m4 * 4 + rank * 2, fb, pol<4>());
          if (g >= FK_NA0 && g < 4) tma_2d(sa, &prm.ws[j], g * 64, t * 128, fb, pol<0>());
          TRACE2(64 + g);
        }
        if ((unsigned)(g - FK_WSPF) < 4u)
          asm volatile("prefetch.global.L2 [%0];" ::"l"(prm.wsp[j] + (size_t)(t * 128 + m4 * 32 + (g - FK_WSPF) * 8 + (lane >> 2)) * 4096 + 3584 + (lane & 3) * 128));
      }
      asm volatile("cp.async.wait_all;" ::: "memory");
    }
    asm volatile("" ::: "memory");
    if (warp == 1) {
      const uint32_t rb = sb + (m4 * 32 + lane) * 128 + ((lane & 7) << 4);
      float a0 = 0.f, a1 = 0.f, a2 = 0.f, a3 = 0.f;
#pragma unroll 1
      for (int g = 0; g < 32; g++) {
        const int s = g & 3;
        mbar_wait(BAR(B_FULL + s), (g >> 2) & 1);
        uint4 u[8];
#pragma unroll
        for (int c = 0; c < 8; c++) u[c] = lds128u((rb + s * STAGE) ^ (c << 4));
        u[7].x = __shfl_sync(~0u, u[7].x, lane);
        if (elect_one()) {
          mbar_arrive(BAR(B_EMPTY + s)); TRACE2(160 + g);
          if (g >= 8 && g < 18) prefetch_tmap(&prm.p + g - 8);
          if (FK_NP && g >= FK_G1 && (g - FK_G1) % FK_GP == 0 && (g - FK_G1) / FK_GP < FK_NP) prefetch_piece(4 + (g - FK_G1) / FK_GP);
          const int p = (g - FK_G0) >> FK_GS;
          if (g >= FK_G0 && !((g - FK_G0) & FK_GS) && (p < 8 ? moe && FK_TD == 1 : p < 12 && FK_TX)) {
            asm volatile("mbarrier.expect_tx.relaxed.cta.shared::cta.b64 [%0], 512;" ::"r"(BAR(B_RSDONE)) : "memory");
            tma_3d(sb + SINK_OFF, &prm.tch[p >> 3], p < 8 ? p : cgrp, p < 8 ? eb * 32 : t * 128 + (p - 8) * 32, BAR(B_RSDONE), POL_NORMAL);
          }
        }
#pragma unroll
        for (int c = 0; c < 8; c++) {
          a0 += bf_lo(u[c].x) + bf_lo(u[c].y); a1 += bf_hi(u[c].x) + bf_hi(u[c].y);
          a2 += bf_lo(u[c].z) + bf_lo(u[c].w); a3 += bf_hi(u[c].z) + bf_hi(u[c].w);
        }
      }
      if (lane == 0) mbar_arrive(BAR(B_RSDONE));
      mbar_wait(BAR(B_RSDONE), 0);
      st_msg8(&S->rs[j * S_ + t * 128 + m4 * 32 + lane], __float_as_uint((a0 + a1) + (a2 + a3)), tag);
    }
    asm volatile("" ::: "memory");
    if (warp >= 2) {
      float* const mod = S->mod[tag & 1];
      if (warp == 3) {
        const uint32_t stab = sb + TAB_OFF, stg = stab + 512;
        {
          const uint32_t cw = __ldg(reinterpret_cast<const uint32_t*>(cvec + t * 64) + lane);
          const uint32_t sp = pack_bf16(silu_f(bf_lo(cw)), silu_f(bf_hi(cw)));
          sts64u(stab + lane * 8, sp << 16, sp & 0xFFFF0000u);
        }
        float acc[8];
#pragma unroll
        for (int i = 0; i < 8; i++) acc[i] = 0.f;
#pragma unroll 1
        for (int n = -3; n < ((FK_X & 16) ? 8 : 24); n++) {
          if (n < ((FK_X & 16) ? 5 : 21) && elect_one()) {
            mbar_expect_tx(mf + (n & 3) * 8, 4096);
            tma_2d(ring + (n & 3) * 4096, &prm.wm, ((n + 3) >> 3) * 2048 + cgrp * 256, t * 64 + ((n + 3) & 7) * 8, mf + (n & 3) * 8, pol<1>());
          }
          if (n < 0) continue;
          const uint32_t sl = ring + ((n + 1) & 3) * 4096 + lane * 16;
          const float4 sv0 = lds128(stab + (n & 7) * 32), sv1 = lds128(stab + (n & 7) * 32 + 16);
          const float sc[8] = {sv0.x, sv0.y, sv0.z, sv0.w, sv1.x, sv1.y, sv1.z, sv1.w};
          mbar_wait(mf + ((n + 1) & 3) * 8, ((n + 1) >> 2) & 1);
          uint4 v[8];
#pragma unroll
          for (int u = 0; u < 8; u++) v[u] = lds128u(sl + u * 512);
#pragma unroll
          for (int u = 0; u < 8; u++) {
            acc[0] = fmaf(sc[u], bf_lo(v[u].x), acc[0]); acc[1] = fmaf(sc[u], bf_hi(v[u].x), acc[1]);
            acc[2] = fmaf(sc[u], bf_lo(v[u].y), acc[2]); acc[3] = fmaf(sc[u], bf_hi(v[u].y), acc[3]);
            acc[4] = fmaf(sc[u], bf_lo(v[u].z), acc[4]); acc[5] = fmaf(sc[u], bf_hi(v[u].z), acc[5]);
            acc[6] = fmaf(sc[u], bf_lo(v[u].w), acc[6]); acc[7] = fmaf(sc[u], bf_hi(v[u].w), acc[7]);
          }
          asm volatile("" : "+f"(acc[0]) :: "memory");
          if ((n & 7) == 7) {
            sts128(stg + lane * 32, acc[0], acc[1], acc[2], acc[3]); sts128(stg + lane * 32 + 16, acc[4], acc[5], acc[6], acc[7]);
#pragma unroll
            for (int i = 0; i < 8; i++) acc[i] = 0.f;
            fence_async_smem();
            if (elect_one()) {
              asm volatile("cp.reduce.async.bulk.global.shared::cta.bulk_group.add.f32 [%0], [%1], 1024;" ::"l"(mod + (n >> 3) * 2048 + cgrp * 256), "r"(stg) : "memory");
              bulk_commit();
              if (n != 15) { bulk_wait<0>(); rel_fence<2>(); red_add(&S->cntMod[n > 7 ? 32 : 0], 1); } else bulk_wait_read<0>();
              TRACE(n > 7 ? 34 + (n >> 3) : 9);
            }
          }
        }
      } else {
        wait_cnt(S->cntMod, tag * 128u);
        if (lane == 0) TRACE(10);
        float4 sa[8];
        {
          const float4 c0 = ldg_cg(mod + D_ + m4 * 256 + lane * 8), c1 = ldg_cg(mod + D_ + m4 * 256 + lane * 8 + 4);
#pragma unroll
          for (int i = 0; i < 8; i++) {
            const float4 sv = ldg_cg(mod + (i >> 1) * 256 + lane * 8 + (i & 1) * 4);
            const uint32_t s0 = pack_bf16(sv.x, sv.y), s1 = pack_bf16(sv.z, sv.w);
            sa[i] = make_float4(bf_lo(s0), bf_hi(s0), bf_lo(s1), bf_hi(s1));
          }
          const uint32_t cw[4] = {pack_bf16(c0.x, c0.y), pack_bf16(c0.z, c0.w), pack_bf16(c1.x, c1.y), pack_bf16(c1.z, c1.w)};
#pragma unroll
          for (int q = 0; q < 4; q++) sts32v(sb + T1_OFF + (lane >> 2) * 64 + q * 16 + (lane & 3) * 4, add_bf16x2(cw[q], 0x3F803F80u) ^ (j ? 0x80008000u : 0u));
        }
        float ul = 0.f;
#pragma unroll 1
        for (int r = 0; r < 8; r++) {
          if (r < 6 && elect_one()) {
            mbar_expect_tx(mf + ((nc + 2) & 3) * 8, 4096);
            bulk_load(ring + ((nc + 3) & 3) * 4096, src + (r + 2) * 2 * D_, 4096, mf + ((nc + 2) & 3) * 8, pol<2>());
          }
          mbar_wait(mf + (nc & 3) * 8, (nc >> 2) & 1); nc++;
          uint4 v[8];
          float u[4] = {0.f, 0.f, 0.f, 0.f};
#pragma unroll
          for (int i = 0; i < 8; i++) v[i] = lds128u(ring + (nc & 3) * 4096 + lane * 16 + i * 512);
#pragma unroll
          for (int i = 0; i < 8; i++) {
            const float4 s0 = sa[2 * (i & 3)], s1 = sa[2 * (i & 3) + 1];
            float &u0 = u[(i >> 2) * 2], &u1 = u[(i >> 2) * 2 + 1];
            u0 = fmaf(bf_lo(v[i].x), s0.x, u0); u1 = fmaf(bf_hi(v[i].x), s0.y, u1); u0 = fmaf(bf_lo(v[i].y), s0.z, u0); u1 = fmaf(bf_hi(v[i].y), s0.w, u1);
            u0 = fmaf(bf_lo(v[i].z), s1.x, u0); u1 = fmaf(bf_hi(v[i].z), s1.y, u1); u0 = fmaf(bf_lo(v[i].w), s1.z, u0); u1 = fmaf(bf_hi(v[i].w), s1.w, u1);
          }
          const float ua = u[0] + u[1], ub = u[2] + u[3];
          float us = ((lane & 1) ? ub : ua) + __shfl_xor_sync(~0u, (lane & 1) ? ua : ub, 1);
#pragma unroll
          for (int o = 16; o > 1; o >>= 1) us += __shfl_xor_sync(~0u, us, o);
          if ((lane >> 1) == r) ul = jw ? -us : us;
        }
        if (lane < 16) st_msg8(&S->u[jw * D_ + e0 + lane], __float_as_uint(ul), tag);
        if (lane == 0) TRACE(11);
#pragma unroll
        for (int i = 0; i < 4; i++) sts128u(ring + lane * 16 + i * 512, SENT, SENT, SENT, SENT);
        fence_async_smem();
        if (elect_one()) {
#pragma unroll 1
          for (int i = 0; i < 9; i++)
            bulk_store(i < 4 ? &S->part[b * 512 + i * 128] : i == 4 ? &S->stats[b * 128] : &S->rowsH[((i - 5) >> 1) * 4096 + (t * 2 + (i & 1)) * 128 + cgrp * 16], ring, i < 5 ? 2048 : 256);
          bulk_store(&S->flagP[b * 32], ring, 128);
          bulk_commit(); bulk_wait<0>();
        }
        if (lane == 12) S->claim[cl * 8] = 0;
        if (lane < 12) reinterpret_cast<float4*>(S->mod[~tag & 1] + b * 48)[lane] = make_float4(0.f, 0.f, 0.f, 0.f);
      }
      named_bar<1, 64>();
    }
    asm volatile("setmaxnreg.dec.sync.aligned.u32 40;" ::: "memory");
    if (warp == 2) {
      if (elect_one()) { rel_fence<4>(); mbar_arrive(BAR(B_RSDONE)); TRACE(30); }
      const int scl = blk_src(lane, cgrp);
      const unsigned* flagAddr = &S->flagP[(t * 8 + (scl >> 2)) * 32 + (scl & 3)];
      const unsigned* cellAddr = &S->flagP[(t * 8 + (lane & 7)) * 32];
      sts32v(sb + PFLAG_OFF + lane * 4, tag - 1);
      if (lane < 4) mbar_arrive(BAR(B_FULL2 + lane));
      mbar_wait(BAR(B_PREADY), 0);
      unsigned ready = 15;
      int u = 4, i7 = 0, kk = 0; uint32_t ph = 1;
#pragma unroll 1
      for (int q = 4; q < 32; q++) {
        const int src = FK_SKIP ? i7 + (i7 >= cgrp) : i7 == cgrp ? 7 : i7;
        if (!((ready >> q) & 1)) {
          unsigned v;
          asm volatile("ld.volatile.shared.u32 %0, [%1];" : "=r"(v) : "r"(sb + PFLAG_OFF + scl * 4) : "memory");
          ready |= __ballot_sync(~0u, v == tag);
          int it = 0;
          while (!((ready >> q) & 1)) {
            ready |= __ballot_sync(~0u, (unsigned)(lane - q) < 7u && ld_rlx(flagAddr) == tag);
            SPIN_CHECK(it);
          }
          fence_async_global();
        }
        if ((q & ~4) == 8) mbar_wait(BAR(B_PS - 2 + (q >> 2)), 0);
        mbar_wait(BAR(q >= 8 ? B_EMPTY2 + u : q == 4 ? B_EMPTY + 2 : B_FULL2 + u), ph);
        if (q >= 8) grid_wait();
        if (elect_one()) {
          TRACE3(128 + q);
          mbar_expect_tx(BAR(B_FULL2 + u), SLOT);
          tma_2d(sb + buf_off(u), &prm.p, (src >> 1) * 256 + kk * 64, (src & 1) * S_ + t * 128, BAR(B_FULL2 + u), pol<5>());
        }
        if (((~ready >> q) & 15) && lane < 8)
          asm volatile("cp.async.cg.shared.global [%0], [%1], 16;" ::"r"(sb + PFLAG_OFF + lane * 16), "l"(cellAddr) : "memory");
        if (++u == 5) { u = 0; ph ^= 1; }
        if (++i7 == 7) { i7 = 0; kk++; }
      }
      asm volatile("cp.async.wait_all;" ::: "memory");
    }
    asm volatile("" ::: "memory");
    if (warp == 0) {
      int u = 0; uint32_t ph = 1;
#pragma unroll 1
      for (int q = 0; q < 32; q++) {
        const int sc = blk_src(q, cgrp);
        mbar_wait(BAR(q >= 5 ? B_EMPTY2 + u : q < 2 ? B_ADONE : q == 4 ? B_EMPTY + 3 : B_EMPTY + 1), q >= 2 ? ph : 0);
        if (elect_one()) {
          TRACE3(160 + q);
          mbar_expect_tx(BAR(B_FULL2 + u), SLOT);
          tma_2d_mc(sb + buf_off(u) + SLOT + rank * 8192, &prm.wd[(sc >> 2) & 1], (sc >> 3) * 256 + (sc & 3) * 64, cgrp * 128 + rank * 64, BAR(B_FULL2 + u), pol<6>());
          if (q & 1) { const int p = 4 + FK_NA + FK_NP + ((q - FK_QP) >> 1); if (q >= FK_QP && p < (FK_TD ? 16 : 24)) prefetch_piece(p);
            else if (FK_TD == 3 && moe && p >= 16 && p < 24) {
              asm volatile("mbarrier.expect_tx.relaxed.cta.shared::cta.b64 [%0], 512;" ::"r"(BAR(B_B27)) : "memory");
              tma_3d(sb + KEY_OFF, &prm.tch[0], p - 16, eb * 32, BAR(B_B27), POL_NORMAL);
            } }
          else if (q >= 10 && q < 2 * FK_NL + 2) weight_box((q >> 1) - 1, BAR(B_FULL2 + (u == 4 ? 0 : u + 1)));
        }
        if (++u == 5) { u = 0; ph ^= 1; }
      }
      if (elect_one()) {
#pragma unroll 1
        for (int n = FK_NL; n < 15; n++) weight_box(n, BAR(B_WF));
        mbar_expect_tx(BAR(B_DN), moe ? 65536 : 0);
#pragma unroll 1
        for (int i = 0; i < 9; i++) {
          if ((i & 3) == 0) mbar_wait(BAR(B_EMPTY2 + 2 + (i >> 2)), 1);
          if (i == 0) { mbar_arrive(BAR(B_B27)); weight_box(15, BAR(B_WF)); mbar_arrive(BAR(B_WF)); }
          else if (moe)
            asm volatile("cp.async.bulk.tensor.5d.shared::cluster.global.mbarrier::complete_tx::bytes.L2::cache_hint [%0], [%1, {0, 0, 0, %3, %4}], [%2], %5;"
                         ::"r"(sb + RKA_OFF + (i + (i >> 3) * 4) * 8192), "l"(&prm.wdn), "r"(BAR(B_DN)), "r"(eb * 2), "r"(i * 2 - 2), "l"(pol<3>()) : "memory");
        }
      }
    }
    asm volatile("" ::: "memory");
    if (warp == 1) {
      if (elect_one()) {
#pragma unroll 1
        for (int kk = 0; kk < 4; kk++) {
          mbar_wait(BAR(B_PREADY + kk), 0);
#pragma unroll 1
          for (int i = 0; i < 4; i++) {
            tma_store_2d(&prm.ps, sb + pstage(kk) + i * 4096, m4 * 256 + kk * 64, j * S_ + t * 128 + i * 32);
            if (kk >= FK_PS0 && i < 3) { const unsigned next = clk32() + FK_PSPACE; while ((int)(clk32() - next) < 0) __nanosleep(20); }
          }
          bulk_commit(); bulk_wait<0>();
          if (kk < 2) mbar_arrive(BAR(B_PS + kk));
          rel_fence<3>();
          st_rlx(&S->flagP[b * 32 + kk], tag);
          TRACE(40 + kk); TRACE3(128 + kk);
        }
        if (FK_XD) { const unsigned next = clk32() + FK_XD; while ((int)(clk32() - next) < 0) __nanosleep(20); }
        mbar_expect_tx(BAR(B_EFULL), (FK_X & 4) ? 0 : 32768);
#pragma unroll 1
        for (int i = 0; i < 8; i++) {
          if (!(FK_X & 4)) tma_3d(sb + E_OFF + i * 4096, &prm.xm, t * 128 + i * 16, cgrp * 2, BAR(B_EFULL), pol<8>());
          const unsigned next = clk32() + FK_SPACE;
          while ((int)(clk32() - next) < 0) __nanosleep(20);
        }
      }
      __syncwarp();
    }
    asm volatile("" ::: "memory");
    if (warp == 3) {
      if (elect_one()) {
        fence_async_smem();
        unsigned next = clk32();
#pragma unroll 1
        for (int n = 0; n < 4 + FK_NA + (FK_TD == 2) * 8; n++) {
          if (n < 4) weight_box(n, BAR(B_WF));
          else if (n < 4 + FK_NA) prefetch_piece(n + FK_NP);
          else if (moe) {
            asm volatile("mbarrier.expect_tx.relaxed.cta.shared::cta.b64 [%0], 512;" ::"r"(BAR(B_TAB)) : "memory");
            tma_3d(sb + KEY_OFF, &prm.tch[0], n - 4 - FK_NA, eb * 32, BAR(B_TAB), POL_NORMAL);
          }
          if (n == 3) mbar_arrive(BAR(B_WF));
          if (!FK_TX && (unsigned)(n - FK_XN) < 4u) pf_bulk(x + (size_t)(b * 16 + (n - FK_XN) * 4) * D_, 8192);
          next += FK_PACE;
          while ((int)(clk32() - next) < 0) __nanosleep(20);
        }
        TRACE(37);
      }
      __syncwarp();
      int it = 0;
      if (!(FK_X & 16)) wait_cnt(&S->cntMod[32], tag * 128u);
      mbar_wait(BAR(B_PREADY + 2), 0);
      {
        const float* mp = S->mod[tag & 1] + cgrp * 128 + lane * 4;
        const float4 ga = ldg_cg(mp + 2 * D_), sv = ldg_cg(mp + 3 * D_), cb = ldg_cg(mp + 4 * D_), gb = ldg_cg(mp + 5 * D_);
        const uint2 wr = __ldg(reinterpret_cast<const uint2*>(prm.w_r + cgrp * 128 + lane * 4));
        const uint32_t Aa = add_bf16x2(pack_bf16(cb.x, cb.y), 0x3F803F80u), Ab = add_bf16x2(pack_bf16(cb.z, cb.w), 0x3F803F80u);
        const uint32_t Sa = pack_bf16(sv.x, sv.y), Sb = pack_bf16(sv.z, sv.w), Ga = pack_bf16(gb.x, gb.y), Gb = pack_bf16(gb.z, gb.w);
        const float w0 = bf_lo(Aa) * bf_lo(wr.x), w1 = bf_hi(Aa) * bf_hi(wr.x), w2 = bf_lo(Ab) * bf_lo(wr.y), w3 = bf_hi(Ab) * bf_hi(wr.y);
        const uint32_t tb = sb + TAB_OFF + (lane >> 3) * 64 + (lane & 1) * 32 + ((lane >> 1) & 3) * 4, Wa = pack_bf16(w0, w1), Wb = pack_bf16(w2, w3);
        auto put = [&](int off, uint32_t a, uint32_t c) { sts32v(tb + off, a); sts32v(tb + off + 16, c); };
        put(T_WH, Wa, Wb); put(T_ONE, 0x3F803F80u, 0x3F803F80u);
        put(T_WL, pack_bf16(w0 - bf_lo(Wa), w1 - bf_hi(Wa)), pack_bf16(w2 - bf_lo(Wb), w3 - bf_hi(Wb)));
        put(T_GA, pack_bf16(ga.x, ga.y), pack_bf16(ga.z, ga.w)); put(T_A, Aa, Ab); put(T_S, Sa, Sb); put(T_G, Ga, Gb);
        float c1 = (w0 + w1) + (w2 + w3), c2 = (bf_lo(Sa) * bf_lo(wr.x) + bf_hi(Sa) * bf_hi(wr.x)) + (bf_lo(Sb) * bf_lo(wr.y) + bf_hi(Sb) * bf_hi(wr.y));
#pragma unroll 1
        for (int h = 0; h < 2; h++) {
#pragma unroll
          for (int o = 16; o; o >>= 1) { c1 += __shfl_xor_sync(~0u, c1, o); c2 += __shfl_xor_sync(~0u, c2, o); }
          if (h) break;
          if (t == 0 && lane == 0) st_msg(&S->cst[cgrp], __float_as_uint(c1), __float_as_uint(c2), tag, 0);
          uint4 cm; it = 0;
          while (true) {
            cm = ld_msg(&S->cst[lane & 7]);
            if (__all_sync(~0u, cm.z == tag)) break;
            SPIN_CHECK(it); __nanosleep(200);
          }
          c1 = 0.25f * __uint_as_float(cm.x); c2 = 0.25f * __uint_as_float(cm.y);
        }
        if (lane == 0) { sts128u(sb + CST_OFF, __float_as_uint(c1), __float_as_uint(c2), tag, b | eb << 8 | (int)moe << 16); TRACE(27); }
      }
    }
    asm volatile("" ::: "memory");
    if (warp & 1) {
      const uint2* src = (warp == 3 ? &S->u[cgrp * 128] : &S->rs[t * 128]) + lane;
      const uint2* src1 = src + (warp == 3 ? D_ : S_);
      uint2 m[8]; int it = 0;
      while (true) {
        bool ok = true;
#pragma unroll
        for (int i = 0; i < 8; i++) { m[i] = ld_msg8(((i & 1) ? src1 : src) + (i >> 1) * 32); ok &= m[i].y == tag; }
        if (__all_sync(~0u, ok)) break;
        SPIN_CHECK(it);
      }
      uint32_t rk[12];
#pragma unroll
      for (int i = 0; i < 4; i++) {
        const float r0 = __uint_as_float(m[2 * i].x) * (warp == 3 ? 0.5f : 1.f), r1 = __uint_as_float(m[2 * i + 1].x) * (warp == 3 ? 0.5f : 1.f);
        const uint32_t hi = pack_bf16(r0, r1), lo = pack_bf16(r0 - bf_lo(hi), r1 - bf_hi(hi));
        rk[3 * i] = hi; rk[3 * i + 1] = warp == 3 ? hi : lo; rk[3 * i + 2] = warp == 3 ? lo : hi;
      }
      mbar_wait(BAR(B_B27), 0);
#pragma unroll
      for (int i = 0; i < 4; i++) sts128u(sb + RKA_OFF + (warp & 2) * 1024 + (i * 32 + lane) * 16, rk[3 * i], rk[3 * i + 1], rk[3 * i + 2], 0);
      fence_async_smem();
      if (elect_one()) { mbar_arrive(BAR(B_TAB)); TRACE(26); }
    }
    asm volatile("" ::: "memory");
    if (warp == 1) {
      mbar_wait(BAR(B_PREADY), 1);
      if (lane == 0) TRACE(60);
      const int lr = lds32u(sb + BK_OFF + (lane >> 4) * 4);
      {
        const uint4 v = lds128u(sb + E_OFF + (lr >> 4) * 4096 + (lane & 8) * 256 + (lr & 15) * 128 + (((lane ^ lr) & 7) << 4));
        st_msg(&S->rowsB[(t * 2 + (lane >> 4)) * 128 + cgrp * 16 + (lane & 15)], v.x, v.y, v.z, v.w);
      }
      const unsigned cmask = __reduce_or_sync(~0u, 1u << (lr >> 4)) | FK_OMASK;
      unsigned todo = ~cmask & 255, smask = 0;
      int r1 = 0, r2 = 0;
#pragma unroll 1
      for (int h = 0; h < 2; h++) {
        if (elect_one()) {
#pragma unroll 1
          for (; todo; todo &= todo - 1) {
            const int i = __ffs(todo) - 1;
            asm volatile("cp.async.bulk.tensor.3d.global.shared::cta.bulk_group.L2::cache_hint [%0, {0, %2, %3}], [%1], %4;"
                         ::"l"(&prm.om), "r"(sb + E_OFF + i * 4096), "r"(t * 128 + i * 16), "r"(cgrp * 2), "l"(pol<9>()) : "memory");
            if (h == 0) {
              const unsigned c0 = clk32();
              uint32_t sel;
              do {
                asm volatile("{\n.reg .pred p;\nmbarrier.test_wait.parity.shared::cta.b64 p, [%1], 1;\nselp.u32 %0, 1, 0, p;\n}" : "=r"(sel) : "r"(BAR(B_B27)) : "memory");
              } while (!sel && clk32() - c0 < FK_OSPACE);
            }
          }
          TRACE(61 + h);
        }
        if (h) break;
        mbar_wait(BAR(B_B27), 1);
        r1 = lds32u(sb + SEL_OFF) - t * 128; r2 = lds32u(sb + SEL_OFF + 4) - t * 128;
        smask = ((unsigned)r1 < 128u ? 1u << (r1 >> 4) : 0) | ((unsigned)r2 < 128u ? 1u << (r2 >> 4) : 0);
        todo = cmask & ~smask;
        if (FK_ODELAY) spin(FK_ODELAY);
      }
#pragma unroll 1
      for (; smask; smask &= smask - 1) {
        const int i = __ffs(smask) - 1;
#pragma unroll 2
        for (int r = lane >> 4; r < 16; r += 2) {
          const uint4 v = lds128u(sb + E_OFF + i * 4096 + (lane & 8) * 256 + r * 128 + (((lane ^ r) & 7) << 4));
          if (i * 16 + r != r1 && i * 16 + r != r2) reinterpret_cast<uint4*>(out + (size_t)(t * 128 + i * 16 + r) * D_)[cgrp * 16 + (lane & 15)] = v;
        }
      }
      if (elect_one()) { bulk_commit(); bulk_wait_read<0>(); TRACE(29); }
    }
    asm volatile("" ::: "memory");
    if (warp == 2) {
      const uint4* cp = &S->cand[(lane >> 1) * 8];
      mbar_wait(BAR(B_B27), 0);
      uint4 m = ld_msg(cp);
      bool ok = __all_sync(~0u, m.z == tag);
      named_bar<5, 288>();
      uint32_t k1, k2;
      {
        const uint4 k4 = lds128u(sb + KEY_OFF + lane * 16);
        const uint32_t ka = max(k4.x, k4.y), kb = max(k4.z, k4.w), m1 = max(ka, kb), m2 = max(min(ka, kb), ka > kb ? min(k4.x, k4.y) : min(k4.z, k4.w));
        k1 = redux_max(m1); k2 = redux_max(m1 == k1 ? m2 : m1);
        if (lane == 0) { st_msg(&S->cand[t * 8], k1, k2, tag, 0); sts64u(sb + BK_OFF, key_row(k1) & 127, key_row(k2) & 127); mbar_arrive(BAR(B_BK)); TRACE(13); }
      }
      int it = 0;
      while (!ok) {
        m = ld_msg(cp);
        ok = __all_sync(~0u, m.z == tag);
        SPIN_CHECK(it);
      }
      warp_top2((lane & 1) ? m.y : m.x, k1, k2);
      const int r1 = key_row(k1), r2 = key_row(k2), slot1 = (r1 >> 7) * 2, slot2 = (r2 >> 7) * 2 + ((r1 >> 7) == (r2 >> 7));
      if (elect_one()) {
        if (moe) {
          fence_async_global();
          bulk_load(sb + H_OFF, &S->rowsH[slot1 * 128], 2048, BAR(B_ROWS), POL_NORMAL);
          bulk_load(sb + H_OFF + 2112, &S->rowsH[slot2 * 128], 2048, BAR(B_ROWS), POL_NORMAL);
        }
        sts64u(sb + SEL_OFF, r1, r2); sts64u(sb + SEL_OFF + 8, slot1 * 2048, slot2 * 2048);
        mbar_expect_tx(BAR(B_ROWS), moe ? 4096 : 0);
        mbar_arrive(BAR(B_B27));
        TRACE(14);
      }
      const int fcol = (b >> 1) * 16 + (lane & 15);
      const float gb = round_bf16(__uint_as_float(ld_rlx(S->mod[tag & 1] + 5 * D_ + fcol)));
      const uint32_t* fbp = reinterpret_cast<const uint32_t*>(&S->rowsB[((b & 1) ? slot2 : slot1) * 128]) + (fcol >> 1);
      uint32_t fb;
      do { fb = ld_rlx(fbp); SPIN_CHECK(it); } while (fb == SENT);
      sts64u(sb + PFLAG_OFF + (lane & 15) * 8, (lane & 1) ? fb & 0xFFFF0000u : fb << 16, __float_as_uint(gb));
      __syncwarp();
      if (lane == 0) {
        sts32(sb + CST_OFF, round_bf16(sigmoid_f(round_bf16(fkey_inv((((b & 1) ? k2 : k1) & ~2047u) | 1024u)))));
        mbar_arrive(BAR(B_FIN));
        if (b == 0) S->epoch[0] = tag;
      }
    }
  } else {
    const int cw = (warp - 4) >> 2;
    const int cwarp = warp - 4;
    const bool elect = (tid & 127) == 0;
    uint32_t rel;
    asm volatile("mapa.shared::cluster.u32 %0, %1, %2;" : "=r"(rel) : "r"(BAR(0)), "r"(tid & 1));
    if (tid & 126) rel = 0;
    asm volatile("" : "+r"(rel));
    auto release = [&](int bar) {
      asm volatile("{\n.reg .pred p;\nsetp.ne.u32 p, %1, 0;\n@p mbarrier.arrive.shared::cluster.b64 _, [%0];\n}" ::"r"(rel + bar * 8), "r"(rel) : "memory");
    };
    const uint32_t da0 = desc_lo(sb + cw * 8192, 16), db0 = desc_lo(sb + SLOT, 8192), db2 = desc_lo(sb + SLOT, 16);

    if (FK_S) {
      const int r = (tid - 128) >> 2;
      const uint32_t base = sb + SLOT + (tid & 3) * 8192 + r * 128 + ((((tid & 3) * 2) | (r & 1)) << 4);
      mbar_wait(BAR(B_FULL), 0);
      uint4 v[8];
#pragma unroll
      for (int c = 0; c < 8; c++) v[c] = lds128u(base ^ (c << 4));
      uint4 m = ld_msg(&S->st0[r * 2]);
      int it = 0;
      while (!__all_sync(~0u, m.z == tag)) { m = ld_msg(&S->st0[r * 2]); SPIN_CHECK(it); }
      if (tid == 128) TRACE(63);
      const float rs = __uint_as_float(m.x), nm = __uint_as_float(m.y);
#pragma unroll
      for (int c = 0; c < 8; c++)
        sts128u(base ^ (c << 4), pack_bf16(fmaf(bf_lo(v[c].x), rs, nm), fmaf(bf_hi(v[c].x), rs, nm)), pack_bf16(fmaf(bf_lo(v[c].y), rs, nm), fmaf(bf_hi(v[c].y), rs, nm)),
                pack_bf16(fmaf(bf_lo(v[c].z), rs, nm), fmaf(bf_hi(v[c].z), rs, nm)), pack_bf16(fmaf(bf_lo(v[c].w), rs, nm), fmaf(bf_hi(v[c].w), rs, nm)));
      fence_async_smem();
      named_bar<2, 256>();
    }
    uint32_t wf[64], uf[64], df[64];
    uint32_t pk[64];
    uint32_t xw[32];
    float lo[64];
    int ln;
    uint32_t so, wo;
    auto p_ready = [&](int kk) { fence_async_smem(); if (elect_one()) mbar_arrive(BAR(B_PREADY + kk)); };
    {
      float pa[64], pb[64];
      {
        float acc[128];
#pragma unroll 1
        for (int g = 0; g < 28; g++) {
          const int s = g & 3;
          mbar_wait(BAR(B_FULL + s), (g >> 2) & 1);
          const uint32_t da = da0 + s * (STAGE >> 4), db = db0 + s * (STAGE >> 4);
          wg_fence();
          wgmma_n256<1>(acc, da, db, g > 0);
#pragma unroll
          for (int k = 1; k < 4; k++) wgmma_n256<1>(acc, da + k * 2, db + k * 128, 1);
          wg_commit();
          wg_wait<1>();
          if (g > 0) { release(B_EMPTY + ((g - 1) & 3)); if (elect) TRACE2(191 + g + cw * 32); }
          STAMP2(g);
        }
        wg_wait<0>();
        release(B_EMPTY + 3);
#pragma unroll
        for (int i = 0; i < 64; i++) {
          asm volatile("mov.b32 %0, %1;" : "=f"(pa[i]) : "f"(acc[i]));
          asm volatile("mov.b32 %0, %1;" : "=f"(pb[i]) : "f"(acc[64 + i]));
        }
      }
      if (elect) TRACE(3 + tr);
      STAMP2(28);
#pragma unroll 1
      for (int s = 0; s < 4; s++) {
        mbar_wait(BAR(B_FULL + s), 1);
        wg_fence();
#pragma unroll
        for (int k = 0; k < 4; k++) wgmma_n128<1>(pa, da0 + s * (STAGE >> 4) + k * 2, db0 + s * (STAGE >> 4) + k * 128);
        wg_commit();
        if (s == 2) { wg_wait<1>(); if (elect) mbar_arrive(BAR(B_A29)); }
      }
      auto b_block = [&](int s) {
        wg_fence();
#pragma unroll
        for (int k = 0; k < 4; k++) wgmma_n128<1>(pb, da0 + s * (STAGE >> 4) + k * 2, db0 + s * (STAGE >> 4) + 1024 + k * 128);
        wg_commit();
      };
      uint4 t0, t1;
      auto load_t = [&](int kk) { t0 = lds128u(sb + T1_OFF + kk * 128 + (ln & 3) * 16); t1 = lds128u(sb + T1_OFF + kk * 128 + 64 + (ln & 3) * 16); };
      auto pack_p = [&](int kk, const float* a) {
        const uint32_t A[8] = {t0.x, t0.y, t0.z, t0.w, t1.x, t1.y, t1.z, t1.w};
#pragma unroll
        for (int i = 0; i < 16; i++) pk[kk * 16 + i] = mul_bf16x2(pack_bf16(a[2 * i], a[2 * i + 1]), A[i >> 1]);
      };
      auto stage_p = [&](int kk) {
#pragma unroll
        for (int k = 0; k < 4; k++) stsm_x4((so ^ (k << 5)) + pstage(kk), pk + kk * 16 + k * 4);
      };
      auto own_block = [&](int q) {
        const uint32_t db = db2 + (buf_off(q) >> 4);
        wg_fence();
        if (q == 0) wgmma_n128_rs<0>(lo, pk, db); else wgmma_n128_rs<1>(lo, pk + q * 16, db);
#pragma unroll
        for (int k = 1; k < 4; k++) wgmma_n128_rs<1>(lo, pk + q * 16 + k * 4, db + k * 2);
        wg_commit();
      };
      b_block(0);
      mbar_wait(BAR(B_RSDONE), 0);
      asm volatile("setmaxnreg.inc.sync.aligned.u32 232;" ::: "memory");
      asm volatile("mov.u32 %0, %%laneid;" : "=r"(ln));
      so = sb + (uint32_t)(cwarp * 16 + (ln & 15)) * 128 + (((ln >> 4) ^ (ln & 7)) << 4);
      wo = sb + SP_OFF + cwarp * 1024 + ((ln & 7) + (ln >> 4) * 8) * 64 + ((((ln >> 3) & 1) ^ ((ln >> 1) & 3)) << 4);
      mbar_wait(BAR(B_A29), 0);
      load_t(0);
      wg_wait<1>();
      reg_fence(pa);
      release(B_ADONE);
      if (elect) TRACE(4 + tr);
      STAMP2(29);
      pack_p(0, pa); stage_p(0);
      if (FK_TR0) { p_ready(0); b_block(1); } else { b_block(1); p_ready(0); }
      if (elect) TRACE(2 + tr);
      wg_wait<1>(); release(B_EMPTY);
      load_t(1);
      b_block(2);
      pack_p(1, pa + 32);
      wg_wait<1>(); release(B_EMPTY + 1);
      STAMP2(30);
      load_t(2);
      b_block(3);
      mbar_wait(BAR(B_FULL2), 0);
      wg_wait<1>(); release(B_EMPTY + 2);
      if (FK_S1 == 0) { mbar_wait(BAR(B_ADONE), 0); stage_p(1); }
      own_block(0);
      if (FK_S1 == 0) p_ready(1);
      mbar_wait(BAR(B_FULL2 + 1), 0);
      if (FK_S1 == 1) mbar_wait(BAR(B_ADONE), 0);
      wg_wait<1>(); release(B_EMPTY + 3);
      reg_fence(pb);
      if (elect) TRACE(1 + tr);
      STAMP2(31);
      if (FK_S1 == 1) stage_p(1);
      own_block(1);
      if (FK_S1 == 1) p_ready(1);
      pack_p(2, pb);
      mbar_wait(BAR(B_FULL2 + 2), 0);
      wg_wait<1>(); release(B_EMPTY2);
      STAMP2(32);
      load_t(3);
      own_block(2);
      pack_p(3, pb + 32);
      mbar_wait(BAR(B_EMPTY + 3), 1);
      mbar_wait(BAR(B_FULL2 + 3), 0);
      wg_wait<1>(); release(B_EMPTY2 + 1);
      STAMP2(33);
      if (FK_S1 == 3) stage_p(1);
      own_block(3);
      if (FK_S1 == 3) p_ready(1);
      mbar_wait(BAR(B_WF), 0);
      wg_wait<1>(); release(B_EMPTY2 + 2);
      STAMP2(34);
    }
    {
      mbar_wait(BAR(B_FULL2 + 4), 0);
#pragma unroll
      for (int q = 4; q < 32; q++) {
        const uint32_t da = da0 + (buf_off(q % 5) >> 4) + (q << 16), db = db2 + (buf_off(q % 5) >> 4) + (q << 16);
        wg_fence();
#pragma unroll
        for (int k = 0; k < 4; k++) wgmma_n128<0>(lo, da + k * 2, db + k * 2);
        if (q == FK_QR) wgmma_n128<0, 8>(lo, desc_lo(sb + RKA_OFF, 0) + (cwarp & 4) * 16, desc_lo(sb + RKB_OFF, 0));
        wg_commit();
        if (q == 31) break;
        if (q + 1 == FK_QR) mbar_wait(BAR(B_TAB), 0);
        if (FK_ORD == 1) { wg_wait<1>(); if (q == 28 && rel) rel = BAR(0); release(B_EMPTY2 + (q - 1) % 5); STAMP2(31 + q); }
        if (q == 8 || q == 14) p_ready(q >> 2);
        if (q == 27) mbar_wait(BAR(B_EFULL), 0);
        mbar_wait(BAR(B_FULL2 + (q + 1) % 5), ((q + 1) / 5) & 1);
        if (q >= 27) {
#pragma unroll
          for (int h = 0; h < 2; h++) ldsm_x4((so ^ ((q - 27) << 5)) + E_OFF + cwarp * 2048 + h * 2048, xw + (q - 27) * 4 + h * 16);
        } else if (!(q & 1)) {
          const int n = (q - 4) >> 1;
#pragma unroll
          for (int h = 0; h < 2; h++) ldsm_x4_t((wo ^ (h << 5)) + (n & 3) * 8192, (n < 8 ? wf + n * 8 : uf + (n - 8) * 8) + h * 4);
        } else if (q < 15 && q != 9) {
          const int i = (q - 5 - (q > 9) * 2) >> 1;
#pragma unroll
          for (int h = 0; h < 2; h++) stsm_x4((so ^ (((i & 1) * 2 + h) << 5)) + pstage(2 + (i >> 1)), pk + 32 + i * 8 + h * 4);
        }
        if (FK_ORD == 0) { wg_wait<1>(); if (q == 28 && rel) rel = BAR(0); release(B_EMPTY2 + (q - 1) % 5); STAMP2(31 + q); }
      }
    }
    if (FK_QR == 32) {
      mbar_wait(BAR(B_TAB), 0);
      wg_fence();
      wgmma_n128<0, 8>(lo, desc_lo(sb + RKA_OFF, 0) + (cwarp & 4) * 16, desc_lo(sb + RKB_OFF, 0));
      wg_commit();
    }
    const int gq = ln >> 2, q4 = ln & 3, row0 = cwarp * 16 + gq;
    const bool odd = ln & 1;
    const uint32_t role = lds32u(sb + CST_OFF + 12), bq = role & 255;
    uint32_t tq = sb + TAB_OFF + q4 * 16, tb = tq + (gq & 1) * T_ONE + (gq & 2) * (T_WL / 2);
    const uint4* src = &S->stats[((bq & ~7) + (q4 >> 1) * 4) * 128 + row0 + 8 * (q4 & 1)];
    uint4* sdst = &S->stats[bq * 128 + row0 + 8 * q4];
    asm volatile("" : "+r"(tq), "+r"(tb), "+l"(src), "+l"(sdst));
    {
      uint4 gw[4];
#pragma unroll
      for (int a = 0; a < 4; a++) gw[a] = lds128u(tq + T_GA + a * 64);
      wg_wait<0>();
      reg_fence(lo);
      STAMP(0);
      if (elect) { TRACE(7 + tr); if (cw == 0) TRACE_CLK(121); }
      float c[2][4], e0[2][4], e1[2][4];
#pragma unroll
      for (int i = 0; i < 4; i++) c[0][i] = c[1][i] = e0[0][i] = e0[1][i] = e1[0][i] = e1[1][i] = 0.f;
#pragma unroll
      for (int a = 0; a < 4; a++) {
        const uint4 bw = lds128u(tb + a * 64);
        const uint32_t g[4] = {gw[a].x, gw[a].y, gw[a].z, gw[a].w};
#pragma unroll
        for (int i = 0; i < 8; i++) xw[a * 8 + i] = fma_bf16x2(g[i >> 1], pack_bf16(lo[a * 16 + 2 * i], lo[a * 16 + 2 * i + 1]), xw[a * 8 + i]);
#pragma unroll
        for (int h = 0; h < 2; h++) {
          const uint32_t* w = xw + a * 8 + h * 4;
          mma_1688(e0[0], w[0], w[1], w[0]); mma_1688(e1[0], w[0], w[1], w[1]); mma_1688(e0[1], w[2], w[3], w[2]); mma_1688(e1[1], w[2], w[3], w[3]);
          mma_16816(c[h], w, h ? bw.z : bw.x, h ? bw.w : bw.y);
        }
      }
      const float c0 = c[0][0] + c[1][0], c2 = c[0][2] + c[1][2];
      const float q0 = (gq & 1) ? e0[0][1] + e0[1][1] : e0[0][0] + e0[1][0], q1 = (gq & 1) ? e1[0][3] + e1[1][3] : e1[0][2] + e1[1][2];
      const int dl = (ln & ~3) | (gq >> 1);
      const float da = (odd ? c2 : c0) + __shfl_xor_sync(~0u, odd ? c0 : c2, 1), s1 = __shfl_xor_sync(~0u, c[0][3] + c[1][3], 1);
      const float qa = __shfl_sync(~0u, q0, dl), qb = __shfl_sync(~0u, q1, dl);
      if (q4 < 2) st_msg(sdst, __float_as_uint(odd ? s1 : c[0][1] + c[1][1]), __float_as_uint(odd ? qb : qa), __float_as_uint(da), 0);
    }
    if (elect) TRACE(8 + tr);
    STAMP(1);
    {
      uint4 m[4], tA[4], tS[4];
      if (FK_H1 < 3) mbar_wait(BAR(B_WF), 1); else mbar_wait(BAR(B_TAB), 0);
      if (FK_H1 == 0) {
#pragma unroll
        for (int i = 0; i < 4; i++) m[i] = ld_msg(src + 128 * i);
      }
      const float2 cst = lds64(sb + CST_OFF);
      if (FK_H1 < 3) {
#pragma unroll
        for (int i = 0; i < 8; i++) ldsm_x4_t((wo ^ ((i & 1) << 5)) + (i >> 1) * 8192, uf + 32 + i * 4);
      }
      if (FK_H1 != 1) {
#pragma unroll
        for (int a = 0; a < 4; a++) { tA[a] = lds128u(tq + T_A + a * 64); tS[a] = lds128u(tq + T_S + a * 64); }
      }
      uint32_t kaddr = sb + KEY_OFF + (row0 + 8 * (q4 & 1)) * 4, kidx = 2047 - ((bq >> 3) * 128 + row0 + 8 * (q4 & 1));
      asm volatile("" : "+r"(kaddr), "+r"(kidx));
      STAMP(2);
      if (FK_H1) {
        uint32_t one;
        asm volatile("ld.volatile.shared.u32 %0, [%1];" : "=r"(one) : "r"(sb + TAB_OFF + T_ONE) : "memory");
        src += one >> 31;
#pragma unroll
        for (int i = 0; i < 4; i++) m[i] = ld_msg(src + 128 * i);
      }
      {
        int it = 0;
        while (!__all_sync(~0u, (m[0].w | m[1].w | m[2].w | m[3].w) == 0)) {
#pragma unroll
          for (int i = 0; i < 4; i++) m[i] = ld_msg(src + 128 * i);
          SPIN_CHECK(it);
        }
      }
      STAMP(3);
      float sa = (__uint_as_float(m[0].x) + __uint_as_float(m[1].x)) + (__uint_as_float(m[2].x) + __uint_as_float(m[3].x));
      float qa = (__uint_as_float(m[0].y) + __uint_as_float(m[1].y)) + (__uint_as_float(m[2].y) + __uint_as_float(m[3].y));
      float da = (__uint_as_float(m[0].z) + __uint_as_float(m[1].z)) + (__uint_as_float(m[2].z) + __uint_as_float(m[3].z));
      sa += __shfl_xor_sync(~0u, sa, 2); qa += __shfl_xor_sync(~0u, qa, 2); da += __shfl_xor_sync(~0u, da, 2);
      const float mean = sa * (1.f / D_);
      const float rs = rsqrt_f(fmaxf(fmaf(-mean, mean, qa * (1.f / D_)), 0.f) + 1e-5f);
      sts32v(kaddr, (fkey(fmaf(rs, fmaf(-mean, cst.x, da), cst.y)) & ~2047u) | kidx);
      uint32_t one;
      asm volatile("bar.arrive 5, 288;\nld.volatile.shared.u32 %0, [%1];" : "=r"(one) : "r"(sb + TAB_OFF + T_ONE) : "memory");
      if (tid == 128) TRACE(12 + 16);
      STAMP(4);
      if (FK_H1 == 1) {
#pragma unroll
        for (int a = 0; a < 4; a++) { tA[a] = lds128u(tq + T_A + a * 64); tS[a] = lds128u(tq + T_S + a * 64); }
      }
      const uint32_t h0 = pack_bf16(rs, rs), l0 = mul_bf16x2(pack_bf16(rs - bf_lo(h0), -mean * rs), one), hx = __shfl_xor_sync(~0u, h0, 1), lx = __shfl_xor_sync(~0u, l0, 1);
      const uint32_t rh[2] = {odd ? hx : h0, odd ? h0 : hx};
      const uint32_t rl[2] = {__byte_perm(odd ? lx : l0, 0, 0x1010), __byte_perm(odd ? l0 : lx, 0, 0x1010)};
      const uint32_t nm[2] = {__byte_perm(odd ? lx : l0, 0, 0x3232), __byte_perm(odd ? l0 : lx, 0, 0x3232)};
      uint32_t h[32];
#pragma unroll
      for (int a = 0; a < 4; a++) {
        const uint32_t A[4] = {tA[a].x, tA[a].y, tA[a].z, tA[a].w}, B[4] = {tS[a].x, tS[a].y, tS[a].z, tS[a].w};
#pragma unroll
        for (int i = 0; i < 8; i++) {
          const uint32_t w = xw[a * 8 + (i & 3) * 2 + (i >> 2)];
          h[a * 8 + i] = fma_bf16x2(fma_bf16x2(w, rh[i >> 2], fma_bf16x2(w, rl[i >> 2], nm[i >> 2])), A[i & 3], B[i & 3]);
        }
      }
      uint4* cp = &S->rowsH[(bq >> 3) * 256 + (bq & 7) * 16 + q4];
#pragma unroll
      for (int i = 0; i < 32; i++) asm volatile("" : "+r"(h[i]));
      asm volatile("" : "+l"(cp));
      mbar_wait(BAR(B_BK), 0);
      STAMP(5);
      const float2 bk = lds64(sb + BK_OFF);
#pragma unroll
      for (int r = 0; r < 2; r++) {
        const bool second = row0 + 8 * r == __float_as_int(bk.y);
        if (second || row0 + 8 * r == __float_as_int(bk.x)) {
#pragma unroll
          for (int a = 0; a < 4; a++) st_msg(cp + (second ? 128 : 0) + a * 4, h[a * 8 + r * 4], h[a * 8 + r * 4 + 1], h[a * 8 + r * 4 + 2], h[a * 8 + r * 4 + 3]);
        }
      }
      mbar_wait(BAR(B_DN), 0);
      if (FK_H1 == 3) {
        mbar_wait(BAR(B_WF), 1);
#pragma unroll
        for (int i = 0; i < 8; i++) ldsm_x4_t((wo ^ ((i & 1) << 5)) + (i >> 1) * 8192, uf + 32 + i * 4);
      }
#pragma unroll
      for (int a = 0; a < 4; a++) {
        const uint4 tG = lds128u(tq + T_G + a * 64);
        const uint32_t G[4] = {tG.x, tG.y, tG.z, tG.w};
#pragma unroll
        for (int i = 0; i < 8; i++) xw[a * 8 + i] = fma_bf16x2(G[i >> 1], h[a * 8 + (i & 1) * 4 + (i >> 1)], xw[a * 8 + i]);
#pragma unroll
        for (int k = 0; k < 2; k++) stsm_x4((so ^ ((((a & 1) * 2) + k) << 5)) + E_OFF + cwarp * 2048 + (a >> 1) * 2048, xw + a * 8 + k * 4);
      }
    }
    fence_async_smem();
    if (elect_one()) mbar_arrive(BAR(B_PREADY));
    STAMP(6);
    if (tid == 128) TRACE(15);
    if (role >> 16) {
      const char* hp = reinterpret_cast<const char*>(&S->rowsH[(cwarp >> 1) * 4 + q4]) + (cwarp & 1) * 8;
      uint32_t db = sb + DN_OFF + (cwarp + (cwarp == 7) * 4) * 8192 + ((ln & 7) + (ln >> 4) * 8) * 128 + ((((ln >> 3) & 1) ^ (ln & 7)) << 4), sa = sb + SEL_OFF + 8 + (gq & 1) * 4;
      const uint32_t ha = sb + H_OFF + (gq & 1) * 2112 + ((cwarp >> 1) * 4 + q4) * 16 + (cwarp & 1) * 8;
#pragma unroll
      for (int i = 0; i < 16; i++) ldsm_x4_t((db ^ (((i >> 1) & 3) << 5)) + (i >> 3) * 4096 + (i & 1) * 2048, df + i * 4);
      STAMP(7);
      mbar_wait(BAR(B_ROWS), 0);
      STAMP(8);
      uint2 hb[8];
#pragma unroll
      for (int i = 0; i < 8; i++) { const float2 v = lds64(ha + i * 256); hb[i] = make_uint2(__float_as_uint(v.x), __float_as_uint(v.y)); }
      STAMP(9);
      int it = 0;
      while (!__all_sync(~0u, max(max(max(hb[0].x, hb[1].x), max(hb[2].x, hb[3].x)), max(max(hb[4].x, hb[5].x), max(hb[6].x, hb[7].x))) != SENT)) {
#pragma unroll
        for (int i = 0; i < 8; i++) hb[i] = ld_msg8(hp + lds32u(sa) + i * 256);
        SPIN_CHECK(it);
      }
      if (tid == 128) TRACE(16);
      STAMP(10);
      float c[4][4];
#pragma unroll
      for (int i = 0; i < 4; i++) c[i][0] = c[i][1] = c[i][2] = c[i][3] = 0.f;
#pragma unroll
      for (int ks = 0; ks < 8; ks++) {
        const uint32_t b0 = hb[ks].x, b1 = hb[ks].y;
        mma_16816(c[0], wf + ks * 8, b0, b1); mma_16816(c[1], wf + ks * 8 + 4, b0, b1);
        mma_16816(c[2], uf + ks * 8, b0, b1); mma_16816(c[3], uf + ks * 8 + 4, b0, b1);
      }
      {
        float v[4];
#pragma unroll
        for (int i = 0; i < 4; i++) v[i] = (q4 & 2) ? (odd ? c[3][i] : c[2][i]) : (odd ? c[1][i] : c[0][i]);
        sts128(sb + RED_OFF + cwarp * 512 + (q4 * 8 + (gq ^ (q4 * 2))) * 16, v[0], v[2], v[1], v[3]);
      }
      uint2* pp = reinterpret_cast<uint2*>(&S->part[((cwarp * 16 + q4 * 2) * 128 + ((role >> 8) & 255)) * 4]) + gq;
      uint32_t ra = sb + RED_OFF + ((ln * 8) ^ ((ln & 16) * 2));
      asm volatile("" : "+l"(pp), "+r"(ra));
      STAMP(11);
      named_bar<2, 256>();
      STAMP(12);
      float g0 = 0.f, g1 = 0.f, u0 = 0.f, u1 = 0.f;
#pragma unroll
      for (int w = 0; w < 8; w++) {
        const float2 gv = lds64(ra + w * 512), uv = lds64((ra ^ 64) + w * 512 + 256);
        g0 += gv.x; g1 += gv.y; u0 += uv.x; u1 += uv.y;
      }
      const uint32_t gp = pack_bf16(g0, g1), up = pack_bf16(u0, u1), sp = pack_bf16(silu_f(bf_lo(gp)), silu_f(bf_hi(gp)));
      const uint32_t act = pack_bf16(bf_lo(sp) * bf_lo(up), bf_hi(sp) * bf_hi(up));
      uint32_t ab[4];
#pragma unroll
      for (int i = 0; i < 4; i++) ab[i] = __shfl_sync(~0u, act, i * 8 + q4 * 2 + (gq & 1));
      if (tid == 128) TRACE(31);
      STAMP(13);
#pragma unroll
      for (int T = 0; T < 2; T++) {
#pragma unroll
        for (int i = 0; i < 4; i++) {
          c[i][0] = c[i][1] = c[i][2] = c[i][3] = 0.f;
          mma_16816(c[i], df + (T * 4 + i) * 8, ab[0], ab[1]); mma_16816(c[i], df + (T * 4 + i) * 8 + 4, ab[2], ab[3]);
        }
        float v[4];
#pragma unroll
        for (int i = 0; i < 4; i++) v[i] = (q4 & 2) ? (odd ? c[3][i] : c[2][i]) : (odd ? c[1][i] : c[0][i]);
        st_msg8(pp + T * 8192, __float_as_uint(v[0]), __float_as_uint(v[2])); st_msg8(pp + T * 8192 + 1024, __float_as_uint(v[1]), __float_as_uint(v[3]));
      }
      if (tid == 128) TRACE(32);
      STAMP(14);
    }
    if (cwarp == 0) {
      const unsigned t0 = clk32();
      mbar_wait(BAR(B_FIN), 0);
      const int fc = q4 * 2 + ((ln >> 2) & 1) + (ln & 8);
      const float2 fo = lds64(sb + PFLAG_OFF + fc * 8);
      const float sg = __uint_as_float(lds32u(sb + CST_OFF));
      __nv_bfloat16* op = out + (size_t)lds32u(sb + SEL_OFF + (bq & 1) * 4) * D_ + (bq >> 1) * 16 + fc;
      const uint4* ip = &S->part[bq * 512 + ln];
      asm volatile("" : "+l"(op), "+l"(ip));
      if (role >> 16) { while (clk32() - t0 < FK_PDELAY) {} } else spin(FK_PDELAY + 600);
      int it = 0;
      uint4 m[14];
      while (true) {
        bool ok = true;
#pragma unroll
        for (int i = 0; i < 14; i++) { m[i] = ld_msg(ip + i * 32); ok &= m[i].x != SENT && m[i].z != SENT; }
        if (__all_sync(~0u, ok)) break;
        SPIN_CHECK(it);
      }
      if (lane == 0) TRACE(33);
      STAMP(15);
      float y[4] = {0.f, 0.f, 0.f, 0.f};
#pragma unroll
      for (int i = 0; i < 14; i++) { y[0] += __uint_as_float(m[i].x); y[1] += __uint_as_float(m[i].y); y[2] += __uint_as_float(m[i].z); y[3] += __uint_as_float(m[i].w); }
      const bool b2 = ln & 4;
      float y0 = (b2 ? y[2] : y[0]) + __shfl_xor_sync(~0u, b2 ? y[0] : y[2], 4), y1 = (b2 ? y[3] : y[1]) + __shfl_xor_sync(~0u, b2 ? y[1] : y[3], 4);
      y0 = ((ln & 8) ? y1 : y0) + __shfl_xor_sync(~0u, (ln & 8) ? y0 : y1, 8);
      y0 += __shfl_xor_sync(~0u, y0, 16);
      const float upd = round_bf16(round_bf16(y0) * sg);
      if (ln < 16) *op = __float2bfloat16_rn(fmaf(fo.y, upd, fo.x));
      if (lane == 0) {
        TRACE(34); TRACE_CLK(122);
      }
    }
  }
}

typedef CUresult (*PFN_encodeTiled)(CUtensorMap*, CUtensorMapDataType, cuuint32_t, void*, const cuuint64_t*, const cuuint64_t*,
                                    const cuuint32_t*, const cuuint32_t*, CUtensorMapInterleave, CUtensorMapSwizzle,
                                    CUtensorMapL2promotion, CUtensorMapFloatOOBfill);

static void mapnd(PFN_encodeTiled enc, CUtensorMap* m, const void* p, int nd, const cuuint64_t* dims, const cuuint64_t* str, const cuuint32_t* box,
                  CUtensorMapSwizzle sw, CUtensorMapL2promotion pr) {
  const cuuint32_t es[5] = {1, 1, 1, 1, 1};
  enc(m, CU_TENSOR_MAP_DATA_TYPE_BFLOAT16, nd, (void*)p, dims, str, box, es, CU_TENSOR_MAP_INTERLEAVE_NONE, sw, pr, CU_TENSOR_MAP_FLOAT_OOB_FILL_NONE);
}
static void map2d(PFN_encodeTiled enc, CUtensorMap* m, const void* p, uint64_t rows, uint64_t cols, uint32_t brows, uint32_t bcols,
                  CUtensorMapSwizzle sw = CU_TENSOR_MAP_SWIZZLE_128B, CUtensorMapL2promotion pr = CU_TENSOR_MAP_L2_PROMOTION_L2_128B) {
  const cuuint64_t dims[2] = {cols, rows}, str[1] = {cols * 2}; const cuuint32_t box[2] = {bcols, brows};
  mapnd(enc, m, p, 2, dims, str, box, sw, pr);
}
static void map3d(PFN_encodeTiled enc, CUtensorMap* m, const void* p, uint64_t rows, uint64_t cols, uint32_t brows, uint32_t bgroups) {
  const cuuint64_t dims[3] = {64, rows, cols / 64}, str[2] = {cols * 2, 128}; const cuuint32_t box[3] = {64, brows, bgroups};
  mapnd(enc, m, p, 3, dims, str, box, CU_TENSOR_MAP_SWIZZLE_128B, CU_TENSOR_MAP_L2_PROMOTION_L2_128B);
}

}

extern "C" void kernel_launch(void* const* d_in, const int* in_sizes, int n_in, void* d_out, int out_size) {
  using namespace fk;
  (void)in_sizes; (void)n_in; (void)out_size;
  static PFN_encodeTiled enc = nullptr;
  static Scratch* scr = nullptr;
  if (!enc) {
    void* fn = nullptr; cudaDriverEntryPointQueryResult qr;
    cudaGetDriverEntryPoint("cuTensorMapEncodeTiled", &fn, cudaEnableDefault, &qr);
    enc = (PFN_encodeTiled)fn;
    cudaGetSymbolAddress((void**)&scr, g_scr);
    cudaFuncSetAttribute(fused_kernel, cudaFuncAttributeMaxDynamicSharedMemorySize, SMEM_BYTES);
  }
  typedef const __nv_bfloat16* bp;
  Params prm;
  prm.w_r = (bp)d_in[6];
  prm.wsp[0] = (const char*)d_in[1]; prm.wsp[1] = (const char*)d_in[2];
  map2d(enc, &prm.ws[0], d_in[1], S_, S_, 128, 64);
  map2d(enc, &prm.ws[1], d_in[2], S_, S_, 128, 64);
  map3d(enc, &prm.n, scr->n, S_, D_, 64, 2);
  map2d(enc, &prm.wm, d_in[11], D_, 6 * D_, 8, 256, CU_TENSOR_MAP_SWIZZLE_NONE, CU_TENSOR_MAP_L2_PROMOTION_L2_256B);
  map2d(enc, &prm.p, scr->P, 2 * S_, D_, 128, 64);
  map2d(enc, &prm.wd[0], d_in[3], D_, D_, 64, 64);
  map2d(enc, &prm.wd[1], d_in[4], D_, D_, 64, 64);
  map2d(enc, &prm.wg, d_in[7], D_, F_, 128, 32, CU_TENSOR_MAP_SWIZZLE_64B);
  map2d(enc, &prm.wu, d_in[8], D_, F_, 128, 32, CU_TENSOR_MAP_SWIZZLE_64B);
  for (int i = 0; i < 3; i++) prm.we[i] = (const char*)d_in[7 + i];
  map2d(enc, &prm.ps, scr->P, 2 * S_, D_, 32, 64);
  for (int i = 0; i < 2; i++) {
    const cuuint64_t dims[3] = {128, 8, i ? 2048u : 3584u}, str[2] = {256, 2048}; const cuuint32_t box[3] = {8, 1, 32};
    mapnd(enc, &prm.tch[i], d_in[i ? 0 : 9], 3, dims, str, box, CU_TENSOR_MAP_SWIZZLE_NONE, CU_TENSOR_MAP_L2_PROMOTION_L2_256B);
  }
  map3d(enc, &prm.xb, d_in[0], S_, D_, 64, 2);
  map3d(enc, &prm.xm, d_in[0], S_, D_, 16, 2);
  map3d(enc, &prm.om, d_out, S_, D_, 16, 2);
  {
    const cuuint64_t dims[5] = {64, 2, 8, 224, 16}, str[4] = {8 * 2048, 2048, 16 * 2048, 128}; const cuuint32_t box[5] = {64, 2, 8, 2, 2};
    mapnd(enc, &prm.wdn, d_in[9], 5, dims, str, box, CU_TENSOR_MAP_SWIZZLE_128B, CU_TENSOR_MAP_L2_PROMOTION_L2_128B);
  }

  fused_kernel<<<NCTA, 384, SMEM_BYTES, cudaStreamPerThread>>>((bp)d_in[0], scr, (__nv_bfloat16*)d_out, (bp)d_in[10], (bp)d_in[3], (bp)d_in[4], prm);
}
```
